```python
import torch

def _softmax(x, axis=-1):
    return torch.softmax(x, dim=axis)
def _gelu(x):
    return torch.nn.functional.gelu(x, approximate="tanh")
def _silu(x):
    return torch.nn.functional.silu(x)
def _sigmoid(x):
    return torch.sigmoid(x)
def _layernorm(x, axis=-1, eps=1e-5):
    m = x.mean(dim=axis, keepdim=True)
    v = x.var(dim=axis, keepdim=True, unbiased=False)
    return (x - m) / torch.sqrt(v + eps)
def _scatter_add(tgt, idx, src, axis=0):
    return tgt.clone().index_add_(axis, idx, src)
def _segment_sum(src, seg, n):
    out = torch.zeros((n,) + src.shape[1:], dtype=src.dtype)
    return out.index_add_(0, seg, src)
def _pad(x, pw):
    flat = tuple(v for pair in reversed(pw) for v in pair)
    return torch.nn.functional.pad(x, flat)

kernel_name = 'gated_mix__linear_kernel_hedgehog__moe_arch_mod__prompt'

def setup_inputs():

    _w = (lambda a: (lambda t: t.to(torch.bfloat16) if t.is_floating_point() else t)(torch.as_tensor(a)))
    def _A_setup():
        B, S, D, H = 1, 2048, 1024, 32
        Dh = D // H
        return {
            "x": _w((lambda *s: torch.randn(*s, dtype=torch.bfloat16) * 0.05)(B, S, D)),
            "wqkv": _w((lambda *s: torch.randn(*s, dtype=torch.bfloat16) * 1.6)(D, 3 * D)),
            "w_phi": _w((lambda *s: torch.randn(*s, dtype=torch.bfloat16) * 1.6)(H, Dh, Dh) * (Dh ** -0.5)),
            "wo": _w((lambda *s: torch.randn(*s, dtype=torch.bfloat16) * 1.6)(D, D)),
        }
    _A_in = _A_setup()

    def _B_setup():
        B, S, D, F, C = 1, 2048, 1024, 3584, 1
        return {
            "x": _w((lambda *s: torch.randn(*s, dtype=torch.bfloat16) * 0.05)(B, S, D)),
            "w_r": _w((lambda *s: torch.randn(*s, dtype=torch.bfloat16) * 1.6)(D)),
            "w_gate": _w((lambda *s: torch.randn(*s, dtype=torch.bfloat16) * 0.8)(D, F)),
            "w_up": _w((lambda *s: torch.randn(*s, dtype=torch.bfloat16) * 0.8)(D, F)),
            "w_down": _w((lambda *s: torch.randn(*s, dtype=torch.bfloat16) * 0.8)(F, D)),
        }
    _B_in = _B_setup()

    return {
        "A_x": _A_in["x"],
        "A_wqkv": _A_in["wqkv"],
        "A_w_phi": _A_in["w_phi"],
        "A_wo": _A_in["wo"],
        "B_x": _B_in["x"],
        "B_w_r": _B_in["w_r"],
        "B_w_gate": _B_in["w_gate"],
        "B_w_up": _B_in["w_up"],
        "B_w_down": _B_in["w_down"],
        "gate_w": _w((lambda *s: torch.randn(*s, dtype=torch.bfloat16) * 0.05)(1024) * 16.0),
    }

def reference(A_x, A_wqkv, A_w_phi, A_wo, B_x, B_w_r, B_w_gate, B_w_up, B_w_down, gate_w):
    def _A_ref(x, wqkv, w_phi, wo):
        B, S, D = x.shape
        H = 32; Dh = D // H
        qkv = (lambda x, *d: x.permute(*d))((x @ wqkv).reshape(B, S, 3, H, Dh), 2, 0, 3, 1, 4)
        q, k, v = qkv[0], qkv[1], qkv[2]
        pq = torch.einsum("bhsd,hdf->bhsf", q, w_phi)
        pk = torch.einsum("bhsd,hdf->bhsf", k, w_phi)
        phi_q = torch.concatenate([_softmax(pq, axis=-1), _softmax(-pq, axis=-1)], axis=-1)
        phi_k = torch.concatenate([_softmax(pk, axis=-1), _softmax(-pk, axis=-1)], axis=-1)
        kv = torch.einsum("bhsf,bhsd->bhfd", phi_k, v)
        z  = torch.einsum("bhsf->bhf", phi_k)
        num = torch.einsum("bhqf,bhfd->bhqd", phi_q, kv)
        den = torch.einsum("bhqf,bhf->bhq", phi_q, z)[..., None] + 1e-6
        o = num / den
        return (lambda x, *d: x.permute(*d))(o, 0, 2, 1, 3).reshape(B, S, D) @ wo

    def _B_ref(x, w_r, w_gate, w_up, w_down):
        B, S, D = x.shape
        C = 1
        r = x @ w_r
        idx = torch.argsort(-r, axis=-1)[:, :C]
        idx_e = (lambda x, n, axis: torch.repeat_interleave(x, n, dim=axis))(idx.reshape(B, C, 1), D, axis=2)
        x_sel = (lambda x, i, axis: torch.take_along_dim(x, i, dim=axis))(x, idx_e, axis=1)
        g = _silu(x_sel @ w_gate)
        u = x_sel @ w_up
        y = (g * u) @ w_down
        r_sel = _sigmoid((lambda x, i, axis: torch.take_along_dim(x, i, dim=axis))(r, idx, axis=1))
        y = y * r_sel.reshape(B, C, 1)
        b_off = (torch.arange(B) * S).reshape(B, 1)
        flat_idx = (idx + b_off).reshape(B * C)
        zero = (x * 0.0).reshape(B * S, D)
        upd = _scatter_add(zero, flat_idx, y.reshape(B * C, D), axis=0)
        return x + upd.reshape(B, S, D)

    x = A_x
    g = _sigmoid((x * gate_w).sum(-1, keepdims=True))
    a = _A_ref(x, A_wqkv, A_w_phi, A_wo)
    b = _B_ref(x, B_w_r, B_w_gate, B_w_up, B_w_down)
    return g * a + (1 - g) * b
```

```cpp
#include <cuda_runtime.h>
#include <cuda_bf16.h>
#include <cuda.h>
#include <stdint.h>

__device__ __forceinline__ uint32_t smem_u32(const void* p) { return (uint32_t)__cvta_generic_to_shared(p); }
__device__ __forceinline__ void mbar_init(uint32_t bar, uint32_t cnt) { asm volatile("mbarrier.init.shared::cta.b64 [%0], %1;" :: "r"(bar), "r"(cnt) : "memory"); }
__device__ __forceinline__ void mbar_expect_tx(uint32_t bar, uint32_t bytes) { asm volatile("mbarrier.arrive.expect_tx.shared::cta.b64 _, [%0], %1;" :: "r"(bar), "r"(bytes) : "memory"); }
__device__ __forceinline__ void mbar_arrive(uint32_t bar) { asm volatile("mbarrier.arrive.shared::cta.b64 _, [%0];" :: "r"(bar) : "memory"); }
__device__ __forceinline__ bool mbar_try_wait(uint32_t bar, uint32_t parity) {
  uint32_t ok;
  asm volatile("{\n.reg .pred p;\nmbarrier.try_wait.parity.shared::cta.b64 p, [%1], %2;\nselp.u32 %0, 1, 0, p;\n}" : "=r"(ok) : "r"(bar), "r"(parity) : "memory");
  return ok;
}
__device__ __forceinline__ bool mbar_test(uint32_t bar, uint32_t parity) {
  uint32_t ok;
  asm volatile("{\n.reg .pred p;\nmbarrier.test_wait.parity.shared::cta.b64 p, [%1], %2;\nselp.u32 %0, 1, 0, p;\n}" : "=r"(ok) : "r"(bar), "r"(parity) : "memory");
  return ok;
}
__device__ __forceinline__ void mbar_wait(uint32_t bar, uint32_t parity) {
#pragma unroll 1
  for (int it = 0; it < (1 << 22); it++) { if (mbar_try_wait(bar, parity)) return; }
  __trap();
}
__device__ __forceinline__ void tma_load_2d(uint32_t dst, const CUtensorMap* tm, int c0, int c1, uint32_t bar) {
  asm volatile("cp.async.bulk.tensor.2d.shared::cluster.global.mbarrier::complete_tx::bytes [%0], [%1, {%3, %4}], [%2];"
    :: "r"(dst), "l"(tm), "r"(bar), "r"(c0), "r"(c1) : "memory");
}
__device__ __forceinline__ void tma_load_2d_mc(uint32_t dst, const CUtensorMap* tm, int c0, int c1, uint32_t bar) {
  asm volatile("cp.async.bulk.tensor.2d.shared::cluster.global.mbarrier::complete_tx::bytes.multicast::cluster [%0], [%1, {%3, %4}], [%2], %5;"
    :: "r"(dst), "l"(tm), "r"(bar), "r"(c0), "r"(c1), "h"((uint16_t)3) : "memory");
}
__device__ __forceinline__ void mbar_arrive_cluster(uint32_t bar) { asm volatile("mbarrier.arrive.shared::cluster.b64 _, [%0];" :: "r"(bar) : "memory"); }
__device__ __forceinline__ void wgmma_fence() { asm volatile("wgmma.fence.sync.aligned;" ::: "memory"); }
__device__ __forceinline__ void wgmma_commit() { asm volatile("wgmma.commit_group.sync.aligned;" ::: "memory"); }
template <int N> __device__ __forceinline__ void wgmma_wait() { asm volatile("wgmma.wait_group.sync.aligned %0;" :: "n"(N) : "memory"); }
template <int N> __device__ __forceinline__ void fence_regs(float (&d)[N]) {
#pragma unroll
  for (int i = 0; i < N; i++) asm volatile("" : "+f"(d[i]) :: "memory");
}
__host__ __device__ constexpr uint32_t dlo(uint32_t addr, uint32_t lbo) { return (addr >> 4) | ((lbo >> 4) << 16); }
constexpr uint32_t H128 = (1024 >> 4) | (1u << 30);
constexpr uint32_t H64 = (512 >> 4) | (2u << 30);

template <int TA, int TB, uint32_t HA, uint32_t HB>
__device__ __forceinline__ void wgmma_ss_n192(float (&d)[96], uint32_t da, uint32_t db, int scale_d) {
  asm volatile("{\n.reg .pred p;\n.reg .b64 da, db;\nsetp.ne.b32 p, %98, 0;\nmov.b64 da, {%96, %101};\nmov.b64 db, {%97, %102};\n"
    "wgmma.mma_async.sync.aligned.m64n192k16.f32.bf16.bf16 {%0, %1, %2, %3, %4, %5, %6, %7, %8, %9, %10, %11, %12, %13, %14, %15, %16, %17, %18, %19, %20, %21, %22, %23, %24, %25, %26, %27, %28, %29, %30, %31, %32, %33, %34, %35, %36, %37, %38, %39, %40, %41, %42, %43, %44, %45, %46, %47, %48, %49, %50, %51, %52, %53, %54, %55, %56, %57, %58, %59, %60, %61, %62, %63, %64, %65, %66, %67, %68, %69, %70, %71, %72, %73, %74, %75, %76, %77, %78, %79, %80, %81, %82, %83, %84, %85, %86, %87, %88, %89, %90, %91, %92, %93, %94, %95}, da, db, p, 1, 1, %99, %100;\n}\n"
    : "+f"(d[0]), "+f"(d[1]), "+f"(d[2]), "+f"(d[3]), "+f"(d[4]), "+f"(d[5]), "+f"(d[6]), "+f"(d[7]), "+f"(d[8]), "+f"(d[9]), "+f"(d[10]), "+f"(d[11]), "+f"(d[12]), "+f"(d[13]), "+f"(d[14]), "+f"(d[15]), "+f"(d[16]), "+f"(d[17]), "+f"(d[18]), "+f"(d[19]), "+f"(d[20]), "+f"(d[21]), "+f"(d[22]), "+f"(d[23]), "+f"(d[24]), "+f"(d[25]), "+f"(d[26]), "+f"(d[27]), "+f"(d[28]), "+f"(d[29]), "+f"(d[30]), "+f"(d[31]), "+f"(d[32]), "+f"(d[33]), "+f"(d[34]), "+f"(d[35]), "+f"(d[36]), "+f"(d[37]), "+f"(d[38]), "+f"(d[39]), "+f"(d[40]), "+f"(d[41]), "+f"(d[42]), "+f"(d[43]), "+f"(d[44]), "+f"(d[45]), "+f"(d[46]), "+f"(d[47]), "+f"(d[48]), "+f"(d[49]), "+f"(d[50]), "+f"(d[51]), "+f"(d[52]), "+f"(d[53]), "+f"(d[54]), "+f"(d[55]), "+f"(d[56]), "+f"(d[57]), "+f"(d[58]), "+f"(d[59]), "+f"(d[60]), "+f"(d[61]), "+f"(d[62]), "+f"(d[63]), "+f"(d[64]), "+f"(d[65]), "+f"(d[66]), "+f"(d[67]), "+f"(d[68]), "+f"(d[69]), "+f"(d[70]), "+f"(d[71]), "+f"(d[72]), "+f"(d[73]), "+f"(d[74]), "+f"(d[75]), "+f"(d[76]), "+f"(d[77]), "+f"(d[78]), "+f"(d[79]), "+f"(d[80]), "+f"(d[81]), "+f"(d[82]), "+f"(d[83]), "+f"(d[84]), "+f"(d[85]), "+f"(d[86]), "+f"(d[87]), "+f"(d[88]), "+f"(d[89]), "+f"(d[90]), "+f"(d[91]), "+f"(d[92]), "+f"(d[93]), "+f"(d[94]), "+f"(d[95])
    : "r"(da), "r"(db), "r"(scale_d), "n"(TA), "n"(TB), "n"(HA), "n"(HB));
}

template <int TA, int TB, uint32_t HA, uint32_t HB>
__device__ __forceinline__ void wgmma_ss_n128(float (&d)[64], uint32_t da, uint32_t db, int scale_d) {
  asm volatile("{\n.reg .pred p;\n.reg .b64 da, db;\nsetp.ne.b32 p, %66, 0;\nmov.b64 da, {%64, %69};\nmov.b64 db, {%65, %70};\n"
    "wgmma.mma_async.sync.aligned.m64n128k16.f32.bf16.bf16 {%0, %1, %2, %3, %4, %5, %6, %7, %8, %9, %10, %11, %12, %13, %14, %15, %16, %17, %18, %19, %20, %21, %22, %23, %24, %25, %26, %27, %28, %29, %30, %31, %32, %33, %34, %35, %36, %37, %38, %39, %40, %41, %42, %43, %44, %45, %46, %47, %48, %49, %50, %51, %52, %53, %54, %55, %56, %57, %58, %59, %60, %61, %62, %63}, da, db, p, 1, 1, %67, %68;\n}\n"
    : "+f"(d[0]), "+f"(d[1]), "+f"(d[2]), "+f"(d[3]), "+f"(d[4]), "+f"(d[5]), "+f"(d[6]), "+f"(d[7]), "+f"(d[8]), "+f"(d[9]), "+f"(d[10]), "+f"(d[11]), "+f"(d[12]), "+f"(d[13]), "+f"(d[14]), "+f"(d[15]), "+f"(d[16]), "+f"(d[17]), "+f"(d[18]), "+f"(d[19]), "+f"(d[20]), "+f"(d[21]), "+f"(d[22]), "+f"(d[23]), "+f"(d[24]), "+f"(d[25]), "+f"(d[26]), "+f"(d[27]), "+f"(d[28]), "+f"(d[29]), "+f"(d[30]), "+f"(d[31]), "+f"(d[32]), "+f"(d[33]), "+f"(d[34]), "+f"(d[35]), "+f"(d[36]), "+f"(d[37]), "+f"(d[38]), "+f"(d[39]), "+f"(d[40]), "+f"(d[41]), "+f"(d[42]), "+f"(d[43]), "+f"(d[44]), "+f"(d[45]), "+f"(d[46]), "+f"(d[47]), "+f"(d[48]), "+f"(d[49]), "+f"(d[50]), "+f"(d[51]), "+f"(d[52]), "+f"(d[53]), "+f"(d[54]), "+f"(d[55]), "+f"(d[56]), "+f"(d[57]), "+f"(d[58]), "+f"(d[59]), "+f"(d[60]), "+f"(d[61]), "+f"(d[62]), "+f"(d[63])
    : "r"(da), "r"(db), "r"(scale_d), "n"(TA), "n"(TB), "n"(HA), "n"(HB));
}

template <int TA, int TB, uint32_t HA, uint32_t HB>
__device__ __forceinline__ void wgmma_ss_n40(float (&d)[20], uint32_t da, uint32_t db, int scale_d) {
  asm volatile("{\n.reg .pred p;\n.reg .b64 da, db;\nsetp.ne.b32 p, %22, 0;\nmov.b64 da, {%20, %25};\nmov.b64 db, {%21, %26};\n"
    "wgmma.mma_async.sync.aligned.m64n40k16.f32.bf16.bf16 {%0, %1, %2, %3, %4, %5, %6, %7, %8, %9, %10, %11, %12, %13, %14, %15, %16, %17, %18, %19}, da, db, p, 1, 1, %23, %24;\n}\n"
    : "+f"(d[0]), "+f"(d[1]), "+f"(d[2]), "+f"(d[3]), "+f"(d[4]), "+f"(d[5]), "+f"(d[6]), "+f"(d[7]), "+f"(d[8]), "+f"(d[9]), "+f"(d[10]), "+f"(d[11]), "+f"(d[12]), "+f"(d[13]), "+f"(d[14]), "+f"(d[15]), "+f"(d[16]), "+f"(d[17]), "+f"(d[18]), "+f"(d[19])
    : "r"(da), "r"(db), "r"(scale_d), "n"(TA), "n"(TB), "n"(HA), "n"(HB));
}

template <int TB, uint32_t HB>
__device__ __forceinline__ void wgmma_rs_n32(float (&d)[16], uint32_t a0, uint32_t a1, uint32_t a2, uint32_t a3, uint32_t db, int scale_d) {
  asm volatile("{\n.reg .pred p;\n.reg .b64 db;\nsetp.ne.b32 p, %21, 0;\nmov.b64 db, {%20, %23};\n"
    "wgmma.mma_async.sync.aligned.m64n32k16.f32.bf16.bf16 {%0, %1, %2, %3, %4, %5, %6, %7, %8, %9, %10, %11, %12, %13, %14, %15}, {%16, %17, %18, %19}, db, p, 1, 1, %22;\n}\n"
    : "+f"(d[0]), "+f"(d[1]), "+f"(d[2]), "+f"(d[3]), "+f"(d[4]), "+f"(d[5]), "+f"(d[6]), "+f"(d[7]), "+f"(d[8]), "+f"(d[9]), "+f"(d[10]), "+f"(d[11]), "+f"(d[12]), "+f"(d[13]), "+f"(d[14]), "+f"(d[15])
    : "r"(a0), "r"(a1), "r"(a2), "r"(a3), "r"(db), "r"(scale_d), "n"(TB), "n"(HB));
}

template <int TB, uint32_t HB>
__device__ __forceinline__ void wgmma_rs_n40(float (&d)[20], uint32_t a0, uint32_t a1, uint32_t a2, uint32_t a3, uint32_t db, int scale_d) {
  asm volatile("{\n.reg .pred p;\n.reg .b64 db;\nsetp.ne.b32 p, %25, 0;\nmov.b64 db, {%24, %27};\n"
    "wgmma.mma_async.sync.aligned.m64n40k16.f32.bf16.bf16 {%0, %1, %2, %3, %4, %5, %6, %7, %8, %9, %10, %11, %12, %13, %14, %15, %16, %17, %18, %19}, {%20, %21, %22, %23}, db, p, 1, 1, %26;\n}\n"
    : "+f"(d[0]), "+f"(d[1]), "+f"(d[2]), "+f"(d[3]), "+f"(d[4]), "+f"(d[5]), "+f"(d[6]), "+f"(d[7]), "+f"(d[8]), "+f"(d[9]), "+f"(d[10]), "+f"(d[11]), "+f"(d[12]), "+f"(d[13]), "+f"(d[14]), "+f"(d[15]), "+f"(d[16]), "+f"(d[17]), "+f"(d[18]), "+f"(d[19])
    : "r"(a0), "r"(a1), "r"(a2), "r"(a3), "r"(db), "r"(scale_d), "n"(TB), "n"(HB));
}

constexpr int S_ = 2048, D_ = 1024, F_ = 3584;
constexpr int NCTA = 128;
#define NMOE_ 112
constexpr int NMOE = NMOE_;
constexpr int KVH = 5 * 128 * 4;

#define NY 8
struct Zeroed {
  float kv[32 * KVH];
  float y[NY * 2 * D_];
  unsigned hint[512];
  unsigned done[128];
  unsigned pad[384];
};
constexpr int ZB = KVH + 32 + NY * 64;
static_assert(sizeof(Zeroed) == NCTA * ZB, "zeroed block");
__device__ __align__(128) Zeroed g_z;
__device__ __align__(128) unsigned g_key[4 * NCTA];
__device__ __align__(128) unsigned g_ready[NCTA];
__device__ __align__(128) uint2 g_bcast[2 * 8 * 16];
__device__ __align__(128) unsigned g_gate[S_];
__device__ __align__(1024) __nv_bfloat16 g_o[S_ * D_];
#define TSTAMP(i)
#define GSTAMP(i)

constexpr int STAGES = 6, KT = 32;
constexpr int A_BYTES = 256 * 64, B_BYTES = 192 * 64, STAGE_BYTES = A_BYTES + B_BYTES;
constexpr int SM_RA = 0;
constexpr int SM_RB = STAGES * A_BYTES;
constexpr int SM_PHIK = 0;
constexpr int SM_V = 65536;
constexpr int SM_O = SM_V;
constexpr int NA2 = 5, NB2 = 7;
#define XT_IN_A 1
constexpr int SM_XT = (XT_IN_A ? SM_RA : SM_RB) + 2 * 16384;
constexpr int SM_XR = STAGES * STAGE_BYTES;
constexpr int SM_MOE = SM_XR;
constexpr int SM_XSEL = SM_XR + 36864;
constexpr int SM_RED = SM_XSEL + 2048;
constexpr int SM_WPHI = 212992;
constexpr int SM_KVB = SM_WPHI + 4096;
constexpr int SM_ONES = SM_KVB + 12288;
constexpr int SM_BAR = SM_ONES + 1024;
constexpr int SM_INFO = SM_BAR + 1008;
constexpr int SM_GATE = SM_BAR + 1024;
constexpr int SM_UPD = SM_GATE + 512;
constexpr int SM_TS = SM_UPD + 256;
constexpr int SM_TOTAL = SM_TS + 256;
static_assert(SM_TOTAL <= 232448 && ZB <= 4608, "smem");
static_assert(SM_WPHI % 1024 == 0 && SM_KVB % 1024 == 0 && SM_ONES % 1024 == 0, "align");
static_assert(SM_MOE + 40960 <= SM_WPHI && SM_RB + NB2 * 16384 <= SM_WPHI, "map");
#define QUAD 1
#define EXPT 0
#define PF_START 0
#define PF_OFF 0
#define KV_DELAY 1100
#define O_YIELD 1
#define TAILV -1
#define NFIRST 5
#define Q_AFTER B_PHI + 1
#define LEAD2 4
#define EVEN_FFN 1
#define KEY_SLEEP 0
#define B5_AFTER B_F2 + 2
#define REG_C 192
#define REG_K 88
#define STR2(x) #x
#define STR(x) STR2(x)
#define XT_H 0
#define EARLY_MAP 1
#define TILE_MODE 1
#define NPRE 1
#define O_OVL 1
#define LATE_SZ 8192
#define LATE_SLEEP 0
#define URG_STEP 0
#define LEAD_AT 1
#define XR_AFTER 3
#define LATE_DELAY 300
#define LATE_STEP 400

constexpr int B_FULL = 0, B_XR = 6, B_WPHI = 10;
constexpr int B_EMPTY = 11, B_XRD = 17;
constexpr int B_INIT = 123;
constexpr int B_ST = 18, B_MOE = 20, B_XSEL = 24, B_H = 25, B_RDY = 26, B_Y = 27, B_XT = 28, B_PEER = 30;
constexpr int B_FB2 = 31, B_F2 = 47;
constexpr int B_DB = 79;
constexpr int B_GO = 95;
constexpr int B_KVB = 111, B_OP = 112, B_MOEE = 116;
constexpr int B_PHI = 120, B_XTD = 122;
constexpr int NBAR = 123;
__host__ __device__ constexpr int bar_count(int i) {
  return (LEAD2 && i == B_F2 + 32 - LEAD2) ? 2 : i < B_DB ? 1 : i < B_GO ? 2 : (XT_IN_A && i == B_GO + 3) ? 9 : i < B_GO + NA2 ? 1 : i == B_GO + NA2 ? 5 : i < B_KVB ? 3 : i < B_PHI ? 4 : 8;
}

struct Maps { CUtensorMap x, w, wo, wphi, wg, wu, wd, tg, tu, td, to, xr, xt, out; int tile[NCTA / 2 + 1]; };

__device__ __forceinline__ uint32_t pack_bf16(float lo, float hi) {
  uint32_t r; asm("cvt.rn.bf16x2.f32 %0, %1, %2;" : "=r"(r) : "f"(hi), "f"(lo)); return r;
}
__device__ __forceinline__ float bf_lo(uint32_t v) { return __uint_as_float(v << 16); }
__device__ __forceinline__ float bf_hi(uint32_t v) { return __uint_as_float(v & 0xffff0000u); }
__device__ __forceinline__ float round_bf16(float v) { return __bfloat162float(__float2bfloat16_rn(v)); }
__device__ __forceinline__ float ex2(float v) { float r; asm("ex2.approx.ftz.f32 %0, %1;" : "=f"(r) : "f"(v)); return r; }
__device__ __forceinline__ float rcp(float v) { float r; asm("rcp.approx.ftz.f32 %0, %1;" : "=f"(r) : "f"(v)); return r; }
__device__ __forceinline__ void stsm4(uint32_t addr, uint32_t r0, uint32_t r1, uint32_t r2, uint32_t r3) {
  asm volatile("stmatrix.sync.aligned.m8n8.x4.shared.b16 [%0], {%1, %2, %3, %4};" :: "r"(addr), "r"(r0), "r"(r1), "r"(r2), "r"(r3) : "memory");
}
__device__ __forceinline__ void stsm2(uint32_t addr, uint32_t r0, uint32_t r1) {
  asm volatile("stmatrix.sync.aligned.m8n8.x2.shared.b16 [%0], {%1, %2};" :: "r"(addr), "r"(r0), "r"(r1) : "memory");
}
__device__ __forceinline__ uint2 lds64(uint32_t addr) {
  uint2 v; asm volatile("ld.shared.v2.u32 {%0, %1}, [%2];" : "=r"(v.x), "=r"(v.y) : "r"(addr) : "memory"); return v;
}
__device__ __forceinline__ void lds128x4(uint32_t addr, uint4& a, uint4& b, uint4& c, uint4& d) {
  asm volatile("ld.shared.v4.u32 {%0, %1, %2, %3}, [%16];\nld.shared.v4.u32 {%4, %5, %6, %7}, [%16 + 128];\n"
               "ld.shared.v4.u32 {%8, %9, %10, %11}, [%16 + 256];\nld.shared.v4.u32 {%12, %13, %14, %15}, [%16 + 384];"
    : "=r"(a.x), "=r"(a.y), "=r"(a.z), "=r"(a.w), "=r"(b.x), "=r"(b.y), "=r"(b.z), "=r"(b.w),
      "=r"(c.x), "=r"(c.y), "=r"(c.z), "=r"(c.w), "=r"(d.x), "=r"(d.y), "=r"(d.z), "=r"(d.w) : "r"(addr) : "memory");
}
__device__ __forceinline__ void ldsm4(uint32_t addr, uint32_t& r0, uint32_t& r1, uint32_t& r2, uint32_t& r3) {
  asm volatile("ldmatrix.sync.aligned.m8n8.x4.shared.b16 {%0, %1, %2, %3}, [%4];" : "=r"(r0), "=r"(r1), "=r"(r2), "=r"(r3) : "r"(addr) : "memory");
}
__device__ __forceinline__ uint4 lds128(uint32_t addr) {
  uint4 v; asm volatile("ld.shared.v4.u32 {%0, %1, %2, %3}, [%4];" : "=r"(v.x), "=r"(v.y), "=r"(v.z), "=r"(v.w) : "r"(addr) : "memory"); return v;
}
__device__ __forceinline__ void sts128(uint32_t addr, uint4 v) {
  asm volatile("st.shared.v4.u32 [%0], {%1, %2, %3, %4};" :: "r"(addr), "r"(v.x), "r"(v.y), "r"(v.z), "r"(v.w) : "memory");
}
__device__ __forceinline__ float lds_f32(uint32_t addr) { float v; asm volatile("ld.shared.f32 %0, [%1];" : "=f"(v) : "r"(addr) : "memory"); return v; }
__device__ __forceinline__ void sts_f32(uint32_t addr, float v) { asm volatile("st.shared.f32 [%0], %1;" :: "r"(addr), "f"(v) : "memory"); }
__device__ __forceinline__ uint32_t lds_u32(uint32_t addr) { uint32_t v; asm volatile("ld.shared.u32 %0, [%1];" : "=r"(v) : "r"(addr) : "memory"); return v; }
__device__ __forceinline__ void sts_u32(uint32_t addr, uint32_t v) { asm volatile("st.shared.u32 [%0], %1;" :: "r"(addr), "r"(v) : "memory"); }
__device__ __forceinline__ unsigned clock32() { unsigned c; asm volatile("mov.u32 %0, %%clock;" : "=r"(c)); return c; }
__device__ __forceinline__ bool elect_one() {
  uint32_t p; asm volatile("{\n.reg .pred q;\nelect.sync _|q, 0xffffffff;\nselp.u32 %0, 1, 0, q;\n}" : "=r"(p)); return p;
}
__device__ __forceinline__ void bar_sync(int id, int n) { asm volatile("bar.sync %0, %1;" :: "r"(id), "r"(n) : "memory"); }
__device__ __forceinline__ void fence_async_smem() { asm volatile("fence.proxy.async.shared::cta;" ::: "memory"); }
__device__ __forceinline__ void fence_async_all() { asm volatile("fence.proxy.async;" ::: "memory"); }
__device__ __forceinline__ void fence_gpu() { asm volatile("fence.acq_rel.gpu;" ::: "memory"); }
__device__ __forceinline__ unsigned ld_acquire(const unsigned* p) { unsigned v; asm volatile("ld.acquire.gpu.global.u32 %0, [%1];" : "=r"(v) : "l"(p) : "memory"); return v; }
__device__ __forceinline__ void red_release(unsigned* p, unsigned v) { asm volatile("red.release.gpu.global.add.u32 [%0], %1;" :: "l"(p), "r"(v) : "memory"); }
__device__ __forceinline__ void st_release(unsigned* p, unsigned v) { asm volatile("st.release.gpu.global.u32 [%0], %1;" :: "l"(p), "r"(v) : "memory"); }
__device__ __forceinline__ unsigned ld_relaxed(const unsigned* p) { unsigned v; asm volatile("ld.relaxed.gpu.global.u32 %0, [%1];" : "=r"(v) : "l"(p) : "memory"); return v; }
__device__ __forceinline__ void red_relaxed(unsigned* p, unsigned v) { asm volatile("red.relaxed.gpu.global.add.u32 [%0], %1;" :: "l"(p), "r"(v) : "memory"); }
__device__ __forceinline__ void st_relaxed(unsigned* p, unsigned v) { asm volatile("st.relaxed.gpu.global.u32 [%0], %1;" :: "l"(p), "r"(v) : "memory"); }
__device__ __forceinline__ void st_relaxed2(uint2* p, unsigned a, unsigned b) { asm volatile("st.relaxed.gpu.global.v2.u32 [%0], {%1, %2};" :: "l"(p), "r"(a), "r"(b) : "memory"); }
template <int SLEEP>
__device__ __forceinline__ unsigned wait_tagged(const uint2* p, unsigned tag) {
  uint2 v;
  int it = 0;
  do {
    if (SLEEP && it > 0) __nanosleep(SLEEP);
    asm volatile("ld.relaxed.gpu.global.v2.u32 {%0, %1}, [%2];" : "=r"(v.x), "=r"(v.y) : "l"(p) : "memory");
    if (++it > (1 << 20)) __trap();
  } while (!__all_sync(0xffffffffu, v.y == tag));
  return v.x;
}
__device__ __forceinline__ void wait_counter(const unsigned* p, unsigned target) {
#pragma unroll 1
  for (int it = 0; it < (1 << 20); it++) { if ((int)(ld_relaxed(p) - target) >= 0) return; }
  __trap();
}
__device__ __forceinline__ float4 ldg_l2(const float* p) {
  float4 v; asm volatile("ld.relaxed.gpu.global.v4.f32 {%0, %1, %2, %3}, [%4];" : "=f"(v.x), "=f"(v.y), "=f"(v.z), "=f"(v.w) : "l"(p) : "memory"); return v;
}
__device__ __forceinline__ float ldg_l2_f(const float* p) { float v; asm volatile("ld.relaxed.gpu.global.f32 %0, [%1];" : "=f"(v) : "l"(p) : "memory"); return v; }
__device__ __forceinline__ void sts64(uint32_t addr, float a, float b) { asm volatile("st.shared.v2.f32 [%0], {%1, %2};" :: "r"(addr), "f"(a), "f"(b) : "memory"); }
__device__ __forceinline__ void bulk_load(uint32_t dst, const void* src, uint32_t bytes, uint32_t bar) {
  asm volatile("cp.async.bulk.shared::cluster.global.mbarrier::complete_tx::bytes [%0], [%1], %2, [%3];" :: "r"(dst), "l"(src), "r"(bytes), "r"(bar) : "memory");
}
__device__ __forceinline__ void bulk_prefetch(const void* src, uint32_t bytes) {
  asm volatile("cp.async.bulk.prefetch.L2.global [%0], %1;" :: "l"(src), "r"(bytes) : "memory");
}
__device__ __forceinline__ void tma_store_2d(const CUtensorMap* tm, uint32_t src, int c0, int c1) {
  asm volatile("cp.async.bulk.tensor.2d.global.shared::cta.bulk_group [%0, {%2, %3}], [%1];" :: "l"(tm), "r"(src), "r"(c0), "r"(c1) : "memory");
}
__device__ __forceinline__ void bulk_store(void* dst, uint32_t src, uint32_t bytes) {
  asm volatile("cp.async.bulk.global.shared::cta.bulk_group [%0], [%1], %2;" :: "l"(dst), "r"(src), "r"(bytes) : "memory");
}
__device__ __forceinline__ void bulk_reduce_f32(void* dst, uint32_t src, uint32_t bytes) {
  asm volatile("cp.reduce.async.bulk.global.shared::cta.bulk_group.add.f32 [%0], [%1], %2;" :: "l"(dst), "r"(src), "r"(bytes) : "memory");
}
__device__ __forceinline__ void tma_load_3d(uint32_t dst, const CUtensorMap* tm, int c0, int c1, int c2, uint32_t bar) {
  asm volatile("cp.async.bulk.tensor.3d.shared::cluster.global.mbarrier::complete_tx::bytes [%0], [%1, {%3, %4, %5}], [%2];"
    :: "r"(dst), "l"(tm), "r"(bar), "r"(c0), "r"(c1), "r"(c2) : "memory");
}
__device__ __forceinline__ void cp_async16(uint32_t dst, const void* src) { asm volatile("cp.async.cg.shared.global [%0], [%1], 16;" :: "r"(dst), "l"(src) : "memory"); }
__device__ __forceinline__ void cp_async_commit() { asm volatile("cp.async.commit_group;" ::: "memory"); }
template <int N> __device__ __forceinline__ void cp_async_wait() { asm volatile("cp.async.wait_group %0;" :: "n"(N) : "memory"); }
__device__ __forceinline__ void prefetch_map(const CUtensorMap* tm) { asm volatile("prefetch.tensormap [%0];" :: "l"(tm) : "memory"); }
__device__ __forceinline__ void bulk_commit() { asm volatile("cp.async.bulk.commit_group;" ::: "memory"); }
__device__ __forceinline__ void bulk_wait0() { asm volatile("cp.async.bulk.wait_group 0;" ::: "memory"); }
__device__ __forceinline__ void bulk_wait0_read() { asm volatile("cp.async.bulk.wait_group.read 0;" ::: "memory"); }
__device__ __forceinline__ void mma16816(float& d0, float& d1, float& d2, float& d3, uint32_t a0, uint32_t a1, uint32_t a2, uint32_t a3, uint32_t b0, uint32_t b1) {
  asm volatile("mma.sync.aligned.m16n8k16.row.col.f32.bf16.bf16.f32 {%0, %1, %2, %3}, {%4, %5, %6, %7}, {%8, %9}, {%0, %1, %2, %3};"
    : "+f"(d0), "+f"(d1), "+f"(d2), "+f"(d3) : "r"(a0), "r"(a1), "r"(a2), "r"(a3), "r"(b0), "r"(b1));
}
__device__ __forceinline__ uint32_t hmul2(uint32_t a, uint32_t b) { uint32_t r; asm("mul.rn.bf16x2 %0, %1, %2;" : "=r"(r) : "r"(a), "r"(b)); return r; }
__device__ __forceinline__ uint32_t hfma2(uint32_t a, uint32_t b, uint32_t c) { uint32_t r; asm("fma.rn.bf16x2 %0, %1, %2, %3;" : "=r"(r) : "r"(a), "r"(b), "r"(c)); return r; }
__device__ __forceinline__ uint32_t hadd2(uint32_t a, uint32_t b) { uint32_t r; asm("add.rn.bf16x2 %0, %1, %2;" : "=r"(r) : "r"(a), "r"(b)); return r; }
__device__ __forceinline__ float sigmoidf_(float v) { return rcp(1.0f + ex2(v * -1.4426950408889634f)); }

__device__ __forceinline__ void hedgehog(const float (&p)[16], uint32_t (&phi)[16]) {
  float mx0 = p[0], mn0 = p[0], mx1 = p[2], mn1 = p[2];
#pragma unroll
  for (int j = 0; j < 4; j++) {
    mx0 = fmaxf(mx0, fmaxf(p[4 * j], p[4 * j + 1])); mn0 = fminf(mn0, fminf(p[4 * j], p[4 * j + 1]));
    mx1 = fmaxf(mx1, fmaxf(p[4 * j + 2], p[4 * j + 3])); mn1 = fminf(mn1, fminf(p[4 * j + 2], p[4 * j + 3]));
  }
#pragma unroll
  for (int o = 1; o <= 2; o <<= 1) {
    mx0 = fmaxf(mx0, __shfl_xor_sync(0xffffffffu, mx0, o)); mn0 = fminf(mn0, __shfl_xor_sync(0xffffffffu, mn0, o));
    mx1 = fmaxf(mx1, __shfl_xor_sync(0xffffffffu, mx1, o)); mn1 = fminf(mn1, __shfl_xor_sync(0xffffffffu, mn1, o));
  }
  float ep[16], en[16];
  float sp0 = 0.f, sn0 = 0.f, sp1 = 0.f, sn1 = 0.f;
#pragma unroll
  for (int j = 0; j < 4; j++) {
#pragma unroll
    for (int c = 0; c < 2; c++) {
      ep[4 * j + c] = ex2(p[4 * j + c] - mx0); en[4 * j + c] = ex2(mn0 - p[4 * j + c]);
      ep[4 * j + 2 + c] = ex2(p[4 * j + 2 + c] - mx1); en[4 * j + 2 + c] = ex2(mn1 - p[4 * j + 2 + c]);
      sp0 += ep[4 * j + c]; sn0 += en[4 * j + c]; sp1 += ep[4 * j + 2 + c]; sn1 += en[4 * j + 2 + c];
    }
  }
#pragma unroll
  for (int o = 1; o <= 2; o <<= 1) {
    sp0 += __shfl_xor_sync(0xffffffffu, sp0, o); sn0 += __shfl_xor_sync(0xffffffffu, sn0, o);
    sp1 += __shfl_xor_sync(0xffffffffu, sp1, o); sn1 += __shfl_xor_sync(0xffffffffu, sn1, o);
  }
  sp0 = rcp(sp0); sn0 = rcp(sn0); sp1 = rcp(sp1); sn1 = rcp(sn1);
#pragma unroll
  for (int j = 0; j < 4; j++) {
    phi[2 * j] = pack_bf16(ep[4 * j] * sp0, ep[4 * j + 1] * sp0);
    phi[2 * j + 1] = pack_bf16(ep[4 * j + 2] * sp1, ep[4 * j + 3] * sp1);
    phi[8 + 2 * j] = pack_bf16(en[4 * j + 1] * sn0, en[4 * j] * sn0);
    phi[8 + 2 * j + 1] = pack_bf16(en[4 * j + 3] * sn1, en[4 * j + 2] * sn1);
  }
}

__device__ __noinline__ void hedgehog_slow(float* buf, int n) {
#pragma unroll 1
  for (int u = 0; u < n; u++) {
    float p[16]; uint32_t phi[16];
#pragma unroll
    for (int i = 0; i < 16; i++) p[i] = buf[u * 16 + i];
    hedgehog(p, phi);
#pragma unroll
    for (int i = 0; i < 16; i++) buf[u * 16 + i] = __uint_as_float(phi[i]);
  }
}

__device__ __forceinline__ void store_phi_k(const uint32_t (&phi)[16], uint32_t a) {
#pragma unroll
  for (int jj = 0; jj < 4; jj++) stsm4(a ^ (jj << 5), phi[4 * jj], phi[4 * jj + 1], phi[4 * jj + 2], phi[4 * jj + 3]);
}
__device__ __forceinline__ void hand_over_smem(uint32_t bar, bool ok) {
  fence_async_smem();
  __syncwarp();
  if (elect_one() & ok) mbar_arrive(bar);
}
__device__ __noinline__ void redo_phi_k(float* buf, unsigned done, uint32_t pa, uint32_t bar) {
  hedgehog_slow(buf, 4);
#pragma unroll 1
  for (int u = 0; u < 4; u++) {
    if ((done >> u) & 1) continue;
    uint32_t phi[16];
#pragma unroll
    for (int i = 0; i < 16; i++) phi[i] = __float_as_uint(buf[u * 16 + i]);
    store_phi_k(phi, pa + (~u & 1) * 32768 + (u >> 1) * 4096);
    if (u >= 2) hand_over_smem(bar + (u - 2) * 8, true);
  }
}

__device__ __forceinline__ uint32_t dup_lo(uint32_t v) { uint32_t r; asm("{\n.reg .b16 l, h;\nmov.b32 {l, h}, %1;\nmov.b32 %0, {l, l};\n}" : "=r"(r) : "r"(v)); return r; }
__device__ __forceinline__ uint32_t dup_hi(uint32_t v) { uint32_t r; asm("{\n.reg .b16 l, h;\nmov.b32 {l, h}, %1;\nmov.b32 %0, {h, h};\n}" : "=r"(r) : "r"(v)); return r; }
struct HState { uint32_t a[16]; float s[5]; };
__device__ __forceinline__ void hedgehog_fast1(const float (&p)[16], HState& a) {
  float sm[8], m[8], r[8];
#pragma unroll
  for (int i = 0; i < 8; i++) {
    const float t0 = ex2(p[2 * i]), t1 = ex2(p[2 * i + 1]);
    a.a[i] = pack_bf16(t0, t1); sm[i] = t0 + t1; m[i] = t0 * t1;
  }
  float mq[4];
#pragma unroll
  for (int i = 0; i < 4; i++) {
    mq[i] = m[2 * i] * m[2 * i + 1];
    const float R = rcp(mq[i]);
    r[2 * i] = R * m[2 * i + 1]; r[2 * i + 1] = R * m[2 * i];
  }
  a.s[4] = (mq[0] + mq[1]) + (mq[2] + mq[3]);
#pragma unroll
  for (int i = 0; i < 4; i++) {
    const uint32_t rr = pack_bf16(r[2 * i], r[2 * i + 1]);
    a.a[8 + 2 * i] = hmul2(a.a[2 * i], dup_lo(rr)); a.a[9 + 2 * i] = hmul2(a.a[2 * i + 1], dup_hi(rr));
  }
#pragma unroll
  for (int c = 0; c < 2; c++) {
    a.s[2 * c] = (sm[c] + sm[2 + c]) + (sm[4 + c] + sm[6 + c]);
    a.s[2 * c + 1] = fmaf(r[6 + c], sm[6 + c], fmaf(r[4 + c], sm[4 + c], fmaf(r[2 + c], sm[2 + c], r[c] * sm[c])));
  }
}
template <bool NORM>
__device__ __forceinline__ bool hedgehog_fast2(const HState& a, uint32_t (&phi)[16], float& s0, float& s1) {
  float s[4] = {a.s[0], a.s[1], a.s[2], a.s[3]};
#pragma unroll
  for (int o = 1; o <= 2; o <<= 1)
#pragma unroll
    for (int i = 0; i < 4; i++) s[i] += __shfl_xor_sync(0xffffffffu, s[i], o);
  const bool ok = ((s[0] + s[1]) + (s[2] + s[3]) <= 7.2e16f) & (a.s[4] <= 1.3e36f);
  if (NORM) {
    const float R0 = rcp(s[0] * s[1]), R1 = rcp(s[2] * s[3]);
    const uint32_t n0 = pack_bf16(R0 * s[1], R0 * s[0]), n1 = pack_bf16(R1 * s[3], R1 * s[2]);
#pragma unroll
    for (int i = 0; i < 8; i++) { phi[i] = hmul2(a.a[i], dup_lo((i & 1) ? n1 : n0)); phi[8 + i] = hmul2(a.a[8 + i], dup_hi((i & 1) ? n1 : n0)); }
  } else {
    const uint32_t n = pack_bf16(s[0] * rcp(s[1]), s[2] * rcp(s[3]));
    s0 = s[0]; s1 = s[2];
#pragma unroll
    for (int i = 0; i < 8; i++) { phi[i] = a.a[i]; phi[8 + i] = hmul2(a.a[8 + i], (i & 1) ? dup_hi(n) : dup_lo(n)); }
  }
  return ok;
}
template <bool NORM>
__device__ __forceinline__ bool hedgehog_fast(const float (&p)[16], uint32_t (&phi)[16], float& s0, float& s1) {
  HState a;
  hedgehog_fast1(p, a);
  return hedgehog_fast2<NORM>(a, phi, s0, s1);
}

template <int OFF>
__device__ __forceinline__ void pack_frags(const float (&acc)[96], uint32_t (&a)[16]) {
#pragma unroll
  for (int i = 0; i < 16; i++) a[i] = pack_bf16(acc[OFF + 2 * i], acc[OFF + 2 * i + 1]);
#pragma unroll
  for (int i = 0; i < 16; i++) asm volatile("" : "+r"(a[i]) :: "memory");
}
__device__ __forceinline__ void issue_feat(const uint32_t (&a)[16], float (&p0)[16], float (&p1)[16], uint32_t wphi) {
  wgmma_fence();
#pragma unroll
  for (int kk = 0; kk < 2; kk++) {
    wgmma_rs_n32<1, H64>(p0, a[4 * kk], a[4 * kk + 1], a[4 * kk + 2], a[4 * kk + 3], dlo(wphi + kk * 1024, 16), kk);
    wgmma_rs_n32<1, H64>(p1, a[8 + 4 * kk], a[8 + 4 * kk + 1], a[8 + 4 * kk + 2], a[8 + 4 * kk + 3], dlo(wphi + 2048 + kk * 1024, 16), kk);
  }
  wgmma_commit();
}
__device__ __forceinline__ void keep_alive(const uint32_t (&a)[16]) {
#pragma unroll
  for (int i = 0; i < 16; i++) asm volatile("" :: "r"(a[i]) : "memory");
}

__device__ __forceinline__ void fma8(float (&a)[8], float xv, const uint4& w) {
  a[0] = fmaf(xv, bf_lo(w.x), a[0]); a[1] = fmaf(xv, bf_hi(w.x), a[1]);
  a[2] = fmaf(xv, bf_lo(w.y), a[2]); a[3] = fmaf(xv, bf_hi(w.y), a[3]);
  a[4] = fmaf(xv, bf_lo(w.z), a[4]); a[5] = fmaf(xv, bf_hi(w.z), a[5]);
  a[6] = fmaf(xv, bf_lo(w.w), a[6]); a[7] = fmaf(xv, bf_hi(w.w), a[7]);
}

template <int J0, int J1>
__device__ __forceinline__ void stage_out(const float (&acc)[64], uint32_t xa) {
#pragma unroll
  for (int jj = J0; jj < J1; jj++)
    stsm4((xa ^ ((jj & 3) << 5)) + (jj >> 2) * 16384, pack_bf16(acc[8 * jj], acc[8 * jj + 1]), pack_bf16(acc[8 * jj + 2], acc[8 * jj + 3]),
          pack_bf16(acc[8 * jj + 4], acc[8 * jj + 5]), pack_bf16(acc[8 * jj + 6], acc[8 * jj + 7]));
}
__device__ __forceinline__ float lds_bf16(uint32_t addr) {
  unsigned short v; asm volatile("ld.shared.u16 %0, [%1];" : "=h"(v) : "r"(addr) : "memory"); return __uint_as_float((uint32_t)v << 16);
}
__device__ __noinline__ void redo_rows(const __nv_bfloat16* pieces, const __nv_bfloat16* wo_cols, const unsigned* done, const __nv_bfloat16* xrows,
                                       uint32_t xa, int wi, uint32_t gate, int routed, uint32_t upd) {
  const int lane = threadIdx.x & 31;
  int it = 0;
  while (!__all_sync(0xffffffffu, ld_acquire(done + (lane & 15)) != 0)) { if (++it > (1 << 20)) __trap(); }
  float acc[64];
  const int g = lane >> 2, q = lane & 3, r0 = wi * 16 + g;
#pragma unroll
  for (int i = 0; i < 32; i++) {
    const int r = g + (i & 1) * 8, c = (i >> 1) * 8 + q * 2;
    uint32_t v = *reinterpret_cast<const uint32_t*>(xrows + (size_t)r * D_ + c);
    if (r == routed) v = hadd2(v, lds_u32(upd + c * 2));
    const float og = round_bf16(1.0f - lds_bf16(gate + r * 2));
    acc[2 * i] = og * bf_lo(v); acc[2 * i + 1] = og * bf_hi(v);
  }
#pragma unroll 1
  for (int ks = 0; ks < 64; ks++) {
    const unsigned* pc = reinterpret_cast<const unsigned*>(pieces + (ks >> 2) * 4096) + r0 * 32 + q;
    const int c0 = ((2 * (ks & 3)) ^ (r0 & 7)) * 4, c1 = ((2 * (ks & 3) + 1) ^ (r0 & 7)) * 4;
    const uint32_t a0 = ld_relaxed(pc + c0), a1 = ld_relaxed(pc + 256 + c0), a2 = ld_relaxed(pc + c1), a3 = ld_relaxed(pc + 256 + c1);
    const unsigned short* wp = reinterpret_cast<const unsigned short*>(wo_cols) + (size_t)(ks * 16 + 2 * q) * D_ + g;
#pragma unroll
    for (int nb = 0; nb < 16; nb++) {
      const uint32_t b0 = wp[nb * 8] | ((uint32_t)wp[nb * 8 + D_] << 16), b1 = wp[nb * 8 + 8 * D_] | ((uint32_t)wp[nb * 8 + 9 * D_] << 16);
      mma16816(acc[4 * nb], acc[4 * nb + 1], acc[4 * nb + 2], acc[4 * nb + 3], a0, a1, a2, a3, b0, b1);
    }
  }
  __syncwarp();
  stage_out<0, 8>(acc, xa);
}

__global__ void __cluster_dims__(2, 1, 1) __launch_bounds__(512, 1)
fused_kernel(const __grid_constant__ Maps maps, const __nv_bfloat16* __restrict__ x,
             const __nv_bfloat16* __restrict__ wo, const __nv_bfloat16* __restrict__ w_r, const __nv_bfloat16* __restrict__ gate_w) {
  extern __shared__ __align__(1024) uint8_t smem_raw[];
  if (threadIdx.x == 0) { prefetch_map(&maps.w); prefetch_map(&maps.x); }
  const int tid = threadIdx.x, warp = __shfl_sync(0xffffffffu, tid >> 5, 0), lane = tid & 31;
  const int rank = blockIdx.x & 1;
  const unsigned cl = blockIdx.x >> 1, hi = (cl - 36) * 37 >> 8, lo7 = cl - 36 - hi * 7;
  const unsigned col = cl < 4 ? 7 : cl < 36 ? (cl & 3) + (~cl & 4) * 2 : lo7 + (lo7 < 3 ? 4 : 9), pos = cl < 4 ? cl : cl < 36 ? (cl - 4) >> 3 : hi;
  const int b = cl < 64 ? (col & 7) * 16 + (col & 8) + pos * 2 + rank : blockIdx.x;
  const int e = blockIdx.x;
  const int tg = b >> 4, hp = b & 15;
  const int half = hp >> 3, ct = hp & 7;
  constexpr uint32_t SB0 = 1024;
  const uint32_t sb = SB0 + ((uint32_t)rank << 24);
  auto BAR = [&](int i) { return sb + SM_BAR + 8 * i; };
  auto load_stage = [&](int kt, int s, bool mc) {
    const uint32_t a = sb + SM_RA + s * A_BYTES, full = BAR(B_FULL + s);
    mbar_expect_tx(full, STAGE_BYTES);
    tma_load_3d(sb + SM_RB + s * B_BYTES, &maps.w, hp * 64, kt * 32, 0, full);
    if (mc) tma_load_2d_mc(a + rank * 8192, &maps.x, kt * 32, tg * 256 + rank * 128, full);
    else { tma_load_2d(a, &maps.x, kt * 32, tg * 256, full); tma_load_2d(a + 8192, &maps.x, kt * 32, tg * 256 + 128, full); }
  };
  auto slice_of = [&](int i) { return (i < 2 ? ct ^ i : i < 8 ? i - 2 * (i - 2 < (ct & 6)) : i) ^ (half * 8); };
  auto load_b2 = [&](int i) {
    const int j = slice_of(i), sl = i + 4 - (i >= 3) * NB2 - (i >= 10) * NB2;
    mbar_expect_tx(BAR(B_FB2 + i), 16384);
    tma_load_3d(sb + SM_RB + sl * 16384, &maps.wo, 0, j * 64, ct * 2, BAR(B_FB2 + i));
  };
  auto load_xt = [&](int w) {
    mbar_expect_tx(BAR(B_XT + w), 16384);
    tma_load_2d(sb + SM_XT + w * 8192, &maps.xt, ct * 128, tg * 256 + half * 128 + w * 64, BAR(B_XT + w));
    tma_load_2d(sb + SM_XT + w * 8192 + 16384, &maps.xt, ct * 128 + 64, tg * 256 + half * 128 + w * 64, BAR(B_XT + w));
  };
  auto o_piece = [&](int hf, int mb, int j) { return g_o + (size_t)((((tg * 2 + hf) * 2 + mb) * 16 + j) * 4096); };

  if (b >= NCTA) {
    if (warp == 0 && b == NCTA) {
      const unsigned tag = (ld_relaxed(&g_bcast[0].y) + 1) & 0xfffu;
      unsigned val = 0;
#pragma unroll 1
      for (int round = 0; round < 2; round++) {
        const unsigned* arr = (round ? g_ready : g_key) + lane * 4;
        unsigned k[16], bad;
        int it = 0;
        do {
          bad = 0;
#pragma unroll
          for (int a = 0; a < 4; a++)
            asm volatile("ld.relaxed.gpu.global.v4.u32 {%0, %1, %2, %3}, [%4];" : "=r"(k[4 * a]), "=r"(k[4 * a + 1]), "=r"(k[4 * a + 2]), "=r"(k[4 * a + 3])
                         : "l"(arr + (round ? 0 : a * NCTA)) : "memory");
#pragma unroll
          for (int i = 0; i < 16; i++) bad |= k[i] ^ tag;
          if (++it > (1 << 20)) __trap();
        } while (!__all_sync(0xffffffffu, (bad & 0xfffu) == 0));
        if (round == 0) {
#pragma unroll
          for (int c = 0; c < 4; c++) {
            const unsigned m = max(max(k[c], k[4 + c]), max(k[8 + c], k[12 + c]));
            val = max(val, (m & 0xffff0000u) | ((127u - (lane * 4 + c)) << 4) | ((m >> 12) & 15u));
          }
          val = __reduce_max_sync(0xffffffffu, val);
        }
        if (lane < 8) st_relaxed2(g_bcast + round * 128 + lane * 16, val, tag);
        const uint32_t* xr = reinterpret_cast<const uint32_t*>(x + (size_t)(2047u - (val & 0x7ffu)) * D_);
        float l = 0.f;
#pragma unroll 4
        for (int i = lane; i < 512; i += 32) {
          const uint32_t pr = hmul2(__ldg(xr + i), __ldg(reinterpret_cast<const uint32_t*>(gate_w) + i));
          l += bf_lo(pr) + bf_hi(pr);
        }
#pragma unroll
        for (int o = 1; o <= 16; o <<= 1) l += __shfl_xor_sync(0xffffffffu, l, o);
        val = __float_as_uint(round_bf16(sigmoidf_(round_bf16(l)))) >> 16;
      }
    }
    return;
  }
  if (warp == 8) {
    if (elect_one()) {
      mbar_init(BAR(0), 1);
      if (NPRE > 1) { mbar_init(BAR(1), 1); mbar_init(BAR(2), 1); }
      if (NPRE > 0) fence_async_smem();
      TSTAMP(40);
      if (NPRE > 0) load_stage(0, 0, false);
      if (NPRE > 1) load_stage(1, 1, false);
      if (NPRE > 2) load_stage(2, 2, false);
      TSTAMP(41);
    }
  } else if (elect_one()) {
    const int i = 3 + warp - (warp > 8);
    mbar_init(BAR(i), i < B_EMPTY ? 1 : 4);
    if (NPRE < 2 && warp >= 14) mbar_init(BAR(warp - 13), 1);
    if (warp == 13) mbar_init(BAR(B_INIT), 3);
  }
  asm volatile("fence.mbarrier_init.release.cluster;" ::: "memory");
  __syncwarp();
  asm volatile("barrier.cluster.arrive.relaxed.aligned;" ::: "memory");
  auto cluster_wait = [&]() { asm volatile("barrier.cluster.wait.aligned;" ::: "memory"); };

  if (warp >= 12) {
    asm volatile("setmaxnreg.dec.sync.aligned.u32 40;");
    const int aw = warp - 12;
    cluster_wait();
    const unsigned old_key = ld_relaxed(g_key + aw * NCTA + b);
    const uint32_t zero = smem_u32(smem_raw) ^ sb;
    {
      float r[4], l[4];
#pragma unroll
      for (int t = 0; t < 4; t++) { r[t] = 0.f; l[t] = 0.f; }
      uint32_t xa = sb + SM_XR + aw * 1024 + lane * 8, wa = sb + SM_XR + 32768 + lane * 8;
#pragma unroll 1
      for (int i = 0; i < 8; i++) {
        if (!(i & 1)) mbar_wait(BAR(B_XR) + i * 4, 0);
        if (tid == 384 && i == 6) TSTAMP(30);
        uint2 wr = lds64(wa);
        const uint2 gw = lds64(wa + 2048);
        uint2 xv[4];
#pragma unroll
        for (int t = 0; t < 4; t++) xv[t] = lds64(xa + t * 256);
        xa += 4096; wa += 256;
        wr.x |= (xv[1].x | xv[2].x | xv[3].x) & zero;
#pragma unroll
        for (int t = 0; t < 4; t++) { r[t] = fmaf(bf_lo(xv[t].x), bf_lo(wr.x), r[t]); l[t] = fmaf(bf_lo(xv[t].x), bf_lo(gw.x), l[t]); }
#pragma unroll
        for (int t = 0; t < 4; t++) { r[t] = fmaf(bf_hi(xv[t].x), bf_hi(wr.x), r[t]); l[t] = fmaf(bf_hi(xv[t].x), bf_hi(gw.x), l[t]); }
#pragma unroll
        for (int t = 0; t < 4; t++) { r[t] = fmaf(bf_lo(xv[t].y), bf_lo(wr.y), r[t]); l[t] = fmaf(bf_lo(xv[t].y), bf_lo(gw.y), l[t]); }
#pragma unroll
        for (int t = 0; t < 4; t++) { r[t] = fmaf(bf_hi(xv[t].y), bf_hi(wr.y), r[t]); l[t] = fmaf(bf_hi(xv[t].y), bf_hi(gw.y), l[t]); }
      }
      float u[4];
#pragma unroll
      for (int t = 0; t < 4; t++) u[t] = ((lane & 4) ? l[t] : r[t]) + __shfl_xor_sync(0xffffffffu, (lane & 4) ? r[t] : l[t], 4);
      const float v0 = ((lane & 1) ? u[1] : u[0]) + __shfl_xor_sync(0xffffffffu, (lane & 1) ? u[0] : u[1], 1);
      const float v1 = ((lane & 1) ? u[3] : u[2]) + __shfl_xor_sync(0xffffffffu, (lane & 1) ? u[2] : u[3], 1);
      float v = ((lane & 2) ? v1 : v0) + __shfl_xor_sync(0xffffffffu, (lane & 2) ? v0 : v1, 2);
      v += __shfl_xor_sync(0xffffffffu, v, 8);
      v += __shfl_xor_sync(0xffffffffu, v, 16);
      v = round_bf16(v);
      unsigned k = __float_as_uint(v) >> 16;
      k = (k & 0x8000u) ? (~k & 0xffffu) : (k | 0x8000u);
      k = __reduce_max_sync(0xffffffffu, lane < 4 ? (k << 4) | (15u - (aw * 4 + lane)) : 0u);
      mbar_wait(BAR(B_INIT), 0);
      const unsigned tag = (old_key + 1) & 0xfffu;
      if (lane == 0) st_relaxed(g_key + aw * NCTA + b, (k << 12) | tag);
      if ((lane >> 2) == 1) st_relaxed(g_gate + b * 16 + aw * 4 + (lane & 3), __float_as_uint(round_bf16(sigmoidf_(v))) | tag);
    }
    if (tid == 384) { TSTAMP(31); GSTAMP(60); }
    fence_async_smem();
    __syncwarp();
    if (elect_one()) mbar_arrive(BAR(B_XRD));
    mbar_wait(BAR(B_XSEL), 0);
    if (tid == 384) TSTAMP(36);
    float ag[8];
#pragma unroll
    for (int i = 0; i < 8; i++) ag[i] = 0.f;
    if (e < NMOE) {
      const uint32_t lw = sb + SM_MOE + aw * 2048 + (lane >> 3) * 512 + (lane & 7) * 16;
      uint32_t lx = sb + SM_XSEL + aw * 32 + (lane >> 3) * 8, fb = BAR(B_MOE), wa = lw;
      bool got = false;
#pragma unroll 1
      for (int m = 0; m < 12; m++) {
#pragma unroll
        for (int c = 0; c < 2; c++) {
          if (!got) mbar_wait(fb + c * 8, (m >> 1) & 1);
          uint4 w0, w1, w2, w3;
          lds128x4(wa + c * 8192, w0, w1, w2, w3);
          uint2 xv = lds64(lx + c * 128);
          got = mbar_test(c ? fb ^ 16 : fb + 8, ((m + c) >> 1) & 1);
          const uint32_t dep = ((w0.x | w1.x | w2.x) | w3.x) & zero;
          xv.x |= dep;
          if (elect_one()) mbar_arrive(fb + dep + (B_MOEE - B_MOE + c) * 8);
          fma8(ag, bf_lo(xv.x), w0); fma8(ag, bf_hi(xv.x), w1); fma8(ag, bf_lo(xv.y), w2); fma8(ag, bf_hi(xv.y), w3);
        }
        fb ^= 16; wa = 2 * lw + 16384 - wa; lx += 256;
        if (m == 7) {
          int ln;
          asm volatile("mov.u32 %0, %%laneid;" : "=r"(ln));
#pragma unroll
          for (int i = 0; i < 4; i++) ag[i] = ((ln & 16) ? ag[4 + i] : ag[i]) + __shfl_xor_sync(0xffffffffu, (ln & 16) ? ag[i] : ag[4 + i], 16);
          const float v0 = ((ln & 8) ? ag[2] : ag[0]) + __shfl_xor_sync(0xffffffffu, (ln & 8) ? ag[0] : ag[2], 8);
          const float v1 = ((ln & 8) ? ag[3] : ag[1]) + __shfl_xor_sync(0xffffffffu, (ln & 8) ? ag[1] : ag[3], 8);
          const uint32_t own = (uint32_t)(ln & 4) << 22;
          asm volatile("st.async.shared::cluster.mbarrier::complete_tx::bytes.v2.f32 [%0], {%1, %2}, [%3];"
                       :: "r"(own + SB0 + SM_RED + rank * 512 + aw * 128 + (ln & 3) * 32 + (ln >> 3) * 8), "f"(v0), "f"(v1), "r"(own + SB0 + SM_BAR + 8 * B_H) : "memory");
          if (tid == 384) TSTAMP(39);
          mbar_wait(BAR(B_H), 0);
          const uint32_t ra = sb + SM_RED + ln * 4;
          float gv = round_bf16((lds_f32(ra) + lds_f32(ra + 128)) + (lds_f32(ra + 256) + lds_f32(ra + 384)));
          const float uv = round_bf16((lds_f32(ra + 512) + lds_f32(ra + 640)) + (lds_f32(ra + 768) + lds_f32(ra + 896)));
          gv = round_bf16(gv * sigmoidf_(gv));
          lx = sb + SM_XSEL + aw * 32;
          asm volatile("st.shared.b16 [%0], %1;" :: "r"(lx + (ln >> 2) * 128 + (ln & 3) * 2), "h"(__bfloat16_as_ushort(__float2bfloat16_rn(gv * uv))) : "memory");
          __syncwarp();
#pragma unroll
          for (int i = 0; i < 8; i++) ag[i] = 0.f;
          if (tid == 384) TSTAMP(33);
        }
      }
      mbar_wait(BAR(B_RDY), 0);
#pragma unroll
      for (int j = 0; j < 3; j++)
        asm volatile("red.global.add.v4.f32 [%0], {%1, %2, %3, %4};" :: "l"(g_z.y + (e & (NY - 1)) * 2 * D_ + (j * 128 + aw * 32 + lane) * 4),
                     "f"(ag[3 * j]), "f"(ag[3 * j + 1]), "f"(j < 2 ? ag[3 * j + 2] : 0.f), "f"(1.0f) : "memory");
    }
    fence_async_smem();
    if (tid == 384) TSTAMP(34);
    bar_sync(4, 128);
    if (aw < 3) {
      if (aw == 0) mbar_wait(BAR(B_PHI), 0);
      if (elect_one()) load_b2(aw);
      if (aw) {
#pragma unroll 1
        for (int i = 0; i < 16; i++) {
          mbar_wait(BAR(B_FB2 + i), 0);
          if (i == 0) mbar_wait(BAR(B_OP + half * 2 + aw - 1), 0);
          if (elect_one()) mbar_expect_tx(BAR(B_F2 + (aw - 1) * 16 + i), i ? 8192 : 0);
        }
      }
    } else {
      const uint4 info = lds128(sb + SM_INFO);
      int it = 0;
      if ((info.y >> 7) == tg * 2 + half) {
        mbar_wait(BAR(B_RDY), 0);
        const float rs = round_bf16(sigmoidf_(__uint_as_float(info.z)));
        float y[9];
        do {
          __nanosleep(100);
#pragma unroll
          for (int i = 0; i < 9; i++) y[i] = 0.f;
#pragma unroll 1
          for (int c = lane >> 4; c < NY; c += 2) {
            const float* yp = g_z.y + c * 2 * D_ + (ct * 16 + (lane & 15)) * 4;
            const float4 a0 = ldg_l2(yp), a1 = ldg_l2(yp + 512), a2 = ldg_l2(yp + 1024);
            y[0] += a0.x; y[1] += a0.y; y[2] += a0.z; y[3] += a1.x; y[4] += a1.y; y[5] += a1.z; y[6] += a2.x; y[7] += a2.y;
            y[8] += a0.w + a1.w + a2.w;
          }
#pragma unroll
          for (int i = 0; i < 9; i++) y[i] += __shfl_xor_sync(0xffffffffu, y[i], 16);
          if (++it > (1 << 20)) __trap();
        } while (!__all_sync(0xffffffffu, y[8] == 3.f * NMOE));
        const int w = (info.y >> 6) & 1, r = info.y & 63;
        mbar_wait(BAR(B_XT + w), 0);
        if (lane < 16) {
          const uint32_t ad = sb + SM_XT + w * 8192 + (lane >> 3) * 16384 + r * 128 + (((lane & 7) ^ (r & 7)) << 4), rs2 = pack_bf16(rs, rs);
          const uint4 xv = lds128(ad);
          const uint4 u = make_uint4(hmul2(pack_bf16(y[0], y[1]), rs2), hmul2(pack_bf16(y[2], y[3]), rs2), hmul2(pack_bf16(y[4], y[5]), rs2), hmul2(pack_bf16(y[6], y[7]), rs2));
          sts128(sb + SM_UPD + lane * 16, u);
          sts128(ad, make_uint4(hadd2(xv.x, u.x), hadd2(xv.y, u.y), hadd2(xv.z, u.z), hadd2(xv.w, u.w)));
        }
        asm volatile("fence.acq_rel.cta;" ::: "memory");
        __syncwarp();
        if (elect_one()) mbar_arrive(BAR(B_Y));
      }
    }
  } else if (warp >= 8) {
    asm volatile("setmaxnreg.dec.sync.aligned.u32 24;");
    cluster_wait();
    if (tid == 256) TSTAMP(58);
    if (warp != 8) {
      if (elect_one()) {
        if (smem_u32(smem_raw) != sb) __trap();
#pragma unroll 1
        for (int i = B_ST + warp - 9; i < NBAR; i += 3) mbar_init(BAR(i), bar_count(i));
        asm volatile("fence.mbarrier_init.release.cluster;" ::: "memory");
      }
#pragma unroll
      for (int i = 0; i < 3; i++) sts128(sb + SM_KVB + (i * 96 + tid - 288) * 16, make_uint4(0, 0, 0, 0));
      if (warp < 11) sts128(sb + SM_ONES + (tid - 288) * 16, make_uint4(0x3f803f80u, 0x3f803f80u, 0x3f803f80u, 0x3f803f80u));
      hand_over_smem(BAR(B_INIT), true);
      if (tid == 288) TSTAMP(57);
    }
    if (warp == 8) {
      int s = NPRE, ph = 1;
#pragma unroll 1
      for (int kt = NPRE; kt < KT; kt++) {
        mbar_wait(BAR(B_EMPTY + s), ph);
        if (elect_one()) {
          load_stage(kt, s, true);
          const unsigned xc = kt - XR_AFTER;
          if (xc < 4) {
            mbar_expect_tx(BAR(B_XR + xc), xc ? 8192 : 12288);
            tma_load_2d(sb + SM_XR + xc * 8192, &maps.xr, xc * 256, b * 16, BAR(B_XR + xc));
            tma_load_2d(sb + SM_XR + xc * 8192 + 4096, &maps.xr, xc * 256 + 128, b * 16, BAR(B_XR + xc));
            if (xc == 0) { bulk_load(sb + SM_XR + 32768, w_r, 2048, BAR(B_XR)); bulk_load(sb + SM_XR + 34816, gate_w, 2048, BAR(B_XR)); }
          }
          const int pg = kt - STAGES - PF_START + PF_OFF;
          if (pg >= (e < NMOE ? PF_OFF : 24) && pg < 26 && (EXPT != 3 || pg >= 24)) {
            const CUtensorMap* tm = &maps.tg + (pg < 16 ? (b & 1) : pg < 24 ? 2 : 3);
            const int c0 = pg < 16 ? (e >> 1) * 64 : 0, c1 = (pg < 16 ? pg : pg < 24 ? e * 8 + pg - 16 : b * 2 + pg - 24) * 64;
            asm volatile("cp.async.bulk.prefetch.tensor.2d.L2.global [%0, {%1, %2}];" :: "l"(tm), "r"(c0), "r"(c1) : "memory");
          }
        }
        if (++s == STAGES) { s = 0; ph ^= 1; }
      }
      mbar_wait(BAR(B_EMPTY + 1), 1);
#pragma unroll 1
      for (int i = 3; i < (XT_IN_A ? NB2 : 5); i++)
        if (elect_one()) { if (!XT_IN_A) load_xt(i - 3); load_b2(i); }
    } else if (warp == 9) {
      const unsigned tag = (ld_relaxed(g_ready + b) + 1) & 0xfffu;
      if (elect_one()) {
        mbar_expect_tx(BAR(B_WPHI), 4096);
        tma_load_2d(sb + SM_WPHI, &maps.wphi, 0, hp * 64, BAR(B_WPHI));
      }
      mbar_wait(BAR(B_WPHI), 0);
#pragma unroll 1
      for (uint32_t ad = sb + SM_WPHI + lane * 16; ad < sb + SM_WPHI + 4096; ad += 512) {
        constexpr float L = 1.4426950408889634f;
        const uint4 w = lds128(ad);
        sts128(ad, make_uint4(pack_bf16(bf_lo(w.x) * L, bf_hi(w.x) * L), pack_bf16(bf_lo(w.y) * L, bf_hi(w.y) * L),
                              pack_bf16(bf_lo(w.z) * L, bf_hi(w.z) * L), pack_bf16(bf_lo(w.w) * L, bf_hi(w.w) * L)));
      }
      fence_async_smem();
      mbar_wait(BAR(B_XRD), 0);
      const unsigned best = __shfl_sync(0xffffffffu, wait_tagged<KEY_SLEEP>(g_bcast + tg * 16, tag), 0);
      const unsigned idx = 2047u - (best & 0x7ffu);
      unsigned u = best >> 16;
      u = (u & 0x8000u) ? (u & 0x7fffu) : (~u & 0xffffu);
      if (elect_one()) {
        sts128(sb + SM_INFO, make_uint4(tag, idx, u << 16, 0));
        mbar_expect_tx(BAR(B_H), 1024);
        mbar_expect_tx(BAR(B_XSEL), 2048);
        bulk_load(sb + SM_XSEL, x + (size_t)idx * D_, 2048, BAR(B_XSEL));
        TSTAMP(32); GSTAMP(61);
        bulk_store(reinterpret_cast<char*>(&g_z) + b * ZB, sb + SM_KVB, ZB);
      }
      bulk_commit(); bulk_wait0();
      fence_gpu();
      __syncwarp();
      if (lane == 0) { st_relaxed(g_ready + b, tag); TSTAMP(42); }
      int it = 0;
#pragma unroll 1
      for (int c = 0; c < 2; c++) {
        uint4 gv;
        do {
          asm volatile("ld.relaxed.gpu.global.v4.u32 {%0, %1, %2, %3}, [%4];" : "=r"(gv.x), "=r"(gv.y), "=r"(gv.z), "=r"(gv.w)
                       : "l"(g_gate + tg * 256 + c * 128 + lane * 4) : "memory");
          if (++it > (1 << 20)) __trap();
        } while (!__all_sync(0xffffffffu, (((gv.x ^ tag) | (gv.y ^ tag) | (gv.z ^ tag) | (gv.w ^ tag)) & 0xfffu) == 0));
        sts64(sb + SM_GATE + c * 256 + lane * 8, __uint_as_float(__byte_perm(gv.x, gv.y, 0x7632)), __uint_as_float(__byte_perm(gv.z, gv.w, 0x7632)));
      }
      const unsigned gsel = wait_tagged<200>(g_bcast + 128 + tg * 16, tag);
      if ((idx >> 8) == tg && lane == 0) asm volatile("st.shared.b16 [%0], %1;" :: "r"(sb + SM_GATE + (idx & 255) * 2), "h"((unsigned short)gsel) : "memory");
      __syncwarp();
      if (elect_one()) { mbar_arrive(BAR(B_RDY)); TSTAMP(43); }
    } else if (e < NMOE) {
      const int w = warp & 1;
      const CUtensorMap* tm = &maps.wg + rank;
      int c0 = (e >> 1) * 64, c1 = 0, c2 = 4 * w;
      uint32_t bar = BAR(B_MOE + w);
      mbar_wait(BAR(B_XRD), 0);
#pragma unroll 1
      for (int m = 0; m < 12; m++) {
        mbar_wait(bar + (B_MOEE - B_MOE) * 8, ((m >> 1) & 1) ^ 1);
        if (elect_one()) {
          mbar_expect_tx(bar, 8192);
          tma_load_3d(sb + SM_MOE + w * 8192 + (m & 1) * 16384, tm, c0, c1, c2, bar);
        }
        bar ^= 16;
        if (m < 7) c2 += 8; else c1 += 8;
        if (m == 7) { tm = &maps.wd; c0 = 0; c1 = e * 32 + w * 4; c2 = 0; }
      }
    }
    const int wi = warp - 8, st = tid - 256;
    bar_sync(5, 128);
    asm volatile("setmaxnreg.inc.sync.aligned.u32 " STR(REG_K) ";");
    {
      auto kv_half = [&](float (&d)[20], int h, int mb) {
#pragma unroll
        for (int i = 0; i < 8; i++)
          wgmma_ss_n40<1, 1, H128, H64>(d, dlo(SB0 + SM_PHIK + 32768, 16) - h * 2048 + (((i & 2) << 2) + (i & 4) + mb * 2 + (i & 1)) * 128,
                                        dlo(SB0 + SM_V, SM_ONES - SM_V) + (h * 16 + (i & 4) * 2 + mb * 4 + (i & 3)) * (64 - (64 << 16)), (mb | i) != 0);
      };
      auto kv_out = [&](float (&d)[20], int h) {
        wgmma_commit();
        wgmma_wait<0>();
        fence_regs(d);
        if (st == 0) TSTAMP(21 + h);
        float* dst = g_z.kv + (hp * 2 + h) * KVH + st * 4;
#pragma unroll
        for (int c = 0; c < 4; c++)
          asm volatile("red.global.add.v4.f32 [%0], {%1, %2, %3, %4};" :: "l"(dst + c * 512),
                       "f"(d[4 * c]), "f"(d[4 * c + 1]), "f"(d[4 * c + 2]), "f"((lane & 1) ? d[4 * c + 3] : 1.0f) : "memory");
        asm volatile("red.global.add.v4.f32 [%0], {%1, %2, %3, %4};" :: "l"(dst + 2048),
                     "f"((lane & 1) ? d[16] : d[3]), "f"((lane & 1) ? d[18] : d[7]), "f"((lane & 1) ? 1.0f : d[11]), "f"((lane & 1) ? 0.0f : d[15]) : "memory");
        bar_sync(5, 128);
        if (XT_IN_A && h == XT_H && wi < 2 && elect_one()) load_xt(wi);
      };
#pragma unroll 1
      for (int h = 0; h < 2; h++) {
        float kv[20];
        mbar_wait(BAR(B_PHI + h), 0);
        if (st == 0) TSTAMP(23 + h);
        wgmma_fence();
        kv_half(kv, h, 0); kv_half(kv, h, 1);
        kv_out(kv, h);
      }
      if (wi == 3 && elect_one()) mbar_arrive_cluster(BAR(B_PEER) ^ (1u << 24));
      if (st == 0) TSTAMP(13);
      const int f = wi * 16 + (lane & 15), sw = (f >> 1) & 3, chi = lane >> 4;
      float4 v[10];
      const float* src = g_z.kv + hp * 2 * KVH + st * 4;
      { const unsigned c0 = clock32(); while (clock32() - c0 < KV_DELAY) {} }
      int it = 0;
      unsigned need = 0x3ff;
#pragma unroll
      for (int i = 0; i < 10; i++) v[i] = make_float4(0.f, 0.f, 0.f, 0.f);
      do {
        if (++it > (1 << 20)) __trap();
        unsigned bad = 0;
        if (st == 0 && it == 1) TSTAMP(35);
#pragma unroll
        for (int i = 0; i < 10; i++)
          asm volatile("{\n.reg .pred p;\nsetp.ne.u32 p, %5, 0;\n@p ld.relaxed.gpu.global.v4.f32 {%0, %1, %2, %3}, [%4];\n}"
                       : "+f"(v[i].x), "+f"(v[i].y), "+f"(v[i].z), "+f"(v[i].w) : "l"(src + i * 512), "r"(need & (1u << i)) : "memory");
#pragma unroll
        for (int i = 0; i < 10; i++) bad |= ((i % 5 == 4 ? v[i].z : v[i].w) != 8.f) << i;
        need = __reduce_or_sync(0xffffffffu, bad & ((lane & 1) ? 0x210u : 0x1efu));
        if (st == 0 && it == 1) TSTAMP(20);
      } while (need);
      uint32_t zz[2];
#pragma unroll
      for (int h = 0; h < 2; h++) {
        const float4* w = v + h * 5;
        const uint32_t kb = sb + SM_KVB + h * 4096 + f * 64;
        zz[h] = __shfl_sync(0xffffffffu, pack_bf16(w[4].x, w[4].y), lane | 1);
        const bool od = lane & 1;
        stsm4(kb + ((chi ^ sw) << 4), pack_bf16(w[0].x, w[0].y), pack_bf16(w[0].z, od ? w[0].w : w[4].x), pack_bf16(w[1].x, w[1].y), pack_bf16(w[1].z, od ? w[1].w : w[4].y));
        stsm4(kb + (((2 + chi) ^ sw) << 4), pack_bf16(w[2].x, w[2].y), pack_bf16(w[2].z, od ? w[2].w : w[4].z), pack_bf16(w[3].x, w[3].y), pack_bf16(w[3].z, od ? w[3].w : w[4].w));
      }
      stsm4(sb + SM_KVB + 8192 + f * 64 + ((chi ^ sw) << 4), zz[0], zz[0] >> 16, zz[1], zz[1] >> 16);
      fence_async_smem();
      __syncwarp();
      if (elect_one()) mbar_arrive(BAR(B_KVB));
    }
    {
      const int pm = wi >> 1;
      if (wi & 1) {
        const int hf = half ^ pm;
        mbar_wait(BAR(B_PEER), 0);
        mbar_wait(BAR(B_OP + hf * 2), 0);
        const unsigned c0 = clock32();
        while (clock32() - c0 < (unsigned)(pm ? LATE_DELAY + ct * LATE_STEP : (ct >> 2) * URG_STEP)) {}
        __syncwarp();
        auto to_partner = [&](int mb) {
          asm volatile("cp.async.bulk.shared::cluster.shared::cta.mbarrier::complete_tx::bytes [%0], [%1], 8192, [%2];"
                       :: "r"((sb ^ (1u << 24)) + SM_RA + mb * 8192), "r"(sb + SM_O + mb * 8192), "r"(BAR(B_F2 + mb * 16 + 1) ^ (1u << 24)) : "memory");
        };
        unsigned* hint = g_z.hint + (tg * 2 + hf) * 32 + hp;
        const int sz = pm ? LATE_SZ : 8192;
#pragma unroll 1
        for (int o = 0; o < 16384; o += sz) {
          const int mb = o >> 13;
          if (o == 8192) mbar_wait(BAR(B_OP + hf * 2 + 1), 0);
          if (elect_one()) bulk_store(reinterpret_cast<char*>(o_piece(hf, mb, hp)) + (o & 8191), sb + SM_O + pm * 16384 + o, sz);
          bulk_commit();
          if (pm == 0 && elect_one()) to_partner(mb);
          bulk_wait0();
          __syncwarp();
          if (((o + sz) & 8191) == 0 && lane == 0) { st_relaxed(hint + mb * 16, 1); TSTAMP((pm ? 37 : 15) + mb); }
        }
        if (lane == 0) mbar_arrive(BAR(B_ST + pm));
        if (pm == 0) {
          if (lane < 2) mbar_arrive_cluster((lane << 24) + SB0 + SM_BAR + 8 * (B_GO + NA2));
          mbar_wait(BAR(B5_AFTER), 0);
#pragma unroll 1
          for (int i = XT_IN_A ? NB2 : 5; i < 16; i++) {
            mbar_wait(i < NB2 ? BAR(B_XTD) : BAR(B_DB + i - NB2), 0);
            if (elect_one()) load_b2(i);
          }
        } else {
          mbar_wait(BAR(B_ST), 0);
          fence_gpu();
          if (lane == 0) st_relaxed(g_z.done + b, 1);
        }
      } else if (pm) {
        const __nv_bfloat16* src = o_piece(half, rank, half * 8);
        uint32_t dst = sb + SM_RA + 16384 + rank * 8192;
        mbar_wait(BAR(B_PEER), 0);
#pragma unroll 1
        for (int i = 2; i < 16; i++) {
          if (i == (ct & 6) + 2) src += 2 * 4096;
          if (i == 8) src -= half * 16 * 4096;
          mbar_wait(BAR(B_GO + i), 0);
          if (elect_one()) {
            asm volatile("cp.async.bulk.shared::cluster.global.mbarrier::complete_tx::bytes.multicast::cluster [%0], [%1], 8192, [%2], %3;"
                         :: "r"(dst), "l"(src), "r"(BAR(B_F2 + rank * 16 + i)), "h"((uint16_t)3) : "memory");
            if (i == 2) TSTAMP(19);
          }
          src += 4096;
          dst += (i == 5 || i == 10) ? -4 * 16384 : 16384;
        }
      } else {
        const unsigned* flag = g_z.hint + (tg * 2 + half) * 32 + rank * 16 + slice_of(lane & 15);
        bool seen = lane < 2 || lane > 15;
        mbar_wait(BAR(B_OP + half * 2 + rank), 0);
        int it = 0;
        do {
          if (ld_relaxed(flag) != 0 && !seen) {
            mbar_arrive(BAR(B_GO) + lane * 8);
            seen = true;
          }
          if (++it > (1 << 20)) __trap();
        } while (!__all_sync(0xffffffffu, seen));
      }
    }
  } else {
    asm volatile("setmaxnreg.inc.sync.aligned.u32 224;");
    const int wg = warp >> 2, wi = warp & 3;
    cluster_wait();
    if (tid == 0) TSTAMP(59);
    float acc0[96], acc1[96];
    {
      int s = 0, ph = 0, sprev = 0;
#pragma unroll 1
      for (int kt = 0; kt < KT - STAGES; kt++) {
        mbar_wait(BAR(B_FULL + s), ph);
        if (kt == 0 && tid == 0) TSTAMP(1);
        if (tid == 0 && !(kt & 1)) TSTAMP(44 + kt / 2);
        const uint32_t da = dlo(SB0 + SM_RA, 16) + s * (A_BYTES >> 4) + wg * 512;
        const uint32_t db = dlo(SB0 + SM_RB, 4096) + s * (B_BYTES >> 4);
        wgmma_fence();
#pragma unroll
        for (int k = 0; k < 2; k++) {
          wgmma_ss_n192<0, 1, H64, H128>(acc0, da + k * 2, db + k * 128, (kt | k) != 0);
          wgmma_ss_n192<0, 1, H64, H128>(acc1, da + 256 + k * 2, db + k * 128, (kt | k) != 0);
        }
        wgmma_commit();
        wgmma_wait<1>();
        if (kt > 0 && wi < 2 && elect_one()) mbar_arrive_cluster((wi << 24) + SB0 + SM_BAR + 8 * (B_EMPTY + sprev));
        sprev = s;
        if (++s == STAGES) { s = 0; ph ^= 1; }
      }
#pragma unroll 1
      for (int kt = 0; kt < STAGES; kt++) {
        mbar_wait(BAR(B_FULL + s), ph);
        const uint32_t da = dlo(SB0 + SM_RA, 16) + s * (A_BYTES >> 4) + wg * 512;
        const uint32_t db = dlo(SB0 + SM_RB, 4096) + s * (B_BYTES >> 4);
        wgmma_fence();
        wgmma_ss_n192<0, 1, H64, H128>(acc0, da, db, 1);
        wgmma_ss_n192<0, 1, H64, H128>(acc0, da + 2, db + 128, 1);
        wgmma_commit();
        wgmma_wait<1>();
        if (kt == 0 && wi < 2 && elect_one()) mbar_arrive_cluster((wi << 24) + SB0 + SM_BAR + 8 * (B_EMPTY + 1));
        if (++s == STAGES) { s = 0; ph ^= 1; }
      }
      mbar_wait(BAR(B_RDY), 0);
    }
    const int trow = wg * 128 + wi * 16 + (lane & 15);
    const int chi = lane >> 4;
    uint32_t ak[16], aq[2][16];
    float p[4][16];
    auto catch_one = [&](int i) {
      const int s = (2 + (i >> 1)) % STAGES;
      wgmma_ss_n192<0, 1, H64, H128>(acc1, dlo(SB0 + SM_RA + s * A_BYTES + 4096 + (i & 1) * 32, 16) + wg * 512, dlo(SB0 + SM_RB + s * B_BYTES + (i & 1) * 2048, 4096), 1);
    };
    auto catch_up = [&](int s) { wgmma_fence(); catch_one(2 * s - 4); catch_one(2 * s - 3); wgmma_commit(); };
    auto store_v = [&](const float (&acc)[96], int mb) {
#pragma unroll
      for (int h = 0; h < 2; h++)
#pragma unroll
        for (int jj = 0; jj < 2; jj++) {
          const int o = 64 + h * 16 + jj * 8;
          stsm4(sb + SM_V + h * 16384 + (trow + mb * 64) * 64 + (((2 * jj + chi) ^ ((trow >> 1) & 3)) << 4),
                pack_bf16(acc[o], acc[o + 1]), pack_bf16(acc[o + 2], acc[o + 3]), pack_bf16(acc[o + 4], acc[o + 5]), pack_bf16(acc[o + 6], acc[o + 7]));
        }
    };
    const uint32_t pa = sb + SM_PHIK + (wi >> 1) * 16384 + wg * 8192 + (trow & 31) * 128 + ((chi ^ (trow & 7)) << 4);
    auto store_phi = [&](const uint32_t (&phi)[16], int h, int mb) { store_phi_k(phi, pa + (1 - h) * 32768 + mb * 4096); };
    auto hand_over = [&](int i, bool ok) { hand_over_smem(BAR(B_PHI + i), ok); };
    bool okk[3];
    {
      HState hs;
      uint32_t phi[16];
      float d0, d1;
      catch_up(2);
      wgmma_wait<1>();
      fence_regs(acc0);
      if (tid == 0) TSTAMP(2);
      store_v(acc0, 0);
      pack_frags<32>(acc0, ak);
      issue_feat(ak, p[0], p[1], SB0 + SM_WPHI);
      catch_up(3);
      pack_frags<0>(acc0, aq[0]);
      wgmma_wait<1>();
      fence_regs(p[0]); fence_regs(p[1]); keep_alive(ak);
      wgmma_fence();
#pragma unroll
      for (int i = 4; i < 4 + NFIRST; i++) catch_one(i);
      okk[0] = hedgehog_fast<true>(p[0], phi, d0, d1);
      store_phi(phi, 0, 0);
#pragma unroll
      for (int i = 4 + NFIRST; i < 12; i++) catch_one(i);
      wgmma_commit();
      okk[0] &= hedgehog_fast<true>(p[1], phi, d0, d1);
      store_phi(phi, 1, 0);
      if (tid == 0) TSTAMP(17);
      wgmma_wait<0>();
      fence_regs(acc1);
      if (tid == 0) TSTAMP(27);
      if (wi < 2 && elect_one()) mbar_arrive_cluster((wi << 24) + SB0 + SM_BAR + 8 * (B_EMPTY + 1));
      pack_frags<32>(acc1, ak);
      issue_feat(ak, p[2], p[3], SB0 + SM_WPHI);
      store_v(acc1, 1);
      pack_frags<0>(acc1, aq[1]);
      wgmma_wait<0>();
      fence_regs(p[2]); fence_regs(p[3]); keep_alive(ak);
      asm volatile("setmaxnreg.dec.sync.aligned.u32 " STR(REG_C) ";");
      if (tid == 0) TSTAMP(28);
      HState h2;
      hedgehog_fast1(p[2], hs);
      hedgehog_fast1(p[3], h2);
      okk[1] = __all_sync(0xffffffffu, okk[0] & hedgehog_fast2<true>(hs, phi, d0, d1));
      store_phi(phi, 0, 1);
      hand_over(0, okk[1]);
      h2.s[0] += lds_f32(sb + SM_INFO + 12);
      okk[2] = __all_sync(0xffffffffu, okk[0] & hedgehog_fast2<true>(h2, phi, d0, d1));
      store_phi(phi, 1, 1);
      hand_over(1, okk[2]);
    }
    if (__builtin_expect(!(okk[1] & okk[2]), 0)) {
      __align__(16) float buf[64];
#pragma unroll
      for (int i = 0; i < 64; i++) buf[i] = p[i >> 4][i & 15];
      redo_phi_k(buf, okk[1] * 5 + okk[2] * 10, pa, BAR(B_PHI));
    }
    if (wi == 0 && lane == 0) TSTAMP(wg ? 29 : 3);
    mbar_wait(BAR(Q_AFTER), 0);
    uint32_t pq[4][16];
    float sc[8];
#pragma unroll
    for (int i = 0; i < 16; i++) { pq[2][i] = 0; pq[3][i] = 0; }
#pragma unroll
    for (int i = 4; i < 8; i++) sc[i] = 0.f;
#pragma unroll 1
    for (int mb = 0; mb < 2; mb++) {
      issue_feat(aq[0], p[0], p[1], SB0 + SM_WPHI);
#pragma unroll
      for (int i = 0; i < 16; i++) { pq[0][i] = pq[2][i]; pq[1][i] = pq[3][i]; }
#pragma unroll
      for (int i = 0; i < 4; i++) sc[i] = sc[4 + i];
      wgmma_wait<0>();
      fence_regs(p[0]); fence_regs(p[1]); keep_alive(aq[0]);
#pragma unroll
      for (int i = 0; i < 16; i++) aq[0][i] = aq[1][i];
      if (tid == 0 && mb == 0) TSTAMP(4);
      const bool ok = hedgehog_fast<false>(p[0], pq[2], sc[4], sc[5]) & hedgehog_fast<false>(p[1], pq[3], sc[6], sc[7]);
      if (__builtin_expect(!__all_sync(0xffffffffu, ok), 0)) {
        __align__(16) float buf[32];
#pragma unroll
        for (int i = 0; i < 32; i++) buf[i] = p[i >> 4][i & 15];
        hedgehog_slow(buf, 2);
#pragma unroll
        for (int i = 0; i < 32; i++) pq[2 + (i >> 4)][i & 15] = __float_as_uint(buf[i]);
#pragma unroll
        for (int i = 4; i < 8; i++) sc[i] = 1.0f;
      }
    }
    if (tid == 0) TSTAMP(5);
    float acc[64];
    const int wq = wg ^ half;
    const uint32_t xo = wq * 8192 + wi * 2048 + (lane & 15) * 128 + ((chi ^ (lane & 7)) << 4);
    const uint32_t ga = sb + SM_GATE + (half * 128 + wq * 64 + wi * 16) * 2;
    mbar_wait(BAR(B_XT + wq), 0);
    float gt[4];
#pragma unroll
    for (int i = 0; i < 4; i++) gt[i] = lds_bf16(sb + SM_GATE + (wg * 128 + (i >> 1) * 64 + wi * 16 + (i & 1) * 8 + (lane >> 2)) * 2);
    const float g0 = lds_bf16(ga + (lane >> 2) * 2), g1 = lds_bf16(ga + 16 + (lane >> 2) * 2);
    const unsigned routed = lds_u32(sb + SM_INFO + 4);
    const uint32_t par = lds_u32(sb + SM_INFO) & 1, tmask = (lane & 3) ? ~0u : ~1u, tbit = (lane & 3) ? 0u : par;
    mbar_wait(BAR(B_KVB), 0);
    if (tid == 0) TSTAMP(7);
    if (wg != half) mbar_wait(BAR(B_OP + half * 2 + O_YIELD - 1), 0);
    {
      float nd[4][20];
#pragma unroll
      for (int u = 0; u < 4; u++)
#pragma unroll
        for (int i = 0; i < 16; i++) asm volatile("" : "+r"(pq[u][i]) :: "memory");
      auto num = [&](int mb, int k0, int k1) {
#pragma unroll
        for (int kk = k0; kk < k1; kk++)
#pragma unroll
          for (int h = 0; h < 2; h++) {
            const int u = mb * 2 + h;
            wgmma_rs_n40<1, H64>(nd[u], pq[u][4 * kk], pq[u][4 * kk + 1], pq[u][4 * kk + 2], pq[u][4 * kk + 3],
                                 dlo(SB0 + SM_KVB + h * 4096 + kk * 1024, 8192 - h * 4096 + h * 16), kk != 0);
          }
        wgmma_commit();
      };
      wgmma_fence();
      num(0, 0, 4);
      if (O_OVL == 2) num(1, 0, 4);
#pragma unroll
      for (int mb = 0; mb < 2; mb++) {
        if (O_OVL == 2 && mb == 0) wgmma_wait<1>(); else wgmma_wait<0>();
        fence_regs(nd[2 * mb]); fence_regs(nd[2 * mb + 1]);
        if (O_OVL == 1 && mb == 0) { wgmma_fence(); num(1, 0, 4); }
        if (tid == 0 && mb == 0) TSTAMP(18);
#pragma unroll
        for (int h = 0; h < 2; h++) {
          const int u = mb * 2 + h;
          const float i0 = gt[2 * mb] * rcp(fmaf(sc[2 * u], 1e-6f, nd[u][16])), i1 = gt[2 * mb + 1] * rcp(fmaf(sc[2 * u + 1], 1e-6f, nd[u][18]));
#pragma unroll
          for (int jj = 0; jj < 2; jj++) {
            const int o = jj * 8;
            stsm4(sb + SM_O + (wg ^ half) * 16384 + ((trow & 63) + mb * 64) * 128 + (((h * 4 + 2 * jj + chi) ^ (trow & 7)) << 4),
                  (pack_bf16(nd[u][o] * i0, nd[u][o + 1] * i0) & tmask) | tbit, (pack_bf16(nd[u][o + 2] * i1, nd[u][o + 3] * i1) & tmask) | tbit,
                  pack_bf16(nd[u][o + 4] * i0, nd[u][o + 5] * i0), pack_bf16(nd[u][o + 6] * i1, nd[u][o + 7] * i1));
          }
        }
        fence_async_smem();
        __syncwarp();
        if (elect_one()) mbar_arrive(BAR(B_OP + wg * 2 + mb));
        if (!O_OVL && mb == 0) { wgmma_fence(); num(1, 0, 4); }
      }
#pragma unroll
      for (int u = 0; u < 4; u++)
#pragma unroll
        for (int i = 0; i < 16; i++) asm volatile("" :: "r"(pq[u][i]) : "memory");
    }
    if (tid == 0) TSTAMP(8);
    uint32_t stale = 0;
    {
      const uint32_t ca = sb - SB0 - (dlo(0, 16) << 4) + wi * 2048 + (lane >> 2) * 128 + ((((lane & 3) * 2) ^ (lane >> 2)) << 4);
      const uint32_t da_end = dlo(SB0 + SM_RA + NA2 * 16384, 16) + wq * 512, f_end = BAR(B_F2 + wq * 16 + 16);
      uint32_t da = da_end - 1024, db = dlo(SB0 + SM_RB + 4 * 16384, 8192), f = f_end - 128;
      uint32_t xs[32];
#pragma unroll
      for (int i = 0; i < 2; i++) {
        mbar_wait(f + i * 8, 0);
        wgmma_fence();
#pragma unroll
        for (int k = 0; k < 4; k++) wgmma_ss_n128<0, 1, H128, H128>(acc, da - i * 4096 + k * 2, db + i * 1024 + k * 128, (i | k) != 0);
        wgmma_commit();
        if (i == 0) {
          if ((routed >> 4) == tg * 16 + half * 8 + wq * 4 + wi) mbar_wait(BAR(B_Y), 0);
#pragma unroll
          for (int jj = 0; jj < 8; jj++)
            ldsm4(((sb + SM_XT + xo) ^ ((jj & 3) << 5)) + (jj >> 2) * 16384, xs[4 * jj], xs[4 * jj + 1], xs[4 * jj + 2], xs[4 * jj + 3]);
          fence_async_smem();
          __syncwarp();
          if (elect_one()) mbar_arrive_cluster(((XT_IN_A ? wq : rank) << 24) + SB0 + SM_BAR + 8 * (XT_IN_A ? B_GO + 3 : B_XTD));
        }
      }
      const float og0 = round_bf16(1.0f - g0), og1 = round_bf16(1.0f - g1);
      da -= 3072; db += 2048; f += 16;
      wgmma_wait<0>();
      fence_regs(acc);
      uint32_t dn = SB0 + SM_BAR + (wi ? (wq << 24) + 8 * (B_GO + NA2) : (rank << 24) + 8 * B_DB);
      if (wi < 2 && elect_one()) mbar_arrive_cluster(dn);
#pragma unroll
      for (int i = 0; i < 32; i++) { acc[2 * i] = fmaf((i & 1) ? og1 : og0, bf_lo(xs[i]), acc[2 * i]); acc[2 * i + 1] = fmaf((i & 1) ? og1 : og0, bf_hi(xs[i]), acc[2 * i + 1]); }
      fence_regs(acc);
      bool got = false;
#pragma unroll 1
      do {
        if (!got) mbar_wait(f, 0);
        wgmma_fence();
        wgmma_ss_n128<0, 1, H128, H128>(acc, da, db, 1);
        const uint32_t ta = ca + (da << 4), t0 = lds_u32(ta), t1 = lds_u32(ta + 1024);
        got = mbar_test(f + 8, 0);
#pragma unroll
        for (int k = 1; k < 4; k++) wgmma_ss_n128<0, 1, H128, H128>(acc, da + k * 2, db + k * 128, 1);
        wgmma_commit();
        da += 1024; if (da == da_end) da -= NA2 * 1024;
        db += 1024; if (db == dlo(SB0 + SM_RB + NB2 * 16384, 8192)) db -= NB2 * 1024;
        f += 8;
        stale |= (t0 ^ par) | (t1 ^ par);
        if (LEAD2 && wq == 0 && wi == 2 && f == f_end - 8 * LEAD_AT && elect_one()) mbar_arrive(BAR(B_F2 + 32 - LEAD2));
        wgmma_wait<1>();
        dn += 8;
        if (wi < 2 && f <= f_end - 32 && elect_one()) mbar_arrive_cluster(dn);
      } while (f != f_end);
      const uint32_t xa = sb + SM_RA + xo, xt = sb + SM_RA + wq * 8192 + wi * 2048;
      const int orow = tg * 256 + half * 128 + wq * 64 + wi * 16;
      const bool redo = __any_sync(0xffffffffu, stale & 1);
      wgmma_wait<0>();
      fence_regs(acc);
      if (wi == 0 && lane == 0) TSTAMP(wq ? 25 : 11);
      stage_out<0, 4>(acc, xa);
      fence_async_smem();
      __syncwarp();
      if (!redo && elect_one()) tma_store_2d(&maps.out, xt, ct * 128, orow);
      stage_out<4, 8>(acc, xa);
      if (__builtin_expect(redo, 0))
        redo_rows(o_piece(half, wq, 0), wo + ct * 128, g_z.done + tg * 16, x + (size_t)orow * D_ + ct * 128, xa, wi, ga, (int)routed - orow, sb + SM_UPD);
      fence_async_smem();
      __syncwarp();
      if (elect_one()) {
        tma_store_2d(&maps.out, xt + 16384, ct * 128 + 64, orow);
        if (redo) tma_store_2d(&maps.out, xt, ct * 128, orow);
      }
      bulk_commit();
      bulk_wait0_read();
    }
  }
}

typedef CUresult (*PFN_encodeTiled)(CUtensorMap*, CUtensorMapDataType, cuuint32_t, void*, const cuuint64_t*, const cuuint64_t*,
                                    const cuuint32_t*, const cuuint32_t*, CUtensorMapInterleave, CUtensorMapSwizzle,
                                    CUtensorMapL2promotion, CUtensorMapFloatOOBfill);
static void make_map(PFN_encodeTiled fn, CUtensorMap* m, const void* ptr, uint64_t rows, uint64_t cols, uint32_t brows, uint32_t bcols,
                     CUtensorMapSwizzle sw, CUtensorMapL2promotion prom) {
  cuuint64_t dims[2] = {cols, rows}; cuuint64_t strides[1] = {cols * 2}; cuuint32_t box[2] = {bcols, brows}; cuuint32_t es[2] = {1, 1};
  fn(m, CU_TENSOR_MAP_DATA_TYPE_BFLOAT16, 2, const_cast<void*>(ptr), dims, strides, box, es, CU_TENSOR_MAP_INTERLEAVE_NONE, sw, prom,
     CU_TENSOR_MAP_FLOAT_OOB_FILL_NONE);
}

extern "C" void kernel_launch(void* const* d_in, const int* in_sizes, int n_in, void* d_out, int out_size) {
  const __nv_bfloat16* x = (const __nv_bfloat16*)d_in[0];
  const __nv_bfloat16* wqkv = (const __nv_bfloat16*)d_in[1];
  const __nv_bfloat16* wphi = (const __nv_bfloat16*)d_in[2];
  const __nv_bfloat16* wo = (const __nv_bfloat16*)d_in[3];
  const __nv_bfloat16* w_r = (const __nv_bfloat16*)d_in[5];
  const __nv_bfloat16* w_gate = (const __nv_bfloat16*)d_in[6];
  const __nv_bfloat16* w_up = (const __nv_bfloat16*)d_in[7];
  const __nv_bfloat16* w_down = (const __nv_bfloat16*)d_in[8];
  const __nv_bfloat16* gate_w = (const __nv_bfloat16*)d_in[9];
  void* fp = nullptr; cudaDriverEntryPointQueryResult qr;
  cudaGetDriverEntryPoint("cuTensorMapEncodeTiled", &fp, cudaEnableDefault, &qr);
  PFN_encodeTiled fn = (PFN_encodeTiled)fp;
  Maps m;
  const CUtensorMapL2promotion P128 = CU_TENSOR_MAP_L2_PROMOTION_L2_128B;
  make_map(fn, &m.x, x, S_, D_, 128, 32, CU_TENSOR_MAP_SWIZZLE_64B, P128);
  {
    cuuint64_t dims[3] = {D_, D_, 3}; cuuint64_t strides[2] = {3 * D_ * 2, D_ * 2}; cuuint32_t box[3] = {64, 32, 3}; cuuint32_t es[3] = {1, 1, 1};
    fn(&m.w, CU_TENSOR_MAP_DATA_TYPE_BFLOAT16, 3, (void*)wqkv, dims, strides, box, es, CU_TENSOR_MAP_INTERLEAVE_NONE,
       CU_TENSOR_MAP_SWIZZLE_128B, P128, CU_TENSOR_MAP_FLOAT_OOB_FILL_NONE);
  }
  {
    cuuint64_t dims[3] = {64, D_, 16}; cuuint64_t strides[2] = {D_ * 2, 128}; cuuint32_t box[3] = {64, 64, 2}; cuuint32_t es[3] = {1, 1, 1};
    fn(&m.wo, CU_TENSOR_MAP_DATA_TYPE_BFLOAT16, 3, (void*)wo, dims, strides, box, es, CU_TENSOR_MAP_INTERLEAVE_NONE,
       CU_TENSOR_MAP_SWIZZLE_128B, P128, CU_TENSOR_MAP_FLOAT_OOB_FILL_NONE);
  }
  make_map(fn, &m.wphi, wphi, 1024, 32, 64, 32, CU_TENSOR_MAP_SWIZZLE_64B, P128);
  for (int i = 0; i < 3; i++) {
    cuuint64_t dims[3] = {i < 2 ? (cuuint64_t)F_ : 64, i < 2 ? (cuuint64_t)16 : F_, i < 2 ? (cuuint64_t)64 : 16};
    cuuint64_t strides[2] = {i < 2 ? (cuuint64_t)F_ * 2 : D_ * 2, i < 2 ? (cuuint64_t)F_ * 32 : 128};
    cuuint32_t box[3] = {64, i < 2 ? 16u : 4u, i < 2 ? 4u : 16u}; cuuint32_t es[3] = {1, 1, 1};
    fn(&m.wg + i, CU_TENSOR_MAP_DATA_TYPE_BFLOAT16, 3, (void*)(i == 0 ? w_gate : i == 1 ? w_up : w_down), dims, strides, box, es,
       CU_TENSOR_MAP_INTERLEAVE_NONE, CU_TENSOR_MAP_SWIZZLE_NONE, P128, CU_TENSOR_MAP_FLOAT_OOB_FILL_NONE);
  }
  make_map(fn, &m.xt, x, S_, D_, 64, 64, CU_TENSOR_MAP_SWIZZLE_128B, P128);
  make_map(fn, &m.out, d_out, S_, D_, 16, 64, CU_TENSOR_MAP_SWIZZLE_128B, P128);
  make_map(fn, &m.xr, x, S_, D_, 16, 128, CU_TENSOR_MAP_SWIZZLE_NONE, P128);
  make_map(fn, &m.tg, w_gate, D_, F_, 64, 64, CU_TENSOR_MAP_SWIZZLE_NONE, P128);
  make_map(fn, &m.tu, w_up, D_, F_, 64, 64, CU_TENSOR_MAP_SWIZZLE_NONE, P128);
  make_map(fn, &m.td, w_down, F_ * 16, 64, 64, 64, CU_TENSOR_MAP_SWIZZLE_NONE, P128);
  make_map(fn, &m.to, wo, D_ * 16, 64, 64, 64, CU_TENSOR_MAP_SWIZZLE_NONE, P128);
  for (int cl = 0; cl < NCTA / 2; cl++) {
    const int col = cl < 4 ? 7 : cl < 36 ? ((cl - 4) & 3) + ((cl - 4) & 4) * 2 : (cl - 36) % 7 + ((cl - 36) % 7 < 3 ? 4 : 9);
    const int pos = cl < 4 ? cl : cl < 36 ? (cl - 4) >> 3 : (cl - 36) / 7;
    m.tile[cl] = ((col & 7) * 16 + (col >> 3) * 8 + pos * 2) | (EVEN_FFN ? cl * 2 : (col & 7) * 16 + (col >> 3) * 8 + pos * 2) << 8;
  }
  m.tile[NCTA / 2] = NCTA;
  cudaFuncSetAttribute(fused_kernel, cudaFuncAttributeMaxDynamicSharedMemorySize, SM_TOTAL);
  fused_kernel<<<NCTA + 2, 512, SM_TOTAL>>>(m, x, wo, w_r, gate_w);
}
```

```cpp
#include <cuda_runtime.h>
#include <cuda_bf16.h>
#include <cuda.h>
#include <stdint.h>

__device__ __forceinline__ uint32_t smem_u32(const void* p) { return (uint32_t)__cvta_generic_to_shared(p); }
__device__ __forceinline__ void mbar_init(uint32_t bar, uint32_t cnt) { asm volatile("mbarrier.init.shared::cta.b64 [%0], %1;" :: "r"(bar), "r"(cnt) : "memory"); }
__device__ __forceinline__ void mbar_expect_tx(uint32_t bar, uint32_t bytes) { asm volatile("mbarrier.arrive.expect_tx.shared::cta.b64 _, [%0], %1;" :: "r"(bar), "r"(bytes) : "memory"); }
__device__ __forceinline__ void mbar_arrive(uint32_t bar) { asm volatile("mbarrier.arrive.shared::cta.b64 _, [%0];" :: "r"(bar) : "memory"); }
__device__ __forceinline__ bool mbar_try_wait(uint32_t bar, uint32_t parity) {
  uint32_t ok;
  asm volatile("{\n.reg .pred p;\nmbarrier.try_wait.parity.shared::cta.b64 p, [%1], %2;\nselp.u32 %0, 1, 0, p;\n}" : "=r"(ok) : "r"(bar), "r"(parity) : "memory");
  return ok;
}
__device__ __forceinline__ bool mbar_test(uint32_t bar, uint32_t parity) {
  uint32_t ok;
  asm volatile("{\n.reg .pred p;\nmbarrier.test_wait.parity.shared::cta.b64 p, [%1], %2;\nselp.u32 %0, 1, 0, p;\n}" : "=r"(ok) : "r"(bar), "r"(parity) : "memory");
  return ok;
}
__device__ __forceinline__ void mbar_wait(uint32_t bar, uint32_t parity) {
#pragma unroll 1
  for (int it = 0; it < (1 << 22); it++) { if (mbar_try_wait(bar, parity)) return; }
  __trap();
}
__device__ __forceinline__ void tma_load_2d(uint32_t dst, const CUtensorMap* tm, int c0, int c1, uint32_t bar) {
  asm volatile("cp.async.bulk.tensor.2d.shared::cluster.global.mbarrier::complete_tx::bytes [%0], [%1, {%3, %4}], [%2];"
    :: "r"(dst), "l"(tm), "r"(bar), "r"(c0), "r"(c1) : "memory");
}
__device__ __forceinline__ void tma_load_2d_mc(uint32_t dst, const CUtensorMap* tm, int c0, int c1, uint32_t bar) {
  asm volatile("cp.async.bulk.tensor.2d.shared::cluster.global.mbarrier::complete_tx::bytes.multicast::cluster [%0], [%1, {%3, %4}], [%2], %5;"
    :: "r"(dst), "l"(tm), "r"(bar), "r"(c0), "r"(c1), "h"((uint16_t)3) : "memory");
}
__device__ __forceinline__ void mbar_arrive_cluster(uint32_t bar) { asm volatile("mbarrier.arrive.shared::cluster.b64 _, [%0];" :: "r"(bar) : "memory"); }
__device__ __forceinline__ void wgmma_fence() { asm volatile("wgmma.fence.sync.aligned;" ::: "memory"); }
__device__ __forceinline__ void wgmma_commit() { asm volatile("wgmma.commit_group.sync.aligned;" ::: "memory"); }
template <int N> __device__ __forceinline__ void wgmma_wait() { asm volatile("wgmma.wait_group.sync.aligned %0;" :: "n"(N) : "memory"); }
template <int N> __device__ __forceinline__ void fence_regs(float (&d)[N]) {
#pragma unroll
  for (int i = 0; i < N; i++) asm volatile("" : "+f"(d[i]) :: "memory");
}
__host__ __device__ constexpr uint32_t dlo(uint32_t addr, uint32_t lbo) { return (addr >> 4) | ((lbo >> 4) << 16); }
constexpr uint32_t H128 = (1024 >> 4) | (1u << 30);
constexpr uint32_t H64 = (512 >> 4) | (2u << 30);

template <int TA, int TB, uint32_t HA, uint32_t HB>
__device__ __forceinline__ void wgmma_ss_n192(float (&d)[96], uint32_t da, uint32_t db, int scale_d) {
  asm volatile("{\n.reg .pred p;\n.reg .b64 da, db;\nsetp.ne.b32 p, %98, 0;\nmov.b64 da, {%96, %101};\nmov.b64 db, {%97, %102};\n"
    "wgmma.mma_async.sync.aligned.m64n192k16.f32.bf16.bf16 {%0, %1, %2, %3, %4, %5, %6, %7, %8, %9, %10, %11, %12, %13, %14, %15, %16, %17, %18, %19, %20, %21, %22, %23, %24, %25, %26, %27, %28, %29, %30, %31, %32, %33, %34, %35, %36, %37, %38, %39, %40, %41, %42, %43, %44, %45, %46, %47, %48, %49, %50, %51, %52, %53, %54, %55, %56, %57, %58, %59, %60, %61, %62, %63, %64, %65, %66, %67, %68, %69, %70, %71, %72, %73, %74, %75, %76, %77, %78, %79, %80, %81, %82, %83, %84, %85, %86, %87, %88, %89, %90, %91, %92, %93, %94, %95}, da, db, p, 1, 1, %99, %100;\n}\n"
    : "+f"(d[0]), "+f"(d[1]), "+f"(d[2]), "+f"(d[3]), "+f"(d[4]), "+f"(d[5]), "+f"(d[6]), "+f"(d[7]), "+f"(d[8]), "+f"(d[9]), "+f"(d[10]), "+f"(d[11]), "+f"(d[12]), "+f"(d[13]), "+f"(d[14]), "+f"(d[15]), "+f"(d[16]), "+f"(d[17]), "+f"(d[18]), "+f"(d[19]), "+f"(d[20]), "+f"(d[21]), "+f"(d[22]), "+f"(d[23]), "+f"(d[24]), "+f"(d[25]), "+f"(d[26]), "+f"(d[27]), "+f"(d[28]), "+f"(d[29]), "+f"(d[30]), "+f"(d[31]), "+f"(d[32]), "+f"(d[33]), "+f"(d[34]), "+f"(d[35]), "+f"(d[36]), "+f"(d[37]), "+f"(d[38]), "+f"(d[39]), "+f"(d[40]), "+f"(d[41]), "+f"(d[42]), "+f"(d[43]), "+f"(d[44]), "+f"(d[45]), "+f"(d[46]), "+f"(d[47]), "+f"(d[48]), "+f"(d[49]), "+f"(d[50]), "+f"(d[51]), "+f"(d[52]), "+f"(d[53]), "+f"(d[54]), "+f"(d[55]), "+f"(d[56]), "+f"(d[57]), "+f"(d[58]), "+f"(d[59]), "+f"(d[60]), "+f"(d[61]), "+f"(d[62]), "+f"(d[63]), "+f"(d[64]), "+f"(d[65]), "+f"(d[66]), "+f"(d[67]), "+f"(d[68]), "+f"(d[69]), "+f"(d[70]), "+f"(d[71]), "+f"(d[72]), "+f"(d[73]), "+f"(d[74]), "+f"(d[75]), "+f"(d[76]), "+f"(d[77]), "+f"(d[78]), "+f"(d[79]), "+f"(d[80]), "+f"(d[81]), "+f"(d[82]), "+f"(d[83]), "+f"(d[84]), "+f"(d[85]), "+f"(d[86]), "+f"(d[87]), "+f"(d[88]), "+f"(d[89]), "+f"(d[90]), "+f"(d[91]), "+f"(d[92]), "+f"(d[93]), "+f"(d[94]), "+f"(d[95])
    : "r"(da), "r"(db), "r"(scale_d), "n"(TA), "n"(TB), "n"(HA), "n"(HB));
}

template <int TA, int TB, uint32_t HA, uint32_t HB>
__device__ __forceinline__ void wgmma_ss_n128(float (&d)[64], uint32_t da, uint32_t db, int scale_d) {
  asm volatile("{\n.reg .pred p;\n.reg .b64 da, db;\nsetp.ne.b32 p, %66, 0;\nmov.b64 da, {%64, %69};\nmov.b64 db, {%65, %70};\n"
    "wgmma.mma_async.sync.aligned.m64n128k16.f32.bf16.bf16 {%0, %1, %2, %3, %4, %5, %6, %7, %8, %9, %10, %11, %12, %13, %14, %15, %16, %17, %18, %19, %20, %21, %22, %23, %24, %25, %26, %27, %28, %29, %30, %31, %32, %33, %34, %35, %36, %37, %38, %39, %40, %41, %42, %43, %44, %45, %46, %47, %48, %49, %50, %51, %52, %53, %54, %55, %56, %57, %58, %59, %60, %61, %62, %63}, da, db, p, 1, 1, %67, %68;\n}\n"
    : "+f"(d[0]), "+f"(d[1]), "+f"(d[2]), "+f"(d[3]), "+f"(d[4]), "+f"(d[5]), "+f"(d[6]), "+f"(d[7]), "+f"(d[8]), "+f"(d[9]), "+f"(d[10]), "+f"(d[11]), "+f"(d[12]), "+f"(d[13]), "+f"(d[14]), "+f"(d[15]), "+f"(d[16]), "+f"(d[17]), "+f"(d[18]), "+f"(d[19]), "+f"(d[20]), "+f"(d[21]), "+f"(d[22]), "+f"(d[23]), "+f"(d[24]), "+f"(d[25]), "+f"(d[26]), "+f"(d[27]), "+f"(d[28]), "+f"(d[29]), "+f"(d[30]), "+f"(d[31]), "+f"(d[32]), "+f"(d[33]), "+f"(d[34]), "+f"(d[35]), "+f"(d[36]), "+f"(d[37]), "+f"(d[38]), "+f"(d[39]), "+f"(d[40]), "+f"(d[41]), "+f"(d[42]), "+f"(d[43]), "+f"(d[44]), "+f"(d[45]), "+f"(d[46]), "+f"(d[47]), "+f"(d[48]), "+f"(d[49]), "+f"(d[50]), "+f"(d[51]), "+f"(d[52]), "+f"(d[53]), "+f"(d[54]), "+f"(d[55]), "+f"(d[56]), "+f"(d[57]), "+f"(d[58]), "+f"(d[59]), "+f"(d[60]), "+f"(d[61]), "+f"(d[62]), "+f"(d[63])
    : "r"(da), "r"(db), "r"(scale_d), "n"(TA), "n"(TB), "n"(HA), "n"(HB));
}

template <int TA, int TB, uint32_t HA, uint32_t HB>
__device__ __forceinline__ void wgmma_ss_n40(float (&d)[20], uint32_t da, uint32_t db, int scale_d) {
  asm volatile("{\n.reg .pred p;\n.reg .b64 da, db;\nsetp.ne.b32 p, %22, 0;\nmov.b64 da, {%20, %25};\nmov.b64 db, {%21, %26};\n"
    "wgmma.mma_async.sync.aligned.m64n40k16.f32.bf16.bf16 {%0, %1, %2, %3, %4, %5, %6, %7, %8, %9, %10, %11, %12, %13, %14, %15, %16, %17, %18, %19}, da, db, p, 1, 1, %23, %24;\n}\n"
    : "+f"(d[0]), "+f"(d[1]), "+f"(d[2]), "+f"(d[3]), "+f"(d[4]), "+f"(d[5]), "+f"(d[6]), "+f"(d[7]), "+f"(d[8]), "+f"(d[9]), "+f"(d[10]), "+f"(d[11]), "+f"(d[12]), "+f"(d[13]), "+f"(d[14]), "+f"(d[15]), "+f"(d[16]), "+f"(d[17]), "+f"(d[18]), "+f"(d[19])
    : "r"(da), "r"(db), "r"(scale_d), "n"(TA), "n"(TB), "n"(HA), "n"(HB));
}

template <int TB, uint32_t HB>
__device__ __forceinline__ void wgmma_rs_n32(float (&d)[16], uint32_t a0, uint32_t a1, uint32_t a2, uint32_t a3, uint32_t db, int scale_d) {
  asm volatile("{\n.reg .pred p;\n.reg .b64 db;\nsetp.ne.b32 p, %21, 0;\nmov.b64 db, {%20, %23};\n"
    "wgmma.mma_async.sync.aligned.m64n32k16.f32.bf16.bf16 {%0, %1, %2, %3, %4, %5, %6, %7, %8, %9, %10, %11, %12, %13, %14, %15}, {%16, %17, %18, %19}, db, p, 1, 1, %22;\n}\n"
    : "+f"(d[0]), "+f"(d[1]), "+f"(d[2]), "+f"(d[3]), "+f"(d[4]), "+f"(d[5]), "+f"(d[6]), "+f"(d[7]), "+f"(d[8]), "+f"(d[9]), "+f"(d[10]), "+f"(d[11]), "+f"(d[12]), "+f"(d[13]), "+f"(d[14]), "+f"(d[15])
    : "r"(a0), "r"(a1), "r"(a2), "r"(a3), "r"(db), "r"(scale_d), "n"(TB), "n"(HB));
}

template <int TB, uint32_t HB>
__device__ __forceinline__ void wgmma_rs_n40(float (&d)[20], uint32_t a0, uint32_t a1, uint32_t a2, uint32_t a3, uint32_t db, int scale_d) {
  asm volatile("{\n.reg .pred p;\n.reg .b64 db;\nsetp.ne.b32 p, %25, 0;\nmov.b64 db, {%24, %27};\n"
    "wgmma.mma_async.sync.aligned.m64n40k16.f32.bf16.bf16 {%0, %1, %2, %3, %4, %5, %6, %7, %8, %9, %10, %11, %12, %13, %14, %15, %16, %17, %18, %19}, {%20, %21, %22, %23}, db, p, 1, 1, %26;\n}\n"
    : "+f"(d[0]), "+f"(d[1]), "+f"(d[2]), "+f"(d[3]), "+f"(d[4]), "+f"(d[5]), "+f"(d[6]), "+f"(d[7]), "+f"(d[8]), "+f"(d[9]), "+f"(d[10]), "+f"(d[11]), "+f"(d[12]), "+f"(d[13]), "+f"(d[14]), "+f"(d[15]), "+f"(d[16]), "+f"(d[17]), "+f"(d[18]), "+f"(d[19])
    : "r"(a0), "r"(a1), "r"(a2), "r"(a3), "r"(db), "r"(scale_d), "n"(TB), "n"(HB));
}

constexpr int S_ = 2048, D_ = 1024, F_ = 3584;
constexpr int NCTA = 128;
#define NMOE_ 112
constexpr int NMOE = NMOE_;
#define KV16 1
constexpr int KVH = 5 * 128 * 2;

#define NY 8
struct Zeroed {
  float kv[32 * KVH];
  float y[NY * 2 * D_];
  unsigned hint[512];
  unsigned done[128];
  unsigned pad[384];
};
constexpr int ZB = KVH + 32 + NY * 64;
static_assert(sizeof(Zeroed) == NCTA * ZB, "zeroed block");
__device__ __align__(128) Zeroed g_z;
__device__ __align__(128) unsigned g_key[4 * NCTA];
__device__ __align__(128) unsigned g_ready[NCTA];
__device__ __align__(128) uint2 g_bcast[2 * 8 * 16];
__device__ __align__(128) unsigned g_gate[S_];
__device__ __align__(1024) __nv_bfloat16 g_o[S_ * D_];
#define TSTAMP(i)
#define GSTAMP(i)

constexpr int STAGES = 6, KT = 32;
constexpr int A_BYTES = 256 * 64, B_BYTES = 192 * 64, STAGE_BYTES = A_BYTES + B_BYTES;
constexpr int SM_RA = 0;
constexpr int SM_RB = STAGES * A_BYTES;
constexpr int SM_PHIK = 0;
constexpr int SM_V = 65536;
constexpr int SM_O = SM_V;
constexpr int NA2 = 5, NB2 = 7;
#define XT_IN_A 1
constexpr int SM_XT = (XT_IN_A ? SM_RA : SM_RB) + 2 * 16384;
constexpr int SM_XR = STAGES * STAGE_BYTES;
constexpr int SM_MOE = SM_XR;
constexpr int SM_XSEL = SM_XR + 36864;
constexpr int SM_RED = SM_XSEL + 2048;
constexpr int SM_WPHI = 212992;
constexpr int SM_KVB = SM_WPHI + 4096;
constexpr int SM_ONES = SM_KVB + 12288;
constexpr int SM_BAR = SM_ONES + 1024;
constexpr int SM_INFO = SM_BAR + 1008;
constexpr int SM_GATE = SM_BAR + 1024;
constexpr int SM_UPD = SM_GATE + 512;
constexpr int SM_TS = SM_UPD + 256;
constexpr int SM_TOTAL = SM_TS + 256;
static_assert(SM_TOTAL <= 232448 && ZB <= 4608, "smem");
static_assert(SM_WPHI % 1024 == 0 && SM_KVB % 1024 == 0 && SM_ONES % 1024 == 0, "align");
static_assert(SM_MOE + 40960 <= SM_WPHI && SM_RB + NB2 * 16384 <= SM_WPHI, "map");
#define QUAD 1
#define KV_OVL 0
#define K_SEQ 0
#define EXPT 0
#define PF_START 0
#define PF_OFF 0
#define KV_DELAY 1100
#define O_YIELD 1
#define TAILV -1
#define NFIRST 5
#define Q_AFTER B_PHI + 1
#define LEAD2 4
#define EVEN_FFN 1
#define KEY_SLEEP 0
#define B5_AFTER B_F2 + 2
#define REG_C 192
#define REG_K 88
#define STR2(x) #x
#define STR(x) STR2(x)
#define XT_H 0
#define EARLY_MAP 1
#define TILE_MODE 1
#define NPRE 1
#define O_OVL 1
#define LATE_SZ 8192
#define LATE_SLEEP 0
#define URG_STEP 0
#define LEAD_AT 1
#define XR_AFTER 3
#define LATE_DELAY 300
#define LATE_STEP 400

constexpr int B_FULL = 0, B_XR = 6, B_WPHI = 10;
constexpr int B_EMPTY = 11, B_XRD = 17;
constexpr int B_INIT = 123;
constexpr int B_ST = 18, B_MOE = 20, B_XSEL = 24, B_H = 25, B_RDY = 26, B_Y = 27, B_XT = 28, B_PEER = 30;
constexpr int B_FB2 = 31, B_F2 = 47;
constexpr int B_DB = 79;
constexpr int B_GO = 95;
constexpr int B_KVB = 111, B_OP = 112, B_MOEE = 116;
constexpr int B_PHI = 120, B_XTD = 122;
constexpr int NBAR = 123;
__host__ __device__ constexpr int bar_count(int i) {
  return (LEAD2 && i == B_F2 + 32 - LEAD2) ? 2 : i < B_DB ? 1 : i < B_GO ? 2 : (XT_IN_A && i == B_GO + 3) ? 9 : i < B_GO + NA2 ? 1 : i == B_GO + NA2 ? 5 : i < B_KVB ? 3 : i < B_PHI ? 4 : 8;
}

struct Maps { CUtensorMap x, w, wo, wphi, wg, wu, wd, tg, tu, td, to, xr, xt, out; int tile[NCTA / 2 + 1]; };

__device__ __forceinline__ uint32_t pack_bf16(float lo, float hi) {
  uint32_t r; asm("cvt.rn.bf16x2.f32 %0, %1, %2;" : "=r"(r) : "f"(hi), "f"(lo)); return r;
}
__device__ __forceinline__ float bf_lo(uint32_t v) { return __uint_as_float(v << 16); }
__device__ __forceinline__ float bf_hi(uint32_t v) { return __uint_as_float(v & 0xffff0000u); }
__device__ __forceinline__ float round_bf16(float v) { return __bfloat162float(__float2bfloat16_rn(v)); }
__device__ __forceinline__ float ex2(float v) { float r; asm("ex2.approx.ftz.f32 %0, %1;" : "=f"(r) : "f"(v)); return r; }
__device__ __forceinline__ float rcp(float v) { float r; asm("rcp.approx.ftz.f32 %0, %1;" : "=f"(r) : "f"(v)); return r; }
__device__ __forceinline__ void stsm4(uint32_t addr, uint32_t r0, uint32_t r1, uint32_t r2, uint32_t r3) {
  asm volatile("stmatrix.sync.aligned.m8n8.x4.shared.b16 [%0], {%1, %2, %3, %4};" :: "r"(addr), "r"(r0), "r"(r1), "r"(r2), "r"(r3) : "memory");
}
__device__ __forceinline__ void stsm2(uint32_t addr, uint32_t r0, uint32_t r1) {
  asm volatile("stmatrix.sync.aligned.m8n8.x2.shared.b16 [%0], {%1, %2};" :: "r"(addr), "r"(r0), "r"(r1) : "memory");
}
__device__ __forceinline__ uint2 lds64(uint32_t addr) {
  uint2 v; asm volatile("ld.shared.v2.u32 {%0, %1}, [%2];" : "=r"(v.x), "=r"(v.y) : "r"(addr) : "memory"); return v;
}
__device__ __forceinline__ void lds128x4(uint32_t addr, uint4& a, uint4& b, uint4& c, uint4& d) {
  asm volatile("ld.shared.v4.u32 {%0, %1, %2, %3}, [%16];\nld.shared.v4.u32 {%4, %5, %6, %7}, [%16 + 128];\n"
               "ld.shared.v4.u32 {%8, %9, %10, %11}, [%16 + 256];\nld.shared.v4.u32 {%12, %13, %14, %15}, [%16 + 384];"
    : "=r"(a.x), "=r"(a.y), "=r"(a.z), "=r"(a.w), "=r"(b.x), "=r"(b.y), "=r"(b.z), "=r"(b.w),
      "=r"(c.x), "=r"(c.y), "=r"(c.z), "=r"(c.w), "=r"(d.x), "=r"(d.y), "=r"(d.z), "=r"(d.w) : "r"(addr) : "memory");
}
__device__ __forceinline__ void ldsm4(uint32_t addr, uint32_t& r0, uint32_t& r1, uint32_t& r2, uint32_t& r3) {
  asm volatile("ldmatrix.sync.aligned.m8n8.x4.shared.b16 {%0, %1, %2, %3}, [%4];" : "=r"(r0), "=r"(r1), "=r"(r2), "=r"(r3) : "r"(addr) : "memory");
}
__device__ __forceinline__ uint4 lds128(uint32_t addr) {
  uint4 v; asm volatile("ld.shared.v4.u32 {%0, %1, %2, %3}, [%4];" : "=r"(v.x), "=r"(v.y), "=r"(v.z), "=r"(v.w) : "r"(addr) : "memory"); return v;
}
__device__ __forceinline__ void sts128(uint32_t addr, uint4 v) {
  asm volatile("st.shared.v4.u32 [%0], {%1, %2, %3, %4};" :: "r"(addr), "r"(v.x), "r"(v.y), "r"(v.z), "r"(v.w) : "memory");
}
__device__ __forceinline__ float lds_f32(uint32_t addr) { float v; asm volatile("ld.shared.f32 %0, [%1];" : "=f"(v) : "r"(addr) : "memory"); return v; }
__device__ __forceinline__ void sts_f32(uint32_t addr, float v) { asm volatile("st.shared.f32 [%0], %1;" :: "r"(addr), "f"(v) : "memory"); }
__device__ __forceinline__ uint32_t lds_u32(uint32_t addr) { uint32_t v; asm volatile("ld.shared.u32 %0, [%1];" : "=r"(v) : "r"(addr) : "memory"); return v; }
__device__ __forceinline__ void sts_u32(uint32_t addr, uint32_t v) { asm volatile("st.shared.u32 [%0], %1;" :: "r"(addr), "r"(v) : "memory"); }
__device__ __forceinline__ unsigned clock32() { unsigned c; asm volatile("mov.u32 %0, %%clock;" : "=r"(c)); return c; }
__device__ __forceinline__ bool elect_one() {
  uint32_t p; asm volatile("{\n.reg .pred q;\nelect.sync _|q, 0xffffffff;\nselp.u32 %0, 1, 0, q;\n}" : "=r"(p)); return p;
}
__device__ __forceinline__ void bar_sync(int id, int n) { asm volatile("bar.sync %0, %1;" :: "r"(id), "r"(n) : "memory"); }
__device__ __forceinline__ void fence_async_smem() { asm volatile("fence.proxy.async.shared::cta;" ::: "memory"); }
__device__ __forceinline__ void fence_async_all() { asm volatile("fence.proxy.async;" ::: "memory"); }
__device__ __forceinline__ void fence_gpu() { asm volatile("fence.acq_rel.gpu;" ::: "memory"); }
__device__ __forceinline__ unsigned ld_acquire(const unsigned* p) { unsigned v; asm volatile("ld.acquire.gpu.global.u32 %0, [%1];" : "=r"(v) : "l"(p) : "memory"); return v; }
__device__ __forceinline__ void red_release(unsigned* p, unsigned v) { asm volatile("red.release.gpu.global.add.u32 [%0], %1;" :: "l"(p), "r"(v) : "memory"); }
__device__ __forceinline__ void st_release(unsigned* p, unsigned v) { asm volatile("st.release.gpu.global.u32 [%0], %1;" :: "l"(p), "r"(v) : "memory"); }
__device__ __forceinline__ unsigned ld_relaxed(const unsigned* p) { unsigned v; asm volatile("ld.relaxed.gpu.global.u32 %0, [%1];" : "=r"(v) : "l"(p) : "memory"); return v; }
__device__ __forceinline__ void red_relaxed(unsigned* p, unsigned v) { asm volatile("red.relaxed.gpu.global.add.u32 [%0], %1;" :: "l"(p), "r"(v) : "memory"); }
__device__ __forceinline__ void st_relaxed(unsigned* p, unsigned v) { asm volatile("st.relaxed.gpu.global.u32 [%0], %1;" :: "l"(p), "r"(v) : "memory"); }
__device__ __forceinline__ void st_relaxed2(uint2* p, unsigned a, unsigned b) { asm volatile("st.relaxed.gpu.global.v2.u32 [%0], {%1, %2};" :: "l"(p), "r"(a), "r"(b) : "memory"); }
template <int SLEEP>
__device__ __forceinline__ unsigned wait_tagged(const uint2* p, unsigned tag) {
  uint2 v;
  int it = 0;
  do {
    if (SLEEP && it > 0) __nanosleep(SLEEP);
    asm volatile("ld.relaxed.gpu.global.v2.u32 {%0, %1}, [%2];" : "=r"(v.x), "=r"(v.y) : "l"(p) : "memory");
    if (++it > (1 << 20)) __trap();
  } while (!__all_sync(0xffffffffu, v.y == tag));
  return v.x;
}
__device__ __forceinline__ void wait_counter(const unsigned* p, unsigned target) {
#pragma unroll 1
  for (int it = 0; it < (1 << 20); it++) { if ((int)(ld_relaxed(p) - target) >= 0) return; }
  __trap();
}
__device__ __forceinline__ float4 ldg_l2(const float* p) {
  float4 v; asm volatile("ld.relaxed.gpu.global.v4.f32 {%0, %1, %2, %3}, [%4];" : "=f"(v.x), "=f"(v.y), "=f"(v.z), "=f"(v.w) : "l"(p) : "memory"); return v;
}
__device__ __forceinline__ float ldg_l2_f(const float* p) { float v; asm volatile("ld.relaxed.gpu.global.f32 %0, [%1];" : "=f"(v) : "l"(p) : "memory"); return v; }
__device__ __forceinline__ void sts64(uint32_t addr, float a, float b) { asm volatile("st.shared.v2.f32 [%0], {%1, %2};" :: "r"(addr), "f"(a), "f"(b) : "memory"); }
__device__ __forceinline__ void bulk_load(uint32_t dst, const void* src, uint32_t bytes, uint32_t bar) {
  asm volatile("cp.async.bulk.shared::cluster.global.mbarrier::complete_tx::bytes [%0], [%1], %2, [%3];" :: "r"(dst), "l"(src), "r"(bytes), "r"(bar) : "memory");
}
__device__ __forceinline__ void bulk_prefetch(const void* src, uint32_t bytes) {
  asm volatile("cp.async.bulk.prefetch.L2.global [%0], %1;" :: "l"(src), "r"(bytes) : "memory");
}
__device__ __forceinline__ void tma_store_2d(const CUtensorMap* tm, uint32_t src, int c0, int c1) {
  asm volatile("cp.async.bulk.tensor.2d.global.shared::cta.bulk_group [%0, {%2, %3}], [%1];" :: "l"(tm), "r"(src), "r"(c0), "r"(c1) : "memory");
}
__device__ __forceinline__ void bulk_store(void* dst, uint32_t src, uint32_t bytes) {
  asm volatile("cp.async.bulk.global.shared::cta.bulk_group [%0], [%1], %2;" :: "l"(dst), "r"(src), "r"(bytes) : "memory");
}
__device__ __forceinline__ void bulk_reduce_f32(void* dst, uint32_t src, uint32_t bytes) {
  asm volatile("cp.reduce.async.bulk.global.shared::cta.bulk_group.add.f32 [%0], [%1], %2;" :: "l"(dst), "r"(src), "r"(bytes) : "memory");
}
__device__ __forceinline__ void tma_load_3d(uint32_t dst, const CUtensorMap* tm, int c0, int c1, int c2, uint32_t bar) {
  asm volatile("cp.async.bulk.tensor.3d.shared::cluster.global.mbarrier::complete_tx::bytes [%0], [%1, {%3, %4, %5}], [%2];"
    :: "r"(dst), "l"(tm), "r"(bar), "r"(c0), "r"(c1), "r"(c2) : "memory");
}
__device__ __forceinline__ void cp_async16(uint32_t dst, const void* src) { asm volatile("cp.async.cg.shared.global [%0], [%1], 16;" :: "r"(dst), "l"(src) : "memory"); }
__device__ __forceinline__ void cp_async_commit() { asm volatile("cp.async.commit_group;" ::: "memory"); }
template <int N> __device__ __forceinline__ void cp_async_wait() { asm volatile("cp.async.wait_group %0;" :: "n"(N) : "memory"); }
__device__ __forceinline__ void prefetch_map(const CUtensorMap* tm) { asm volatile("prefetch.tensormap [%0];" :: "l"(tm) : "memory"); }
__device__ __forceinline__ void bulk_commit() { asm volatile("cp.async.bulk.commit_group;" ::: "memory"); }
__device__ __forceinline__ void bulk_wait0() { asm volatile("cp.async.bulk.wait_group 0;" ::: "memory"); }
__device__ __forceinline__ void bulk_wait0_read() { asm volatile("cp.async.bulk.wait_group.read 0;" ::: "memory"); }
__device__ __forceinline__ void mma16816(float& d0, float& d1, float& d2, float& d3, uint32_t a0, uint32_t a1, uint32_t a2, uint32_t a3, uint32_t b0, uint32_t b1) {
  asm volatile("mma.sync.aligned.m16n8k16.row.col.f32.bf16.bf16.f32 {%0, %1, %2, %3}, {%4, %5, %6, %7}, {%8, %9}, {%0, %1, %2, %3};"
    : "+f"(d0), "+f"(d1), "+f"(d2), "+f"(d3) : "r"(a0), "r"(a1), "r"(a2), "r"(a3), "r"(b0), "r"(b1));
}
__device__ __forceinline__ uint32_t hmul2(uint32_t a, uint32_t b) { uint32_t r; asm("mul.rn.bf16x2 %0, %1, %2;" : "=r"(r) : "r"(a), "r"(b)); return r; }
__device__ __forceinline__ uint32_t hfma2(uint32_t a, uint32_t b, uint32_t c) { uint32_t r; asm("fma.rn.bf16x2 %0, %1, %2, %3;" : "=r"(r) : "r"(a), "r"(b), "r"(c)); return r; }
__device__ __forceinline__ uint32_t hadd2(uint32_t a, uint32_t b) { uint32_t r; asm("add.rn.bf16x2 %0, %1, %2;" : "=r"(r) : "r"(a), "r"(b)); return r; }
__device__ __forceinline__ float sigmoidf_(float v) { return rcp(1.0f + ex2(v * -1.4426950408889634f)); }

__device__ __forceinline__ void hedgehog(const float (&p)[16], uint32_t (&phi)[16]) {
  float mx0 = p[0], mn0 = p[0], mx1 = p[2], mn1 = p[2];
#pragma unroll
  for (int j = 0; j < 4; j++) {
    mx0 = fmaxf(mx0, fmaxf(p[4 * j], p[4 * j + 1])); mn0 = fminf(mn0, fminf(p[4 * j], p[4 * j + 1]));
    mx1 = fmaxf(mx1, fmaxf(p[4 * j + 2], p[4 * j + 3])); mn1 = fminf(mn1, fminf(p[4 * j + 2], p[4 * j + 3]));
  }
#pragma unroll
  for (int o = 1; o <= 2; o <<= 1) {
    mx0 = fmaxf(mx0, __shfl_xor_sync(0xffffffffu, mx0, o)); mn0 = fminf(mn0, __shfl_xor_sync(0xffffffffu, mn0, o));
    mx1 = fmaxf(mx1, __shfl_xor_sync(0xffffffffu, mx1, o)); mn1 = fminf(mn1, __shfl_xor_sync(0xffffffffu, mn1, o));
  }
  float ep[16], en[16];
  float sp0 = 0.f, sn0 = 0.f, sp1 = 0.f, sn1 = 0.f;
#pragma unroll
  for (int j = 0; j < 4; j++) {
#pragma unroll
    for (int c = 0; c < 2; c++) {
      ep[4 * j + c] = ex2(p[4 * j + c] - mx0); en[4 * j + c] = ex2(mn0 - p[4 * j + c]);
      ep[4 * j + 2 + c] = ex2(p[4 * j + 2 + c] - mx1); en[4 * j + 2 + c] = ex2(mn1 - p[4 * j + 2 + c]);
      sp0 += ep[4 * j + c]; sn0 += en[4 * j + c]; sp1 += ep[4 * j + 2 + c]; sn1 += en[4 * j + 2 + c];
    }
  }
#pragma unroll
  for (int o = 1; o <= 2; o <<= 1) {
    sp0 += __shfl_xor_sync(0xffffffffu, sp0, o); sn0 += __shfl_xor_sync(0xffffffffu, sn0, o);
    sp1 += __shfl_xor_sync(0xffffffffu, sp1, o); sn1 += __shfl_xor_sync(0xffffffffu, sn1, o);
  }
  sp0 = rcp(sp0); sn0 = rcp(sn0); sp1 = rcp(sp1); sn1 = rcp(sn1);
#pragma unroll
  for (int j = 0; j < 4; j++) {
    phi[2 * j] = pack_bf16(ep[4 * j] * sp0, ep[4 * j + 1] * sp0);
    phi[2 * j + 1] = pack_bf16(ep[4 * j + 2] * sp1, ep[4 * j + 3] * sp1);
    phi[8 + 2 * j] = pack_bf16(en[4 * j + 1] * sn0, en[4 * j] * sn0);
    phi[8 + 2 * j + 1] = pack_bf16(en[4 * j + 3] * sn1, en[4 * j + 2] * sn1);
  }
}

__device__ __noinline__ void hedgehog_slow(float* buf, int n) {
#pragma unroll 1
  for (int u = 0; u < n; u++) {
    float p[16]; uint32_t phi[16];
#pragma unroll
    for (int i = 0; i < 16; i++) p[i] = buf[u * 16 + i];
    hedgehog(p, phi);
#pragma unroll
    for (int i = 0; i < 16; i++) buf[u * 16 + i] = __uint_as_float(phi[i]);
  }
}

__device__ __forceinline__ void store_phi_k(const uint32_t (&phi)[16], uint32_t a) {
#pragma unroll
  for (int jj = 0; jj < 4; jj++) stsm4(a ^ (jj << 5), phi[4 * jj], phi[4 * jj + 1], phi[4 * jj + 2], phi[4 * jj + 3]);
}
__device__ __forceinline__ void hand_over_smem(uint32_t bar, bool ok) {
  fence_async_smem();
  __syncwarp();
  if (elect_one() & ok) mbar_arrive(bar);
}
__device__ __noinline__ void redo_phi_k(float* buf, unsigned done, uint32_t pa, uint32_t bar) {
  hedgehog_slow(buf, 4);
#pragma unroll 1
  for (int u = 0; u < 4; u++) {
    if ((done >> u) & 1) continue;
    uint32_t phi[16];
#pragma unroll
    for (int i = 0; i < 16; i++) phi[i] = __float_as_uint(buf[u * 16 + i]);
    store_phi_k(phi, pa + (~u & 1) * 32768 + (u >> 1) * 4096);
    if (u >= 2) hand_over_smem(bar + (u - 2) * 8, true);
  }
}

__device__ __forceinline__ uint32_t dup_lo(uint32_t v) { uint32_t r; asm("{\n.reg .b16 l, h;\nmov.b32 {l, h}, %1;\nmov.b32 %0, {l, l};\n}" : "=r"(r) : "r"(v)); return r; }
__device__ __forceinline__ uint32_t dup_hi(uint32_t v) { uint32_t r; asm("{\n.reg .b16 l, h;\nmov.b32 {l, h}, %1;\nmov.b32 %0, {h, h};\n}" : "=r"(r) : "r"(v)); return r; }
struct HState { uint32_t a[16]; float s[5]; };
__device__ __forceinline__ void hedgehog_fast1(const float (&p)[16], HState& a) {
  float sm[8], m[8], r[8];
#pragma unroll
  for (int i = 0; i < 8; i++) {
    const float t0 = ex2(p[2 * i]), t1 = ex2(p[2 * i + 1]);
    a.a[i] = pack_bf16(t0, t1); sm[i] = t0 + t1; m[i] = t0 * t1;
  }
  float mq[4];
#pragma unroll
  for (int i = 0; i < 4; i++) {
    mq[i] = m[2 * i] * m[2 * i + 1];
    const float R = rcp(mq[i]);
    r[2 * i] = R * m[2 * i + 1]; r[2 * i + 1] = R * m[2 * i];
  }
  a.s[4] = (mq[0] + mq[1]) + (mq[2] + mq[3]);
#pragma unroll
  for (int i = 0; i < 4; i++) {
    const uint32_t rr = pack_bf16(r[2 * i], r[2 * i + 1]);
    a.a[8 + 2 * i] = hmul2(a.a[2 * i], dup_lo(rr)); a.a[9 + 2 * i] = hmul2(a.a[2 * i + 1], dup_hi(rr));
  }
#pragma unroll
  for (int c = 0; c < 2; c++) {
    a.s[2 * c] = (sm[c] + sm[2 + c]) + (sm[4 + c] + sm[6 + c]);
    a.s[2 * c + 1] = fmaf(r[6 + c], sm[6 + c], fmaf(r[4 + c], sm[4 + c], fmaf(r[2 + c], sm[2 + c], r[c] * sm[c])));
  }
}
template <bool NORM>
__device__ __forceinline__ bool hedgehog_fast2(const HState& a, uint32_t (&phi)[16], float& s0, float& s1) {
  float s[4] = {a.s[0], a.s[1], a.s[2], a.s[3]};
#pragma unroll
  for (int o = 1; o <= 2; o <<= 1)
#pragma unroll
    for (int i = 0; i < 4; i++) s[i] += __shfl_xor_sync(0xffffffffu, s[i], o);
  const bool ok = ((s[0] + s[1]) + (s[2] + s[3]) <= 7.2e16f) & (a.s[4] <= 1.3e36f);
  if (NORM) {
    const float R0 = rcp(s[0] * s[1]), R1 = rcp(s[2] * s[3]);
    const uint32_t n0 = pack_bf16(R0 * s[1], R0 * s[0]), n1 = pack_bf16(R1 * s[3], R1 * s[2]);
#pragma unroll
    for (int i = 0; i < 8; i++) { phi[i] = hmul2(a.a[i], dup_lo((i & 1) ? n1 : n0)); phi[8 + i] = hmul2(a.a[8 + i], dup_hi((i & 1) ? n1 : n0)); }
  } else {
    const uint32_t n = pack_bf16(s[0] * rcp(s[1]), s[2] * rcp(s[3]));
    s0 = s[0]; s1 = s[2];
#pragma unroll
    for (int i = 0; i < 8; i++) { phi[i] = a.a[i]; phi[8 + i] = hmul2(a.a[8 + i], (i & 1) ? dup_hi(n) : dup_lo(n)); }
  }
  return ok;
}
template <bool NORM>
__device__ __forceinline__ bool hedgehog_fast(const float (&p)[16], uint32_t (&phi)[16], float& s0, float& s1) {
  HState a;
  hedgehog_fast1(p, a);
  return hedgehog_fast2<NORM>(a, phi, s0, s1);
}

template <int OFF>
__device__ __forceinline__ void pack_frags(const float (&acc)[96], uint32_t (&a)[16]) {
#pragma unroll
  for (int i = 0; i < 16; i++) a[i] = pack_bf16(acc[OFF + 2 * i], acc[OFF + 2 * i + 1]);
#pragma unroll
  for (int i = 0; i < 16; i++) asm volatile("" : "+r"(a[i]) :: "memory");
}
__device__ __forceinline__ void issue_feat(const uint32_t (&a)[16], float (&p0)[16], float (&p1)[16], uint32_t wphi) {
  wgmma_fence();
#pragma unroll
  for (int kk = 0; kk < 2; kk++) {
    wgmma_rs_n32<1, H64>(p0, a[4 * kk], a[4 * kk + 1], a[4 * kk + 2], a[4 * kk + 3], dlo(wphi + kk * 1024, 16), kk);
    wgmma_rs_n32<1, H64>(p1, a[8 + 4 * kk], a[8 + 4 * kk + 1], a[8 + 4 * kk + 2], a[8 + 4 * kk + 3], dlo(wphi + 2048 + kk * 1024, 16), kk);
  }
  wgmma_commit();
}
__device__ __forceinline__ void keep_alive(const uint32_t (&a)[16]) {
#pragma unroll
  for (int i = 0; i < 16; i++) asm volatile("" :: "r"(a[i]) : "memory");
}

__device__ __forceinline__ void fma8(float (&a)[8], float xv, const uint4& w) {
  a[0] = fmaf(xv, bf_lo(w.x), a[0]); a[1] = fmaf(xv, bf_hi(w.x), a[1]);
  a[2] = fmaf(xv, bf_lo(w.y), a[2]); a[3] = fmaf(xv, bf_hi(w.y), a[3]);
  a[4] = fmaf(xv, bf_lo(w.z), a[4]); a[5] = fmaf(xv, bf_hi(w.z), a[5]);
  a[6] = fmaf(xv, bf_lo(w.w), a[6]); a[7] = fmaf(xv, bf_hi(w.w), a[7]);
}

template <int J0, int J1>
__device__ __forceinline__ void stage_out(const float (&acc)[64], uint32_t xa) {
#pragma unroll
  for (int jj = J0; jj < J1; jj++)
    stsm4((xa ^ ((jj & 3) << 5)) + (jj >> 2) * 16384, pack_bf16(acc[8 * jj], acc[8 * jj + 1]), pack_bf16(acc[8 * jj + 2], acc[8 * jj + 3]),
          pack_bf16(acc[8 * jj + 4], acc[8 * jj + 5]), pack_bf16(acc[8 * jj + 6], acc[8 * jj + 7]));
}
__device__ __forceinline__ float lds_bf16(uint32_t addr) {
  unsigned short v; asm volatile("ld.shared.u16 %0, [%1];" : "=h"(v) : "r"(addr) : "memory"); return __uint_as_float((uint32_t)v << 16);
}
__device__ __noinline__ void redo_rows(const __nv_bfloat16* pieces, const __nv_bfloat16* wo_cols, const unsigned* done, const __nv_bfloat16* xrows,
                                       uint32_t xa, int wi, uint32_t gate, int routed, uint32_t upd) {
  const int lane = threadIdx.x & 31;
  int it = 0;
  while (!__all_sync(0xffffffffu, ld_acquire(done + (lane & 15)) != 0)) { if (++it > (1 << 20)) __trap(); }
  float acc[64];
  const int g = lane >> 2, q = lane & 3, r0 = wi * 16 + g;
#pragma unroll
  for (int i = 0; i < 32; i++) {
    const int r = g + (i & 1) * 8, c = (i >> 1) * 8 + q * 2;
    uint32_t v = *reinterpret_cast<const uint32_t*>(xrows + (size_t)r * D_ + c);
    if (r == routed) v = hadd2(v, lds_u32(upd + c * 2));
    const float og = round_bf16(1.0f - lds_bf16(gate + r * 2));
    acc[2 * i] = og * bf_lo(v); acc[2 * i + 1] = og * bf_hi(v);
  }
#pragma unroll 1
  for (int ks = 0; ks < 64; ks++) {
    const unsigned* pc = reinterpret_cast<const unsigned*>(pieces + (ks >> 2) * 4096) + r0 * 32 + q;
    const int c0 = ((2 * (ks & 3)) ^ (r0 & 7)) * 4, c1 = ((2 * (ks & 3) + 1) ^ (r0 & 7)) * 4;
    const uint32_t a0 = ld_relaxed(pc + c0), a1 = ld_relaxed(pc + 256 + c0), a2 = ld_relaxed(pc + c1), a3 = ld_relaxed(pc + 256 + c1);
    const unsigned short* wp = reinterpret_cast<const unsigned short*>(wo_cols) + (size_t)(ks * 16 + 2 * q) * D_ + g;
#pragma unroll
    for (int nb = 0; nb < 16; nb++) {
      const uint32_t b0 = wp[nb * 8] | ((uint32_t)wp[nb * 8 + D_] << 16), b1 = wp[nb * 8 + 8 * D_] | ((uint32_t)wp[nb * 8 + 9 * D_] << 16);
      mma16816(acc[4 * nb], acc[4 * nb + 1], acc[4 * nb + 2], acc[4 * nb + 3], a0, a1, a2, a3, b0, b1);
    }
  }
  __syncwarp();
  stage_out<0, 8>(acc, xa);
}

__global__ void __cluster_dims__(2, 1, 1) __launch_bounds__(512, 1)
fused_kernel(const __grid_constant__ Maps maps, const __nv_bfloat16* __restrict__ x,
             const __nv_bfloat16* __restrict__ wo, const __nv_bfloat16* __restrict__ w_r, const __nv_bfloat16* __restrict__ gate_w) {
  extern __shared__ __align__(1024) uint8_t smem_raw[];
  if (threadIdx.x == 0) { prefetch_map(&maps.w); prefetch_map(&maps.x); }
  const int tid = threadIdx.x, warp = __shfl_sync(0xffffffffu, tid >> 5, 0), lane = tid & 31;
  const int rank = blockIdx.x & 1;
  const unsigned cl = blockIdx.x >> 1, hi = (cl - 36) * 37 >> 8, lo7 = cl - 36 - hi * 7;
  const unsigned col = cl < 4 ? 7 : cl < 36 ? (cl & 3) + (~cl & 4) * 2 : lo7 + (lo7 < 3 ? 4 : 9), pos = cl < 4 ? cl : cl < 36 ? (cl - 4) >> 3 : hi;
  const int b = cl < 64 ? (col & 7) * 16 + (col & 8) + pos * 2 + rank : blockIdx.x;
  const int e = blockIdx.x;
  const int tg = b >> 4, hp = b & 15;
  const int half = hp >> 3, ct = hp & 7;
  constexpr uint32_t SB0 = 1024;
  const uint32_t sb = SB0 + ((uint32_t)rank << 24);
  auto BAR = [&](int i) { return sb + SM_BAR + 8 * i; };
  auto load_stage = [&](int kt, int s, bool mc) {
    const uint32_t a = sb + SM_RA + s * A_BYTES, full = BAR(B_FULL + s);
    mbar_expect_tx(full, STAGE_BYTES);
    tma_load_3d(sb + SM_RB + s * B_BYTES, &maps.w, hp * 64, kt * 32, 0, full);
    if (mc) tma_load_2d_mc(a + rank * 8192, &maps.x, kt * 32, tg * 256 + rank * 128, full);
    else { tma_load_2d(a, &maps.x, kt * 32, tg * 256, full); tma_load_2d(a + 8192, &maps.x, kt * 32, tg * 256 + 128, full); }
  };
  auto slice_of = [&](int i) { return (i < 2 ? ct ^ i : i < 8 ? i - 2 * (i - 2 < (ct & 6)) : i) ^ (half * 8); };
  auto load_b2 = [&](int i) {
    const int j = slice_of(i), sl = i + 4 - (i >= 3) * NB2 - (i >= 10) * NB2;
    mbar_expect_tx(BAR(B_FB2 + i), 16384);
    tma_load_3d(sb + SM_RB + sl * 16384, &maps.wo, 0, j * 64, ct * 2, BAR(B_FB2 + i));
  };
  auto load_xt = [&](int w) {
    mbar_expect_tx(BAR(B_XT + w), 16384);
    tma_load_2d(sb + SM_XT + w * 8192, &maps.xt, ct * 128, tg * 256 + half * 128 + w * 64, BAR(B_XT + w));
    tma_load_2d(sb + SM_XT + w * 8192 + 16384, &maps.xt, ct * 128 + 64, tg * 256 + half * 128 + w * 64, BAR(B_XT + w));
  };
  auto o_piece = [&](int hf, int mb, int j) { return g_o + (size_t)((((tg * 2 + hf) * 2 + mb) * 16 + j) * 4096); };

  if (b >= NCTA) {
    if (warp == 0 && b == NCTA) {
      const unsigned tag = (ld_relaxed(&g_bcast[0].y) + 1) & 0xfffu;
      unsigned val = 0;
#pragma unroll 1
      for (int round = 0; round < 2; round++) {
        const unsigned* arr = (round ? g_ready : g_key) + lane * 4;
        unsigned k[16], bad;
        int it = 0;
        do {
          bad = 0;
#pragma unroll
          for (int a = 0; a < 4; a++)
            asm volatile("ld.relaxed.gpu.global.v4.u32 {%0, %1, %2, %3}, [%4];" : "=r"(k[4 * a]), "=r"(k[4 * a + 1]), "=r"(k[4 * a + 2]), "=r"(k[4 * a + 3])
                         : "l"(arr + (round ? 0 : a * NCTA)) : "memory");
#pragma unroll
          for (int i = 0; i < 16; i++) bad |= k[i] ^ tag;
          if (++it > (1 << 20)) __trap();
        } while (!__all_sync(0xffffffffu, (bad & 0xfffu) == 0));
        if (round == 0) {
#pragma unroll
          for (int c = 0; c < 4; c++) {
            const unsigned m = max(max(k[c], k[4 + c]), max(k[8 + c], k[12 + c]));
            val = max(val, (m & 0xffff0000u) | ((127u - (lane * 4 + c)) << 4) | ((m >> 12) & 15u));
          }
          val = __reduce_max_sync(0xffffffffu, val);
        }
        if (lane < 8) st_relaxed2(g_bcast + round * 128 + lane * 16, val, tag);
        const uint32_t* xr = reinterpret_cast<const uint32_t*>(x + (size_t)(2047u - (val & 0x7ffu)) * D_);
        float l = 0.f;
#pragma unroll 4
        for (int i = lane; i < 512; i += 32) {
          const uint32_t pr = hmul2(__ldg(xr + i), __ldg(reinterpret_cast<const uint32_t*>(gate_w) + i));
          l += bf_lo(pr) + bf_hi(pr);
        }
#pragma unroll
        for (int o = 1; o <= 16; o <<= 1) l += __shfl_xor_sync(0xffffffffu, l, o);
        val = __float_as_uint(round_bf16(sigmoidf_(round_bf16(l)))) >> 16;
      }
    }
    return;
  }
  if (warp == 8) {
    if (elect_one()) {
      mbar_init(BAR(0), 1);
      if (NPRE > 1) { mbar_init(BAR(1), 1); mbar_init(BAR(2), 1); }
      if (NPRE > 0) fence_async_smem();
      TSTAMP(40);
      if (NPRE > 0) load_stage(0, 0, false);
      if (NPRE > 1) load_stage(1, 1, false);
      if (NPRE > 2) load_stage(2, 2, false);
      TSTAMP(41);
    }
  } else if (elect_one()) {
    const int i = 3 + warp - (warp > 8);
    mbar_init(BAR(i), i < B_EMPTY ? 1 : 4);
    if (NPRE < 2 && warp >= 14) mbar_init(BAR(warp - 13), 1);
    if (warp == 13) mbar_init(BAR(B_INIT), 3);
  }
  asm volatile("fence.mbarrier_init.release.cluster;" ::: "memory");
  __syncwarp();
  asm volatile("barrier.cluster.arrive.relaxed.aligned;" ::: "memory");
  auto cluster_wait = [&]() { asm volatile("barrier.cluster.wait.aligned;" ::: "memory"); };

  if (warp >= 12) {
    asm volatile("setmaxnreg.dec.sync.aligned.u32 40;");
    const int aw = warp - 12;
    cluster_wait();
    const unsigned old_key = ld_relaxed(g_key + aw * NCTA + b);
    const uint32_t zero = smem_u32(smem_raw) ^ sb;
    {
      float r[4], l[4];
#pragma unroll
      for (int t = 0; t < 4; t++) { r[t] = 0.f; l[t] = 0.f; }
      uint32_t xa = sb + SM_XR + aw * 1024 + lane * 8, wa = sb + SM_XR + 32768 + lane * 8;
#pragma unroll 1
      for (int i = 0; i < 8; i++) {
        if (!(i & 1)) mbar_wait(BAR(B_XR) + i * 4, 0);
        if (tid == 384 && i == 6) TSTAMP(30);
        uint2 wr = lds64(wa);
        const uint2 gw = lds64(wa + 2048);
        uint2 xv[4];
#pragma unroll
        for (int t = 0; t < 4; t++) xv[t] = lds64(xa + t * 256);
        xa += 4096; wa += 256;
        wr.x |= (xv[1].x | xv[2].x | xv[3].x) & zero;
#pragma unroll
        for (int t = 0; t < 4; t++) { r[t] = fmaf(bf_lo(xv[t].x), bf_lo(wr.x), r[t]); l[t] = fmaf(bf_lo(xv[t].x), bf_lo(gw.x), l[t]); }
#pragma unroll
        for (int t = 0; t < 4; t++) { r[t] = fmaf(bf_hi(xv[t].x), bf_hi(wr.x), r[t]); l[t] = fmaf(bf_hi(xv[t].x), bf_hi(gw.x), l[t]); }
#pragma unroll
        for (int t = 0; t < 4; t++) { r[t] = fmaf(bf_lo(xv[t].y), bf_lo(wr.y), r[t]); l[t] = fmaf(bf_lo(xv[t].y), bf_lo(gw.y), l[t]); }
#pragma unroll
        for (int t = 0; t < 4; t++) { r[t] = fmaf(bf_hi(xv[t].y), bf_hi(wr.y), r[t]); l[t] = fmaf(bf_hi(xv[t].y), bf_hi(gw.y), l[t]); }
      }
      float u[4];
#pragma unroll
      for (int t = 0; t < 4; t++) u[t] = ((lane & 4) ? l[t] : r[t]) + __shfl_xor_sync(0xffffffffu, (lane & 4) ? r[t] : l[t], 4);
      const float v0 = ((lane & 1) ? u[1] : u[0]) + __shfl_xor_sync(0xffffffffu, (lane & 1) ? u[0] : u[1], 1);
      const float v1 = ((lane & 1) ? u[3] : u[2]) + __shfl_xor_sync(0xffffffffu, (lane & 1) ? u[2] : u[3], 1);
      float v = ((lane & 2) ? v1 : v0) + __shfl_xor_sync(0xffffffffu, (lane & 2) ? v0 : v1, 2);
      v += __shfl_xor_sync(0xffffffffu, v, 8);
      v += __shfl_xor_sync(0xffffffffu, v, 16);
      v = round_bf16(v);
      unsigned k = __float_as_uint(v) >> 16;
      k = (k & 0x8000u) ? (~k & 0xffffu) : (k | 0x8000u);
      k = __reduce_max_sync(0xffffffffu, lane < 4 ? (k << 4) | (15u - (aw * 4 + lane)) : 0u);
      mbar_wait(BAR(B_INIT), 0);
      const unsigned tag = (old_key + 1) & 0xfffu;
      if (lane == 0) st_relaxed(g_key + aw * NCTA + b, (k << 12) | tag);
      if ((lane >> 2) == 1) st_relaxed(g_gate + b * 16 + aw * 4 + (lane & 3), __float_as_uint(round_bf16(sigmoidf_(v))) | tag);
    }
    if (tid == 384) { TSTAMP(31); GSTAMP(60); }
    fence_async_smem();
    __syncwarp();
    if (elect_one()) mbar_arrive(BAR(B_XRD));
    mbar_wait(BAR(B_XSEL), 0);
    if (tid == 384) TSTAMP(36);
    float ag[8];
#pragma unroll
    for (int i = 0; i < 8; i++) ag[i] = 0.f;
    if (e < NMOE) {
      const uint32_t lw = sb + SM_MOE + aw * 2048 + (lane >> 3) * 512 + (lane & 7) * 16;
      uint32_t lx = sb + SM_XSEL + aw * 32 + (lane >> 3) * 8, fb = BAR(B_MOE), wa = lw;
      bool got = false;
#pragma unroll 1
      for (int m = 0; m < 12; m++) {
#pragma unroll
        for (int c = 0; c < 2; c++) {
          if (!got) mbar_wait(fb + c * 8, (m >> 1) & 1);
          uint4 w0, w1, w2, w3;
          lds128x4(wa + c * 8192, w0, w1, w2, w3);
          uint2 xv = lds64(lx + c * 128);
          got = mbar_test(c ? fb ^ 16 : fb + 8, ((m + c) >> 1) & 1);
          const uint32_t dep = ((w0.x | w1.x | w2.x) | w3.x) & zero;
          xv.x |= dep;
          if (elect_one()) mbar_arrive(fb + dep + (B_MOEE - B_MOE + c) * 8);
          fma8(ag, bf_lo(xv.x), w0); fma8(ag, bf_hi(xv.x), w1); fma8(ag, bf_lo(xv.y), w2); fma8(ag, bf_hi(xv.y), w3);
        }
        fb ^= 16; wa = 2 * lw + 16384 - wa; lx += 256;
        if (m == 7) {
          int ln;
          asm volatile("mov.u32 %0, %%laneid;" : "=r"(ln));
#pragma unroll
          for (int i = 0; i < 4; i++) ag[i] = ((ln & 16) ? ag[4 + i] : ag[i]) + __shfl_xor_sync(0xffffffffu, (ln & 16) ? ag[i] : ag[4 + i], 16);
          const float v0 = ((ln & 8) ? ag[2] : ag[0]) + __shfl_xor_sync(0xffffffffu, (ln & 8) ? ag[0] : ag[2], 8);
          const float v1 = ((ln & 8) ? ag[3] : ag[1]) + __shfl_xor_sync(0xffffffffu, (ln & 8) ? ag[1] : ag[3], 8);
          const uint32_t own = (uint32_t)(ln & 4) << 22;
          asm volatile("st.async.shared::cluster.mbarrier::complete_tx::bytes.v2.f32 [%0], {%1, %2}, [%3];"
                       :: "r"(own + SB0 + SM_RED + rank * 512 + aw * 128 + (ln & 3) * 32 + (ln >> 3) * 8), "f"(v0), "f"(v1), "r"(own + SB0 + SM_BAR + 8 * B_H) : "memory");
          if (tid == 384) TSTAMP(39);
          mbar_wait(BAR(B_H), 0);
          const uint32_t ra = sb + SM_RED + ln * 4;
          float gv = round_bf16((lds_f32(ra) + lds_f32(ra + 128)) + (lds_f32(ra + 256) + lds_f32(ra + 384)));
          const float uv = round_bf16((lds_f32(ra + 512) + lds_f32(ra + 640)) + (lds_f32(ra + 768) + lds_f32(ra + 896)));
          gv = round_bf16(gv * sigmoidf_(gv));
          lx = sb + SM_XSEL + aw * 32;
          asm volatile("st.shared.b16 [%0], %1;" :: "r"(lx + (ln >> 2) * 128 + (ln & 3) * 2), "h"(__bfloat16_as_ushort(__float2bfloat16_rn(gv * uv))) : "memory");
          __syncwarp();
#pragma unroll
          for (int i = 0; i < 8; i++) ag[i] = 0.f;
          if (tid == 384) TSTAMP(33);
        }
      }
      mbar_wait(BAR(B_RDY), 0);
#pragma unroll
      for (int j = 0; j < 3; j++)
        asm volatile("red.global.add.v4.f32 [%0], {%1, %2, %3, %4};" :: "l"(g_z.y + (e & (NY - 1)) * 2 * D_ + (j * 128 + aw * 32 + lane) * 4),
                     "f"(ag[3 * j]), "f"(ag[3 * j + 1]), "f"(j < 2 ? ag[3 * j + 2] : 0.f), "f"(1.0f) : "memory");
    }
    fence_async_smem();
    if (tid == 384) TSTAMP(34);
    bar_sync(4, 128);
    if (aw < 3) {
      if (aw == 0) mbar_wait(BAR(B_PHI), 0);
      if (elect_one()) load_b2(aw);
      if (aw) {
#pragma unroll 1
        for (int i = 0; i < 16; i++) {
          mbar_wait(BAR(B_FB2 + i), 0);
          if (i == 0) mbar_wait(BAR(B_OP + half * 2 + aw - 1), 0);
          if (elect_one()) mbar_expect_tx(BAR(B_F2 + (aw - 1) * 16 + i), i ? 8192 : 0);
        }
      }
    } else {
      const uint4 info = lds128(sb + SM_INFO);
      int it = 0;
      if ((info.y >> 7) == tg * 2 + half) {
        mbar_wait(BAR(B_RDY), 0);
        const float rs = round_bf16(sigmoidf_(__uint_as_float(info.z)));
        float y[9];
        do {
          __nanosleep(100);
#pragma unroll
          for (int i = 0; i < 9; i++) y[i] = 0.f;
#pragma unroll 1
          for (int c = lane >> 4; c < NY; c += 2) {
            const float* yp = g_z.y + c * 2 * D_ + (ct * 16 + (lane & 15)) * 4;
            const float4 a0 = ldg_l2(yp), a1 = ldg_l2(yp + 512), a2 = ldg_l2(yp + 1024);
            y[0] += a0.x; y[1] += a0.y; y[2] += a0.z; y[3] += a1.x; y[4] += a1.y; y[5] += a1.z; y[6] += a2.x; y[7] += a2.y;
            y[8] += a0.w + a1.w + a2.w;
          }
#pragma unroll
          for (int i = 0; i < 9; i++) y[i] += __shfl_xor_sync(0xffffffffu, y[i], 16);
          if (++it > (1 << 20)) __trap();
        } while (!__all_sync(0xffffffffu, y[8] == 3.f * NMOE));
        const int w = (info.y >> 6) & 1, r = info.y & 63;
        mbar_wait(BAR(B_XT + w), 0);
        if (lane < 16) {
          const uint32_t ad = sb + SM_XT + w * 8192 + (lane >> 3) * 16384 + r * 128 + (((lane & 7) ^ (r & 7)) << 4), rs2 = pack_bf16(rs, rs);
          const uint4 xv = lds128(ad);
          const uint4 u = make_uint4(hmul2(pack_bf16(y[0], y[1]), rs2), hmul2(pack_bf16(y[2], y[3]), rs2), hmul2(pack_bf16(y[4], y[5]), rs2), hmul2(pack_bf16(y[6], y[7]), rs2));
          sts128(sb + SM_UPD + lane * 16, u);
          sts128(ad, make_uint4(hadd2(xv.x, u.x), hadd2(xv.y, u.y), hadd2(xv.z, u.z), hadd2(xv.w, u.w)));
        }
        asm volatile("fence.acq_rel.cta;" ::: "memory");
        __syncwarp();
        if (elect_one()) mbar_arrive(BAR(B_Y));
      }
    }
  } else if (warp >= 8) {
    asm volatile("setmaxnreg.dec.sync.aligned.u32 24;");
    cluster_wait();
    if (tid == 256) TSTAMP(58);
    if (warp != 8) {
      if (elect_one()) {
        if (smem_u32(smem_raw) != sb) __trap();
#pragma unroll 1
        for (int i = B_ST + warp - 9; i < NBAR; i += 3) mbar_init(BAR(i), bar_count(i));
        asm volatile("fence.mbarrier_init.release.cluster;" ::: "memory");
      }
#pragma unroll
      for (int i = 0; i < (ZB + 1535) / 1536; i++) sts128(sb + SM_KVB + (i * 96 + tid - 288) * 16, make_uint4(0, 0, 0, 0));
      if (warp < 11) sts128(sb + SM_ONES + (tid - 288) * 16, make_uint4(0x3f803f80u, 0x3f803f80u, 0x3f803f80u, 0x3f803f80u));
      hand_over_smem(BAR(B_INIT), true);
      if (tid == 288) TSTAMP(57);
    }
    if (warp == 8) {
      int s = NPRE, ph = 1;
#pragma unroll 1
      for (int kt = NPRE; kt < KT; kt++) {
        mbar_wait(BAR(B_EMPTY + s), ph);
        if (elect_one()) {
          load_stage(kt, s, true);
          const unsigned xc = kt - XR_AFTER;
          if (xc < 4) {
            mbar_expect_tx(BAR(B_XR + xc), xc ? 8192 : 12288);
            tma_load_2d(sb + SM_XR + xc * 8192, &maps.xr, xc * 256, b * 16, BAR(B_XR + xc));
            tma_load_2d(sb + SM_XR + xc * 8192 + 4096, &maps.xr, xc * 256 + 128, b * 16, BAR(B_XR + xc));
            if (xc == 0) { bulk_load(sb + SM_XR + 32768, w_r, 2048, BAR(B_XR)); bulk_load(sb + SM_XR + 34816, gate_w, 2048, BAR(B_XR)); }
          }
          const int pg = kt - STAGES - PF_START + PF_OFF;
          if (pg >= (e < NMOE ? PF_OFF : 24) && pg < 26 && (EXPT != 3 || pg >= 24)) {
            const CUtensorMap* tm = &maps.tg + (pg < 16 ? (b & 1) : pg < 24 ? 2 : 3);
            const int c0 = pg < 16 ? (e >> 1) * 64 : 0, c1 = (pg < 16 ? pg : pg < 24 ? e * 8 + pg - 16 : b * 2 + pg - 24) * 64;
            asm volatile("cp.async.bulk.prefetch.tensor.2d.L2.global [%0, {%1, %2}];" :: "l"(tm), "r"(c0), "r"(c1) : "memory");
          }
        }
        if (++s == STAGES) { s = 0; ph ^= 1; }
      }
      mbar_wait(BAR(B_EMPTY + 1), 1);
#pragma unroll 1
      for (int i = 3; i < (XT_IN_A ? NB2 : 5); i++)
        if (elect_one()) { if (!XT_IN_A) load_xt(i - 3); load_b2(i); }
    } else if (warp == 9) {
      const unsigned tag = (ld_relaxed(g_ready + b) + 1) & 0xfffu;
      if (elect_one()) {
        mbar_expect_tx(BAR(B_WPHI), 4096);
        tma_load_2d(sb + SM_WPHI, &maps.wphi, 0, hp * 64, BAR(B_WPHI));
      }
      mbar_wait(BAR(B_WPHI), 0);
#pragma unroll 1
      for (uint32_t ad = sb + SM_WPHI + lane * 16; ad < sb + SM_WPHI + 4096; ad += 512) {
        constexpr float L = 1.4426950408889634f;
        const uint4 w = lds128(ad);
        sts128(ad, make_uint4(pack_bf16(bf_lo(w.x) * L, bf_hi(w.x) * L), pack_bf16(bf_lo(w.y) * L, bf_hi(w.y) * L),
                              pack_bf16(bf_lo(w.z) * L, bf_hi(w.z) * L), pack_bf16(bf_lo(w.w) * L, bf_hi(w.w) * L)));
      }
      fence_async_smem();
      mbar_wait(BAR(B_XRD), 0);
      const unsigned best = __shfl_sync(0xffffffffu, wait_tagged<KEY_SLEEP>(g_bcast + tg * 16, tag), 0);
      const unsigned idx = 2047u - (best & 0x7ffu);
      unsigned u = best >> 16;
      u = (u & 0x8000u) ? (u & 0x7fffu) : (~u & 0xffffu);
      if (elect_one()) {
        sts128(sb + SM_INFO, make_uint4(tag, idx, u << 16, 0));
        mbar_expect_tx(BAR(B_H), 1024);
        mbar_expect_tx(BAR(B_XSEL), 2048);
        bulk_load(sb + SM_XSEL, x + (size_t)idx * D_, 2048, BAR(B_XSEL));
        TSTAMP(32); GSTAMP(61);
        bulk_store(reinterpret_cast<char*>(&g_z) + b * ZB, sb + SM_KVB, ZB);
      }
      bulk_commit(); bulk_wait0();
      fence_gpu();
      __syncwarp();
      if (lane == 0) { st_relaxed(g_ready + b, tag); TSTAMP(42); }
      int it = 0;
#pragma unroll 1
      for (int c = 0; c < 2; c++) {
        uint4 gv;
        do {
          asm volatile("ld.relaxed.gpu.global.v4.u32 {%0, %1, %2, %3}, [%4];" : "=r"(gv.x), "=r"(gv.y), "=r"(gv.z), "=r"(gv.w)
                       : "l"(g_gate + tg * 256 + c * 128 + lane * 4) : "memory");
          if (++it > (1 << 20)) __trap();
        } while (!__all_sync(0xffffffffu, (((gv.x ^ tag) | (gv.y ^ tag) | (gv.z ^ tag) | (gv.w ^ tag)) & 0xfffu) == 0));
        sts64(sb + SM_GATE + c * 256 + lane * 8, __uint_as_float(__byte_perm(gv.x, gv.y, 0x7632)), __uint_as_float(__byte_perm(gv.z, gv.w, 0x7632)));
      }
      const unsigned gsel = wait_tagged<200>(g_bcast + 128 + tg * 16, tag);
      if ((idx >> 8) == tg && lane == 0) asm volatile("st.shared.b16 [%0], %1;" :: "r"(sb + SM_GATE + (idx & 255) * 2), "h"((unsigned short)gsel) : "memory");
      __syncwarp();
      if (elect_one()) { mbar_arrive(BAR(B_RDY)); TSTAMP(43); }
    } else if (e < NMOE) {
      const int w = warp & 1;
      const CUtensorMap* tm = &maps.wg + rank;
      int c0 = (e >> 1) * 64, c1 = 0, c2 = 4 * w;
      uint32_t bar = BAR(B_MOE + w);
      mbar_wait(BAR(B_XRD), 0);
#pragma unroll 1
      for (int m = 0; m < 12; m++) {
        mbar_wait(bar + (B_MOEE - B_MOE) * 8, ((m >> 1) & 1) ^ 1);
        if (elect_one()) {
          mbar_expect_tx(bar, 8192);
          tma_load_3d(sb + SM_MOE + w * 8192 + (m & 1) * 16384, tm, c0, c1, c2, bar);
        }
        bar ^= 16;
        if (m < 7) c2 += 8; else c1 += 8;
        if (m == 7) { tm = &maps.wd; c0 = 0; c1 = e * 32 + w * 4; c2 = 0; }
      }
    }
    const int wi = warp - 8, st = tid - 256;
    bar_sync(5, 128);
    asm volatile("setmaxnreg.inc.sync.aligned.u32 " STR(REG_K) ";");
    {
      auto kv_half = [&](float (&d)[20], int h, int mb) {
#pragma unroll
        for (int i = 0; i < 8; i++)
          wgmma_ss_n40<1, 1, H128, H64>(d, dlo(SB0 + SM_PHIK + 32768, 16) - h * 2048 + (((i & 2) << 2) + (i & 4) + mb * 2 + (i & 1)) * 128,
                                        dlo(SB0 + SM_V, SM_ONES - SM_V) + (h * 16 + (i & 4) * 2 + mb * 4 + (i & 3)) * (64 - (64 << 16)), (mb | i) != 0);
      };
      auto kv_out = [&](float (&d)[20], int h) {
        fence_regs(d);
        float* dst = g_z.kv + (hp * 2 + h) * KVH + st * 2;
        const int q = lane & 3;
        uint32_t w[8];
#pragma unroll
        for (int i = 0; i < 8; i++) w[i] = pack_bf16(d[2 * i], d[2 * i + 1]);
#pragma unroll
        for (int c = 0; c < 4; c++)
          asm volatile("red.global.add.noftz.v2.bf16x2 [%0], {%1, %2};" :: "l"(dst + c * 256), "r"(w[2 * c]), "r"(q == c ? 0x3f80u : w[2 * c + 1]) : "memory");
        asm volatile("red.global.add.noftz.v2.bf16x2 [%0], {%1, %2};" :: "l"(dst + 1024), "r"((q & 2) ? ((q & 1) ? w[7] : w[5]) : ((q & 1) ? w[3] : w[1])),
                     "r"(q == 0 ? 0x3f80u : q == 1 ? pack_bf16(d[16], d[18]) : 0u) : "memory");
      };
#pragma unroll 1
      for (int h = 0; h < 2; h++) {
        float kv[20];
        mbar_wait(BAR(B_PHI + h), 0);
        if (st == 0) TSTAMP(23 + h);
        wgmma_fence();
        kv_half(kv, h, 0); kv_half(kv, h, 1);
        wgmma_commit();
        wgmma_wait<0>();
        if (st == 0) TSTAMP(21 + h);
        kv_out(kv, h);
        bar_sync(5, 128);
        if (XT_IN_A && h == XT_H && wi < 2 && elect_one()) load_xt(wi);
      }
      if (wi == 3 && elect_one()) mbar_arrive_cluster(BAR(B_PEER) ^ (1u << 24));
      if (st == 0) TSTAMP(13);
      const int f = wi * 16 + (lane & 15), sw = (f >> 1) & 3, chi = lane >> 4;
      uint2 v[10];
      const float* src = g_z.kv + hp * 2 * KVH + st * 2;
      const int q = lane & 3;
      { const unsigned c0 = clock32(); while (clock32() - c0 < KV_DELAY) {} }
      int it = 0;
      unsigned need = 0x3ff;
#pragma unroll
      for (int i = 0; i < 10; i++) v[i] = make_uint2(0, 0);
      do {
        if (++it > (1 << 20)) __trap();
        unsigned bad = 0;
        if (st == 0 && it == 1) TSTAMP(35);
#pragma unroll
        for (int i = 0; i < 10; i++)
          asm volatile("{\n.reg .pred p;\nsetp.ne.u32 p, %3, 0;\n@p ld.relaxed.gpu.global.v2.u32 {%0, %1}, [%2];\n}"
                       : "+r"(v[i].x), "+r"(v[i].y) : "l"(src + i * 256), "r"(need & (1u << i)) : "memory");
#pragma unroll
        for (int i = 0; i < 10; i++) bad |= (v[i].y != 0x4100u) << i;
        need = __reduce_or_sync(0xffffffffu, bad & ((0x21u << q) | (q ? 0u : 0x210u)));
        if (st == 0 && it == 1) TSTAMP(20);
      } while (need);
      uint32_t zz[2];
#pragma unroll
      for (int h = 0; h < 2; h++) {
        const uint2* w = v + h * 5;
        const uint32_t kb = sb + SM_KVB + h * 4096 + f * 64;
        zz[h] = __shfl_sync(0xffffffffu, w[4].y, (lane & 28) + 1);
        stsm4(kb + ((chi ^ sw) << 4), w[0].x, q == 0 ? w[4].x : w[0].y, w[1].x, q == 1 ? w[4].x : w[1].y);
        stsm4(kb + (((2 + chi) ^ sw) << 4), w[2].x, q == 2 ? w[4].x : w[2].y, w[3].x, q == 3 ? w[4].x : w[3].y);
      }
      stsm4(sb + SM_KVB + 8192 + f * 64 + ((chi ^ sw) << 4), zz[0], zz[0] >> 16, zz[1], zz[1] >> 16);
      fence_async_smem();
      __syncwarp();
      if (elect_one()) mbar_arrive(BAR(B_KVB));
    }
    {
      const int pm = wi >> 1;
      if (wi & 1) {
        const int hf = half ^ pm;
        mbar_wait(BAR(B_PEER), 0);
        mbar_wait(BAR(B_OP + hf * 2), 0);
        const unsigned c0 = clock32();
        while (clock32() - c0 < (unsigned)(pm ? LATE_DELAY + ct * LATE_STEP : (ct >> 2) * URG_STEP)) {}
        __syncwarp();
        auto to_partner = [&](int mb) {
          asm volatile("cp.async.bulk.shared::cluster.shared::cta.mbarrier::complete_tx::bytes [%0], [%1], 8192, [%2];"
                       :: "r"((sb ^ (1u << 24)) + SM_RA + mb * 8192), "r"(sb + SM_O + mb * 8192), "r"(BAR(B_F2 + mb * 16 + 1) ^ (1u << 24)) : "memory");
        };
        unsigned* hint = g_z.hint + (tg * 2 + hf) * 32 + hp;
        const int sz = pm ? LATE_SZ : 8192;
#pragma unroll 1
        for (int o = 0; o < 16384; o += sz) {
          const int mb = o >> 13;
          if (o == 8192) mbar_wait(BAR(B_OP + hf * 2 + 1), 0);
          if (elect_one()) bulk_store(reinterpret_cast<char*>(o_piece(hf, mb, hp)) + (o & 8191), sb + SM_O + pm * 16384 + o, sz);
          bulk_commit();
          if (pm == 0 && elect_one()) to_partner(mb);
          bulk_wait0();
          __syncwarp();
          if (((o + sz) & 8191) == 0 && lane == 0) { st_relaxed(hint + mb * 16, 1); TSTAMP((pm ? 37 : 15) + mb); }
        }
        if (lane == 0) mbar_arrive(BAR(B_ST + pm));
        if (pm == 0) {
          if (lane < 2) mbar_arrive_cluster((lane << 24) + SB0 + SM_BAR + 8 * (B_GO + NA2));
          mbar_wait(BAR(B5_AFTER), 0);
#pragma unroll 1
          for (int i = XT_IN_A ? NB2 : 5; i < 16; i++) {
            mbar_wait(i < NB2 ? BAR(B_XTD) : BAR(B_DB + i - NB2), 0);
            if (elect_one()) load_b2(i);
          }
        } else {
          mbar_wait(BAR(B_ST), 0);
          fence_gpu();
          if (lane == 0) st_relaxed(g_z.done + b, 1);
        }
      } else if (pm) {
        const __nv_bfloat16* src = o_piece(half, rank, half * 8);
        uint32_t dst = sb + SM_RA + 16384 + rank * 8192;
        mbar_wait(BAR(B_PEER), 0);
#pragma unroll 1
        for (int i = 2; i < 16; i++) {
          if (i == (ct & 6) + 2) src += 2 * 4096;
          if (i == 8) src -= half * 16 * 4096;
          mbar_wait(BAR(B_GO + i), 0);
          if (elect_one()) {
            asm volatile("cp.async.bulk.shared::cluster.global.mbarrier::complete_tx::bytes.multicast::cluster [%0], [%1], 8192, [%2], %3;"
                         :: "r"(dst), "l"(src), "r"(BAR(B_F2 + rank * 16 + i)), "h"((uint16_t)3) : "memory");
            if (i == 2) TSTAMP(19);
          }
          src += 4096;
          dst += (i == 5 || i == 10) ? -4 * 16384 : 16384;
        }
      } else {
        const unsigned* flag = g_z.hint + (tg * 2 + half) * 32 + rank * 16 + slice_of(lane & 15);
        bool seen = lane < 2 || lane > 15;
        mbar_wait(BAR(B_OP + half * 2 + rank), 0);
        int it = 0;
        do {
          if (ld_relaxed(flag) != 0 && !seen) {
            mbar_arrive(BAR(B_GO) + lane * 8);
            seen = true;
          }
          if (++it > (1 << 20)) __trap();
        } while (!__all_sync(0xffffffffu, seen));
      }
    }
  } else {
    asm volatile("setmaxnreg.inc.sync.aligned.u32 224;");
    const int wg = warp >> 2, wi = warp & 3;
    cluster_wait();
    if (tid == 0) TSTAMP(59);
    float acc0[96], acc1[96];
    {
      int s = 0, ph = 0, sprev = 0;
#pragma unroll 1
      for (int kt = 0; kt < KT - STAGES; kt++) {
        mbar_wait(BAR(B_FULL + s), ph);
        if (kt == 0 && tid == 0) TSTAMP(1);
        if (tid == 0 && !(kt & 1)) TSTAMP(44 + kt / 2);
        const uint32_t da = dlo(SB0 + SM_RA, 16) + s * (A_BYTES >> 4) + wg * 512;
        const uint32_t db = dlo(SB0 + SM_RB, 4096) + s * (B_BYTES >> 4);
        wgmma_fence();
#pragma unroll
        for (int k = 0; k < 2; k++) {
          wgmma_ss_n192<0, 1, H64, H128>(acc0, da + k * 2, db + k * 128, (kt | k) != 0);
          wgmma_ss_n192<0, 1, H64, H128>(acc1, da + 256 + k * 2, db + k * 128, (kt | k) != 0);
        }
        wgmma_commit();
        wgmma_wait<1>();
        if (kt > 0 && wi < 2 && elect_one()) mbar_arrive_cluster((wi << 24) + SB0 + SM_BAR + 8 * (B_EMPTY + sprev));
        sprev = s;
        if (++s == STAGES) { s = 0; ph ^= 1; }
      }
#pragma unroll 1
      for (int kt = 0; kt < STAGES; kt++) {
        mbar_wait(BAR(B_FULL + s), ph);
        const uint32_t da = dlo(SB0 + SM_RA, 16) + s * (A_BYTES >> 4) + wg * 512;
        const uint32_t db = dlo(SB0 + SM_RB, 4096) + s * (B_BYTES >> 4);
        wgmma_fence();
        wgmma_ss_n192<0, 1, H64, H128>(acc0, da, db, 1);
        wgmma_ss_n192<0, 1, H64, H128>(acc0, da + 2, db + 128, 1);
        wgmma_commit();
        wgmma_wait<1>();
        if (kt == 0 && wi < 2 && elect_one()) mbar_arrive_cluster((wi << 24) + SB0 + SM_BAR + 8 * (B_EMPTY + 1));
        if (++s == STAGES) { s = 0; ph ^= 1; }
      }
      mbar_wait(BAR(B_RDY), 0);
    }
    const int trow = wg * 128 + wi * 16 + (lane & 15);
    const int chi = lane >> 4;
    uint32_t ak[16], aq[2][16];
    float p[4][16];
    auto catch_one = [&](int i) {
      const int s = (2 + (i >> 1)) % STAGES;
      wgmma_ss_n192<0, 1, H64, H128>(acc1, dlo(SB0 + SM_RA + s * A_BYTES + 4096 + (i & 1) * 32, 16) + wg * 512, dlo(SB0 + SM_RB + s * B_BYTES + (i & 1) * 2048, 4096), 1);
    };
    auto catch_up = [&](int s) { wgmma_fence(); catch_one(2 * s - 4); catch_one(2 * s - 3); wgmma_commit(); };
    auto store_v = [&](const float (&acc)[96], int mb) {
#pragma unroll
      for (int h = 0; h < 2; h++)
#pragma unroll
        for (int jj = 0; jj < 2; jj++) {
          const int o = 64 + h * 16 + jj * 8;
          stsm4(sb + SM_V + h * 16384 + (trow + mb * 64) * 64 + (((2 * jj + chi) ^ ((trow >> 1) & 3)) << 4),
                pack_bf16(acc[o], acc[o + 1]), pack_bf16(acc[o + 2], acc[o + 3]), pack_bf16(acc[o + 4], acc[o + 5]), pack_bf16(acc[o + 6], acc[o + 7]));
        }
    };
    const uint32_t pa = sb + SM_PHIK + (wi >> 1) * 16384 + wg * 8192 + (trow & 31) * 128 + ((chi ^ (trow & 7)) << 4);
    auto store_phi = [&](const uint32_t (&phi)[16], int h, int mb) { store_phi_k(phi, pa + (1 - h) * 32768 + mb * 4096); };
    auto hand_over = [&](int i, bool ok) { hand_over_smem(BAR(B_PHI + i), ok); };
    bool okk[3];
    {
      HState hs;
      uint32_t phi[16];
      float d0, d1;
      catch_up(2);
      wgmma_wait<1>();
      fence_regs(acc0);
      if (tid == 0) TSTAMP(2);
      store_v(acc0, 0);
      pack_frags<32>(acc0, ak);
      issue_feat(ak, p[0], p[1], SB0 + SM_WPHI);
      catch_up(3);
      pack_frags<0>(acc0, aq[0]);
      wgmma_wait<1>();
      fence_regs(p[0]); fence_regs(p[1]); keep_alive(ak);
      wgmma_fence();
#pragma unroll
      for (int i = 4; i < 4 + NFIRST; i++) catch_one(i);
      okk[0] = hedgehog_fast<true>(p[0], phi, d0, d1);
      store_phi(phi, 0, 0);
#pragma unroll
      for (int i = 4 + NFIRST; i < 12; i++) catch_one(i);
      wgmma_commit();
      okk[0] &= hedgehog_fast<true>(p[1], phi, d0, d1);
      store_phi(phi, 1, 0);
      if (tid == 0) TSTAMP(17);
      wgmma_wait<0>();
      fence_regs(acc1);
      if (tid == 0) TSTAMP(27);
      if (wi < 2 && elect_one()) mbar_arrive_cluster((wi << 24) + SB0 + SM_BAR + 8 * (B_EMPTY + 1));
      pack_frags<32>(acc1, ak);
      issue_feat(ak, p[2], p[3], SB0 + SM_WPHI);
      store_v(acc1, 1);
      pack_frags<0>(acc1, aq[1]);
      wgmma_wait<0>();
      fence_regs(p[2]); fence_regs(p[3]); keep_alive(ak);
      asm volatile("setmaxnreg.dec.sync.aligned.u32 " STR(REG_C) ";");
      if (tid == 0) TSTAMP(28);
      HState h2;
      hedgehog_fast1(p[2], hs);
      hedgehog_fast1(p[3], h2);
      okk[1] = __all_sync(0xffffffffu, okk[0] & hedgehog_fast2<true>(hs, phi, d0, d1));
      store_phi(phi, 0, 1);
      hand_over(0, okk[1]);
      h2.s[0] += lds_f32(sb + SM_INFO + 12);
      okk[2] = __all_sync(0xffffffffu, okk[0] & hedgehog_fast2<true>(h2, phi, d0, d1));
      store_phi(phi, 1, 1);
      hand_over(1, okk[2]);
    }
    if (__builtin_expect(!(okk[1] & okk[2]), 0)) {
      __align__(16) float buf[64];
#pragma unroll
      for (int i = 0; i < 64; i++) buf[i] = p[i >> 4][i & 15];
      redo_phi_k(buf, okk[1] * 5 + okk[2] * 10, pa, BAR(B_PHI));
    }
    if (wi == 0 && lane == 0) TSTAMP(wg ? 29 : 3);
    mbar_wait(BAR(Q_AFTER), 0);
    uint32_t pq[4][16];
    float sc[8];
#pragma unroll
    for (int i = 0; i < 16; i++) { pq[2][i] = 0; pq[3][i] = 0; }
#pragma unroll
    for (int i = 4; i < 8; i++) sc[i] = 0.f;
#pragma unroll 1
    for (int mb = 0; mb < 2; mb++) {
      issue_feat(aq[0], p[0], p[1], SB0 + SM_WPHI);
#pragma unroll
      for (int i = 0; i < 16; i++) { pq[0][i] = pq[2][i]; pq[1][i] = pq[3][i]; }
#pragma unroll
      for (int i = 0; i < 4; i++) sc[i] = sc[4 + i];
      wgmma_wait<0>();
      fence_regs(p[0]); fence_regs(p[1]); keep_alive(aq[0]);
#pragma unroll
      for (int i = 0; i < 16; i++) aq[0][i] = aq[1][i];
      if (tid == 0 && mb == 0) TSTAMP(4);
      const bool ok = hedgehog_fast<false>(p[0], pq[2], sc[4], sc[5]) & hedgehog_fast<false>(p[1], pq[3], sc[6], sc[7]);
      if (__builtin_expect(!__all_sync(0xffffffffu, ok), 0)) {
        __align__(16) float buf[32];
#pragma unroll
        for (int i = 0; i < 32; i++) buf[i] = p[i >> 4][i & 15];
        hedgehog_slow(buf, 2);
#pragma unroll
        for (int i = 0; i < 32; i++) pq[2 + (i >> 4)][i & 15] = __float_as_uint(buf[i]);
#pragma unroll
        for (int i = 4; i < 8; i++) sc[i] = 1.0f;
      }
    }
    if (tid == 0) TSTAMP(5);
    float acc[64];
    const int wq = wg ^ half;
    const uint32_t xo = wq * 8192 + wi * 2048 + (lane & 15) * 128 + ((chi ^ (lane & 7)) << 4);
    const uint32_t ga = sb + SM_GATE + (half * 128 + wq * 64 + wi * 16) * 2;
    mbar_wait(BAR(B_XT + wq), 0);
    float gt[4];
#pragma unroll
    for (int i = 0; i < 4; i++) gt[i] = lds_bf16(sb + SM_GATE + (wg * 128 + (i >> 1) * 64 + wi * 16 + (i & 1) * 8 + (lane >> 2)) * 2);
    const float g0 = lds_bf16(ga + (lane >> 2) * 2), g1 = lds_bf16(ga + 16 + (lane >> 2) * 2);
    const unsigned routed = lds_u32(sb + SM_INFO + 4);
    const uint32_t par = lds_u32(sb + SM_INFO) & 1, tmask = (lane & 3) ? ~0u : ~1u, tbit = (lane & 3) ? 0u : par;
    mbar_wait(BAR(B_KVB), 0);
    if (tid == 0) TSTAMP(7);
    if (wg != half) mbar_wait(BAR(B_OP + half * 2 + O_YIELD - 1), 0);
    {
      float nd[4][20];
#pragma unroll
      for (int u = 0; u < 4; u++)
#pragma unroll
        for (int i = 0; i < 16; i++) asm volatile("" : "+r"(pq[u][i]) :: "memory");
      auto num = [&](int mb, int k0, int k1) {
#pragma unroll
        for (int kk = k0; kk < k1; kk++)
#pragma unroll
          for (int h = 0; h < 2; h++) {
            const int u = mb * 2 + h;
            wgmma_rs_n40<1, H64>(nd[u], pq[u][4 * kk], pq[u][4 * kk + 1], pq[u][4 * kk + 2], pq[u][4 * kk + 3],
                                 dlo(SB0 + SM_KVB + h * 4096 + kk * 1024, 8192 - h * 4096 + h * 16), kk != 0);
          }
        wgmma_commit();
      };
      wgmma_fence();
      num(0, 0, 4);
      if (O_OVL == 2) num(1, 0, 4);
#pragma unroll
      for (int mb = 0; mb < 2; mb++) {
        if (O_OVL == 2 && mb == 0) wgmma_wait<1>(); else wgmma_wait<0>();
        fence_regs(nd[2 * mb]); fence_regs(nd[2 * mb + 1]);
        if (O_OVL == 1 && mb == 0) { wgmma_fence(); num(1, 0, 4); }
        if (tid == 0 && mb == 0) TSTAMP(18);
#pragma unroll
        for (int h = 0; h < 2; h++) {
          const int u = mb * 2 + h;
          const float i0 = gt[2 * mb] * rcp(fmaf(sc[2 * u], 1e-6f, nd[u][16])), i1 = gt[2 * mb + 1] * rcp(fmaf(sc[2 * u + 1], 1e-6f, nd[u][18]));
#pragma unroll
          for (int jj = 0; jj < 2; jj++) {
            const int o = jj * 8;
            stsm4(sb + SM_O + (wg ^ half) * 16384 + ((trow & 63) + mb * 64) * 128 + (((h * 4 + 2 * jj + chi) ^ (trow & 7)) << 4),
                  (pack_bf16(nd[u][o] * i0, nd[u][o + 1] * i0) & tmask) | tbit, (pack_bf16(nd[u][o + 2] * i1, nd[u][o + 3] * i1) & tmask) | tbit,
                  pack_bf16(nd[u][o + 4] * i0, nd[u][o + 5] * i0), pack_bf16(nd[u][o + 6] * i1, nd[u][o + 7] * i1));
          }
        }
        fence_async_smem();
        __syncwarp();
        if (elect_one()) mbar_arrive(BAR(B_OP + wg * 2 + mb));
        if (!O_OVL && mb == 0) { wgmma_fence(); num(1, 0, 4); }
      }
#pragma unroll
      for (int u = 0; u < 4; u++)
#pragma unroll
        for (int i = 0; i < 16; i++) asm volatile("" :: "r"(pq[u][i]) : "memory");
    }
    if (tid == 0) TSTAMP(8);
    uint32_t stale = 0;
    {
      const uint32_t ca = sb - SB0 - (dlo(0, 16) << 4) + wi * 2048 + (lane >> 2) * 128 + ((((lane & 3) * 2) ^ (lane >> 2)) << 4);
      const uint32_t da_end = dlo(SB0 + SM_RA + NA2 * 16384, 16) + wq * 512, f_end = BAR(B_F2 + wq * 16 + 16);
      uint32_t da = da_end - 1024, db = dlo(SB0 + SM_RB + 4 * 16384, 8192), f = f_end - 128;
      uint32_t xs[32];
#pragma unroll
      for (int i = 0; i < 2; i++) {
        mbar_wait(f + i * 8, 0);
        wgmma_fence();
#pragma unroll
        for (int k = 0; k < 4; k++) wgmma_ss_n128<0, 1, H128, H128>(acc, da - i * 4096 + k * 2, db + i * 1024 + k * 128, (i | k) != 0);
        wgmma_commit();
        if (i == 0) {
          if ((routed >> 4) == tg * 16 + half * 8 + wq * 4 + wi) mbar_wait(BAR(B_Y), 0);
#pragma unroll
          for (int jj = 0; jj < 8; jj++)
            ldsm4(((sb + SM_XT + xo) ^ ((jj & 3) << 5)) + (jj >> 2) * 16384, xs[4 * jj], xs[4 * jj + 1], xs[4 * jj + 2], xs[4 * jj + 3]);
          fence_async_smem();
          __syncwarp();
          if (elect_one()) mbar_arrive_cluster(((XT_IN_A ? wq : rank) << 24) + SB0 + SM_BAR + 8 * (XT_IN_A ? B_GO + 3 : B_XTD));
        }
      }
      const float og0 = round_bf16(1.0f - g0), og1 = round_bf16(1.0f - g1);
      da -= 3072; db += 2048; f += 16;
      wgmma_wait<0>();
      fence_regs(acc);
      uint32_t dn = SB0 + SM_BAR + (wi ? (wq << 24) + 8 * (B_GO + NA2) : (rank << 24) + 8 * B_DB);
      if (wi < 2 && elect_one()) mbar_arrive_cluster(dn);
#pragma unroll
      for (int i = 0; i < 32; i++) { acc[2 * i] = fmaf((i & 1) ? og1 : og0, bf_lo(xs[i]), acc[2 * i]); acc[2 * i + 1] = fmaf((i & 1) ? og1 : og0, bf_hi(xs[i]), acc[2 * i + 1]); }
      fence_regs(acc);
      bool got = false;
#pragma unroll 1
      do {
        if (!got) mbar_wait(f, 0);
        wgmma_fence();
        wgmma_ss_n128<0, 1, H128, H128>(acc, da, db, 1);
        const uint32_t ta = ca + (da << 4), t0 = lds_u32(ta), t1 = lds_u32(ta + 1024);
        got = mbar_test(f + 8, 0);
#pragma unroll
        for (int k = 1; k < 4; k++) wgmma_ss_n128<0, 1, H128, H128>(acc, da + k * 2, db + k * 128, 1);
        wgmma_commit();
        da += 1024; if (da == da_end) da -= NA2 * 1024;
        db += 1024; if (db == dlo(SB0 + SM_RB + NB2 * 16384, 8192)) db -= NB2 * 1024;
        f += 8;
        stale |= (t0 ^ par) | (t1 ^ par);
        if (LEAD2 && wq == 0 && wi == 2 && f == f_end - 8 * LEAD_AT && elect_one()) mbar_arrive(BAR(B_F2 + 32 - LEAD2));
        wgmma_wait<1>();
        dn += 8;
        if (wi < 2 && f <= f_end - 32 && elect_one()) mbar_arrive_cluster(dn);
      } while (f != f_end);
      const uint32_t xa = sb + SM_RA + xo, xt = sb + SM_RA + wq * 8192 + wi * 2048;
      const int orow = tg * 256 + half * 128 + wq * 64 + wi * 16;
      const bool redo = __any_sync(0xffffffffu, stale & 1);
      wgmma_wait<0>();
      fence_regs(acc);
      if (wi == 0 && lane == 0) TSTAMP(wq ? 25 : 11);
      stage_out<0, 4>(acc, xa);
      fence_async_smem();
      __syncwarp();
      if (!redo && elect_one()) tma_store_2d(&maps.out, xt, ct * 128, orow);
      stage_out<4, 8>(acc, xa);
      if (__builtin_expect(redo, 0))
        redo_rows(o_piece(half, wq, 0), wo + ct * 128, g_z.done + tg * 16, x + (size_t)orow * D_ + ct * 128, xa, wi, ga, (int)routed - orow, sb + SM_UPD);
      fence_async_smem();
      __syncwarp();
      if (elect_one()) {
        tma_store_2d(&maps.out, xt + 16384, ct * 128 + 64, orow);
        if (redo) tma_store_2d(&maps.out, xt, ct * 128, orow);
      }
      bulk_commit();
      bulk_wait0_read();
    }
  }
}

typedef CUresult (*PFN_encodeTiled)(CUtensorMap*, CUtensorMapDataType, cuuint32_t, void*, const cuuint64_t*, const cuuint64_t*,
                                    const cuuint32_t*, const cuuint32_t*, CUtensorMapInterleave, CUtensorMapSwizzle,
                                    CUtensorMapL2promotion, CUtensorMapFloatOOBfill);
static void make_map(PFN_encodeTiled fn, CUtensorMap* m, const void* ptr, uint64_t rows, uint64_t cols, uint32_t brows, uint32_t bcols,
                     CUtensorMapSwizzle sw, CUtensorMapL2promotion prom) {
  cuuint64_t dims[2] = {cols, rows}; cuuint64_t strides[1] = {cols * 2}; cuuint32_t box[2] = {bcols, brows}; cuuint32_t es[2] = {1, 1};
  fn(m, CU_TENSOR_MAP_DATA_TYPE_BFLOAT16, 2, const_cast<void*>(ptr), dims, strides, box, es, CU_TENSOR_MAP_INTERLEAVE_NONE, sw, prom,
     CU_TENSOR_MAP_FLOAT_OOB_FILL_NONE);
}

extern "C" void kernel_launch(void* const* d_in, const int* in_sizes, int n_in, void* d_out, int out_size) {
  const __nv_bfloat16* x = (const __nv_bfloat16*)d_in[0];
  const __nv_bfloat16* wqkv = (const __nv_bfloat16*)d_in[1];
  const __nv_bfloat16* wphi = (const __nv_bfloat16*)d_in[2];
  const __nv_bfloat16* wo = (const __nv_bfloat16*)d_in[3];
  const __nv_bfloat16* w_r = (const __nv_bfloat16*)d_in[5];
  const __nv_bfloat16* w_gate = (const __nv_bfloat16*)d_in[6];
  const __nv_bfloat16* w_up = (const __nv_bfloat16*)d_in[7];
  const __nv_bfloat16* w_down = (const __nv_bfloat16*)d_in[8];
  const __nv_bfloat16* gate_w = (const __nv_bfloat16*)d_in[9];
  void* fp = nullptr; cudaDriverEntryPointQueryResult qr;
  cudaGetDriverEntryPoint("cuTensorMapEncodeTiled", &fp, cudaEnableDefault, &qr);
  PFN_encodeTiled fn = (PFN_encodeTiled)fp;
  Maps m;
  const CUtensorMapL2promotion P128 = CU_TENSOR_MAP_L2_PROMOTION_L2_128B;
  make_map(fn, &m.x, x, S_, D_, 128, 32, CU_TENSOR_MAP_SWIZZLE_64B, P128);
  {
    cuuint64_t dims[3] = {D_, D_, 3}; cuuint64_t strides[2] = {3 * D_ * 2, D_ * 2}; cuuint32_t box[3] = {64, 32, 3}; cuuint32_t es[3] = {1, 1, 1};
    fn(&m.w, CU_TENSOR_MAP_DATA_TYPE_BFLOAT16, 3, (void*)wqkv, dims, strides, box, es, CU_TENSOR_MAP_INTERLEAVE_NONE,
       CU_TENSOR_MAP_SWIZZLE_128B, P128, CU_TENSOR_MAP_FLOAT_OOB_FILL_NONE);
  }
  {
    cuuint64_t dims[3] = {64, D_, 16}; cuuint64_t strides[2] = {D_ * 2, 128}; cuuint32_t box[3] = {64, 64, 2}; cuuint32_t es[3] = {1, 1, 1};
    fn(&m.wo, CU_TENSOR_MAP_DATA_TYPE_BFLOAT16, 3, (void*)wo, dims, strides, box, es, CU_TENSOR_MAP_INTERLEAVE_NONE,
       CU_TENSOR_MAP_SWIZZLE_128B, P128, CU_TENSOR_MAP_FLOAT_OOB_FILL_NONE);
  }
  make_map(fn, &m.wphi, wphi, 1024, 32, 64, 32, CU_TENSOR_MAP_SWIZZLE_64B, P128);
  for (int i = 0; i < 3; i++) {
    cuuint64_t dims[3] = {i < 2 ? (cuuint64_t)F_ : 64, i < 2 ? (cuuint64_t)16 : F_, i < 2 ? (cuuint64_t)64 : 16};
    cuuint64_t strides[2] = {i < 2 ? (cuuint64_t)F_ * 2 : D_ * 2, i < 2 ? (cuuint64_t)F_ * 32 : 128};
    cuuint32_t box[3] = {64, i < 2 ? 16u : 4u, i < 2 ? 4u : 16u}; cuuint32_t es[3] = {1, 1, 1};
    fn(&m.wg + i, CU_TENSOR_MAP_DATA_TYPE_BFLOAT16, 3, (void*)(i == 0 ? w_gate : i == 1 ? w_up : w_down), dims, strides, box, es,
       CU_TENSOR_MAP_INTERLEAVE_NONE, CU_TENSOR_MAP_SWIZZLE_NONE, P128, CU_TENSOR_MAP_FLOAT_OOB_FILL_NONE);
  }
  make_map(fn, &m.xt, x, S_, D_, 64, 64, CU_TENSOR_MAP_SWIZZLE_128B, P128);
  make_map(fn, &m.out, d_out, S_, D_, 16, 64, CU_TENSOR_MAP_SWIZZLE_128B, P128);
  make_map(fn, &m.xr, x, S_, D_, 16, 128, CU_TENSOR_MAP_SWIZZLE_NONE, P128);
  make_map(fn, &m.tg, w_gate, D_, F_, 64, 64, CU_TENSOR_MAP_SWIZZLE_NONE, P128);
  make_map(fn, &m.tu, w_up, D_, F_, 64, 64, CU_TENSOR_MAP_SWIZZLE_NONE, P128);
  make_map(fn, &m.td, w_down, F_ * 16, 64, 64, 64, CU_TENSOR_MAP_SWIZZLE_NONE, P128);
  make_map(fn, &m.to, wo, D_ * 16, 64, 64, 64, CU_TENSOR_MAP_SWIZZLE_NONE, P128);
  for (int cl = 0; cl < NCTA / 2; cl++) {
    const int col = cl < 4 ? 7 : cl < 36 ? ((cl - 4) & 3) + ((cl - 4) & 4) * 2 : (cl - 36) % 7 + ((cl - 36) % 7 < 3 ? 4 : 9);
    const int pos = cl < 4 ? cl : cl < 36 ? (cl - 4) >> 3 : (cl - 36) / 7;
    m.tile[cl] = ((col & 7) * 16 + (col >> 3) * 8 + pos * 2) | (EVEN_FFN ? cl * 2 : (col & 7) * 16 + (col >> 3) * 8 + pos * 2) << 8;
  }
  m.tile[NCTA / 2] = NCTA;
  cudaFuncSetAttribute(fused_kernel, cudaFuncAttributeMaxDynamicSharedMemorySize, SM_TOTAL);
  fused_kernel<<<NCTA + 2, 512, SM_TOTAL>>>(m, x, wo, w_r, gate_w);
}
```

```cpp
#include <cuda_runtime.h>
#include <cuda_bf16.h>
#include <cuda.h>
#include <stdint.h>

__device__ __forceinline__ uint32_t smem_u32(const void* p) { return (uint32_t)__cvta_generic_to_shared(p); }
__device__ __forceinline__ void mbar_init(uint32_t bar, uint32_t cnt) { asm volatile("mbarrier.init.shared::cta.b64 [%0], %1;" :: "r"(bar), "r"(cnt) : "memory"); }
__device__ __forceinline__ void mbar_expect_tx(uint32_t bar, uint32_t bytes) { asm volatile("mbarrier.arrive.expect_tx.shared::cta.b64 _, [%0], %1;" :: "r"(bar), "r"(bytes) : "memory"); }
__device__ __forceinline__ void mbar_arrive(uint32_t bar) { asm volatile("mbarrier.arrive.shared::cta.b64 _, [%0];" :: "r"(bar) : "memory"); }
__device__ __forceinline__ bool mbar_try_wait(uint32_t bar, uint32_t parity) {
  uint32_t ok;
  asm volatile("{\n.reg .pred p;\nmbarrier.try_wait.parity.shared::cta.b64 p, [%1], %2;\nselp.u32 %0, 1, 0, p;\n}" : "=r"(ok) : "r"(bar), "r"(parity) : "memory");
  return ok;
}
__device__ __forceinline__ bool mbar_test(uint32_t bar, uint32_t parity) {
  uint32_t ok;
  asm volatile("{\n.reg .pred p;\nmbarrier.test_wait.parity.shared::cta.b64 p, [%1], %2;\nselp.u32 %0, 1, 0, p;\n}" : "=r"(ok) : "r"(bar), "r"(parity) : "memory");
  return ok;
}
__device__ __forceinline__ void mbar_wait(uint32_t bar, uint32_t parity) {
  asm volatile("{\n.reg .pred p;\nWAIT: mbarrier.try_wait.parity.shared::cta.b64 p, [%0], %1;\n@!p bra.uni WAIT;\n}" :: "r"(bar), "r"(parity) : "memory");
}
__device__ __forceinline__ void mbar_wait_bounded(uint32_t bar, uint32_t parity) {
#pragma unroll 1
  for (int it = 0; it < (1 << 22); it++) { if (mbar_try_wait(bar, parity)) return; }
  __trap();
}
__device__ __forceinline__ void tma_load_2d(uint32_t dst, const CUtensorMap* tm, int c0, int c1, uint32_t bar) {
  asm volatile("cp.async.bulk.tensor.2d.shared::cluster.global.mbarrier::complete_tx::bytes [%0], [%1, {%3, %4}], [%2];"
    :: "r"(dst), "l"(tm), "r"(bar), "r"(c0), "r"(c1) : "memory");
}
__device__ __forceinline__ void tma_load_2d_mc(uint32_t dst, const CUtensorMap* tm, int c0, int c1, uint32_t bar) {
  asm volatile("cp.async.bulk.tensor.2d.shared::cluster.global.mbarrier::complete_tx::bytes.multicast::cluster [%0], [%1, {%3, %4}], [%2], %5;"
    :: "r"(dst), "l"(tm), "r"(bar), "r"(c0), "r"(c1), "h"((uint16_t)3) : "memory");
}
__device__ __forceinline__ void mbar_arrive_cluster(uint32_t bar) { asm volatile("mbarrier.arrive.shared::cluster.b64 _, [%0];" :: "r"(bar) : "memory"); }
__device__ __forceinline__ void wgmma_fence() { asm volatile("wgmma.fence.sync.aligned;" ::: "memory"); }
__device__ __forceinline__ void wgmma_commit() { asm volatile("wgmma.commit_group.sync.aligned;" ::: "memory"); }
template <int N> __device__ __forceinline__ void wgmma_wait() { asm volatile("wgmma.wait_group.sync.aligned %0;" :: "n"(N) : "memory"); }
template <int N> __device__ __forceinline__ void fence_regs(float (&d)[N]) {
#pragma unroll
  for (int i = 0; i < N; i++) asm volatile("" : "+f"(d[i]) :: "memory");
}
__host__ __device__ constexpr uint32_t dlo(uint32_t addr, uint32_t lbo) { return (addr >> 4) | ((lbo >> 4) << 16); }
constexpr uint32_t H128 = (1024 >> 4) | (1u << 30);
constexpr uint32_t H64 = (512 >> 4) | (2u << 30);

template <int TA, int TB, uint32_t HA, uint32_t HB>
__device__ __forceinline__ void wgmma_ss_n192(float (&d)[96], uint32_t da, uint32_t db, int scale_d) {
  asm volatile("{\n.reg .pred p;\n.reg .b64 da, db;\nsetp.ne.b32 p, %98, 0;\nmov.b64 da, {%96, %101};\nmov.b64 db, {%97, %102};\n"
    "wgmma.mma_async.sync.aligned.m64n192k16.f32.bf16.bf16 {%0, %1, %2, %3, %4, %5, %6, %7, %8, %9, %10, %11, %12, %13, %14, %15, %16, %17, %18, %19, %20, %21, %22, %23, %24, %25, %26, %27, %28, %29, %30, %31, %32, %33, %34, %35, %36, %37, %38, %39, %40, %41, %42, %43, %44, %45, %46, %47, %48, %49, %50, %51, %52, %53, %54, %55, %56, %57, %58, %59, %60, %61, %62, %63, %64, %65, %66, %67, %68, %69, %70, %71, %72, %73, %74, %75, %76, %77, %78, %79, %80, %81, %82, %83, %84, %85, %86, %87, %88, %89, %90, %91, %92, %93, %94, %95}, da, db, p, 1, 1, %99, %100;\n}\n"
    : "+f"(d[0]), "+f"(d[1]), "+f"(d[2]), "+f"(d[3]), "+f"(d[4]), "+f"(d[5]), "+f"(d[6]), "+f"(d[7]), "+f"(d[8]), "+f"(d[9]), "+f"(d[10]), "+f"(d[11]), "+f"(d[12]), "+f"(d[13]), "+f"(d[14]), "+f"(d[15]), "+f"(d[16]), "+f"(d[17]), "+f"(d[18]), "+f"(d[19]), "+f"(d[20]), "+f"(d[21]), "+f"(d[22]), "+f"(d[23]), "+f"(d[24]), "+f"(d[25]), "+f"(d[26]), "+f"(d[27]), "+f"(d[28]), "+f"(d[29]), "+f"(d[30]), "+f"(d[31]), "+f"(d[32]), "+f"(d[33]), "+f"(d[34]), "+f"(d[35]), "+f"(d[36]), "+f"(d[37]), "+f"(d[38]), "+f"(d[39]), "+f"(d[40]), "+f"(d[41]), "+f"(d[42]), "+f"(d[43]), "+f"(d[44]), "+f"(d[45]), "+f"(d[46]), "+f"(d[47]), "+f"(d[48]), "+f"(d[49]), "+f"(d[50]), "+f"(d[51]), "+f"(d[52]), "+f"(d[53]), "+f"(d[54]), "+f"(d[55]), "+f"(d[56]), "+f"(d[57]), "+f"(d[58]), "+f"(d[59]), "+f"(d[60]), "+f"(d[61]), "+f"(d[62]), "+f"(d[63]), "+f"(d[64]), "+f"(d[65]), "+f"(d[66]), "+f"(d[67]), "+f"(d[68]), "+f"(d[69]), "+f"(d[70]), "+f"(d[71]), "+f"(d[72]), "+f"(d[73]), "+f"(d[74]), "+f"(d[75]), "+f"(d[76]), "+f"(d[77]), "+f"(d[78]), "+f"(d[79]), "+f"(d[80]), "+f"(d[81]), "+f"(d[82]), "+f"(d[83]), "+f"(d[84]), "+f"(d[85]), "+f"(d[86]), "+f"(d[87]), "+f"(d[88]), "+f"(d[89]), "+f"(d[90]), "+f"(d[91]), "+f"(d[92]), "+f"(d[93]), "+f"(d[94]), "+f"(d[95])
    : "r"(da), "r"(db), "r"(scale_d), "n"(TA), "n"(TB), "n"(HA), "n"(HB));
}

template <int TA, int TB, uint32_t HA, uint32_t HB>
__device__ __forceinline__ void wgmma_ss_n128(float (&d)[64], uint32_t da, uint32_t db, int scale_d) {
  asm volatile("{\n.reg .pred p;\n.reg .b64 da, db;\nsetp.ne.b32 p, %66, 0;\nmov.b64 da, {%64, %69};\nmov.b64 db, {%65, %70};\n"
    "wgmma.mma_async.sync.aligned.m64n128k16.f32.bf16.bf16 {%0, %1, %2, %3, %4, %5, %6, %7, %8, %9, %10, %11, %12, %13, %14, %15, %16, %17, %18, %19, %20, %21, %22, %23, %24, %25, %26, %27, %28, %29, %30, %31, %32, %33, %34, %35, %36, %37, %38, %39, %40, %41, %42, %43, %44, %45, %46, %47, %48, %49, %50, %51, %52, %53, %54, %55, %56, %57, %58, %59, %60, %61, %62, %63}, da, db, p, 1, 1, %67, %68;\n}\n"
    : "+f"(d[0]), "+f"(d[1]), "+f"(d[2]), "+f"(d[3]), "+f"(d[4]), "+f"(d[5]), "+f"(d[6]), "+f"(d[7]), "+f"(d[8]), "+f"(d[9]), "+f"(d[10]), "+f"(d[11]), "+f"(d[12]), "+f"(d[13]), "+f"(d[14]), "+f"(d[15]), "+f"(d[16]), "+f"(d[17]), "+f"(d[18]), "+f"(d[19]), "+f"(d[20]), "+f"(d[21]), "+f"(d[22]), "+f"(d[23]), "+f"(d[24]), "+f"(d[25]), "+f"(d[26]), "+f"(d[27]), "+f"(d[28]), "+f"(d[29]), "+f"(d[30]), "+f"(d[31]), "+f"(d[32]), "+f"(d[33]), "+f"(d[34]), "+f"(d[35]), "+f"(d[36]), "+f"(d[37]), "+f"(d[38]), "+f"(d[39]), "+f"(d[40]), "+f"(d[41]), "+f"(d[42]), "+f"(d[43]), "+f"(d[44]), "+f"(d[45]), "+f"(d[46]), "+f"(d[47]), "+f"(d[48]), "+f"(d[49]), "+f"(d[50]), "+f"(d[51]), "+f"(d[52]), "+f"(d[53]), "+f"(d[54]), "+f"(d[55]), "+f"(d[56]), "+f"(d[57]), "+f"(d[58]), "+f"(d[59]), "+f"(d[60]), "+f"(d[61]), "+f"(d[62]), "+f"(d[63])
    : "r"(da), "r"(db), "r"(scale_d), "n"(TA), "n"(TB), "n"(HA), "n"(HB));
}

template <int TA, int TB, uint32_t HA, uint32_t HB>
__device__ __forceinline__ void wgmma_ss_n40(float (&d)[20], uint32_t da, uint32_t db, int scale_d) {
  asm volatile("{\n.reg .pred p;\n.reg .b64 da, db;\nsetp.ne.b32 p, %22, 0;\nmov.b64 da, {%20, %25};\nmov.b64 db, {%21, %26};\n"
    "wgmma.mma_async.sync.aligned.m64n40k16.f32.bf16.bf16 {%0, %1, %2, %3, %4, %5, %6, %7, %8, %9, %10, %11, %12, %13, %14, %15, %16, %17, %18, %19}, da, db, p, 1, 1, %23, %24;\n}\n"
    : "+f"(d[0]), "+f"(d[1]), "+f"(d[2]), "+f"(d[3]), "+f"(d[4]), "+f"(d[5]), "+f"(d[6]), "+f"(d[7]), "+f"(d[8]), "+f"(d[9]), "+f"(d[10]), "+f"(d[11]), "+f"(d[12]), "+f"(d[13]), "+f"(d[14]), "+f"(d[15]), "+f"(d[16]), "+f"(d[17]), "+f"(d[18]), "+f"(d[19])
    : "r"(da), "r"(db), "r"(scale_d), "n"(TA), "n"(TB), "n"(HA), "n"(HB));
}

template <int TB, uint32_t HB>
__device__ __forceinline__ void wgmma_rs_n32(float (&d)[16], uint32_t a0, uint32_t a1, uint32_t a2, uint32_t a3, uint32_t db, int scale_d) {
  asm volatile("{\n.reg .pred p;\n.reg .b64 db;\nsetp.ne.b32 p, %21, 0;\nmov.b64 db, {%20, %23};\n"
    "wgmma.mma_async.sync.aligned.m64n32k16.f32.bf16.bf16 {%0, %1, %2, %3, %4, %5, %6, %7, %8, %9, %10, %11, %12, %13, %14, %15}, {%16, %17, %18, %19}, db, p, 1, 1, %22;\n}\n"
    : "+f"(d[0]), "+f"(d[1]), "+f"(d[2]), "+f"(d[3]), "+f"(d[4]), "+f"(d[5]), "+f"(d[6]), "+f"(d[7]), "+f"(d[8]), "+f"(d[9]), "+f"(d[10]), "+f"(d[11]), "+f"(d[12]), "+f"(d[13]), "+f"(d[14]), "+f"(d[15])
    : "r"(a0), "r"(a1), "r"(a2), "r"(a3), "r"(db), "r"(scale_d), "n"(TB), "n"(HB));
}

template <int TB, uint32_t HB>
__device__ __forceinline__ void wgmma_rs_n40(float (&d)[20], uint32_t a0, uint32_t a1, uint32_t a2, uint32_t a3, uint32_t db, int scale_d) {
  asm volatile("{\n.reg .pred p;\n.reg .b64 db;\nsetp.ne.b32 p, %25, 0;\nmov.b64 db, {%24, %27};\n"
    "wgmma.mma_async.sync.aligned.m64n40k16.f32.bf16.bf16 {%0, %1, %2, %3, %4, %5, %6, %7, %8, %9, %10, %11, %12, %13, %14, %15, %16, %17, %18, %19}, {%20, %21, %22, %23}, db, p, 1, 1, %26;\n}\n"
    : "+f"(d[0]), "+f"(d[1]), "+f"(d[2]), "+f"(d[3]), "+f"(d[4]), "+f"(d[5]), "+f"(d[6]), "+f"(d[7]), "+f"(d[8]), "+f"(d[9]), "+f"(d[10]), "+f"(d[11]), "+f"(d[12]), "+f"(d[13]), "+f"(d[14]), "+f"(d[15]), "+f"(d[16]), "+f"(d[17]), "+f"(d[18]), "+f"(d[19])
    : "r"(a0), "r"(a1), "r"(a2), "r"(a3), "r"(db), "r"(scale_d), "n"(TB), "n"(HB));
}

constexpr int S_ = 2048, D_ = 1024, F_ = 3584;
constexpr int NCTA = 128;
#define NMOE_ 112
constexpr int NMOE = NMOE_;
#define KV16 1
constexpr int KVH = 5 * 128 * 2;

#define NY 8
struct Zeroed {
  float kv[32 * KVH];
  float y[NY * 2 * D_];
  unsigned hint[512];
  unsigned done[128];
  unsigned pad[384];
};
constexpr int ZB = KVH + 32 + NY * 64;
static_assert(sizeof(Zeroed) == NCTA * ZB, "zeroed block");
__device__ __align__(128) Zeroed g_z;
__device__ __align__(128) unsigned g_key[4 * NCTA];
__device__ __align__(128) unsigned g_ready[NCTA];
__device__ __align__(128) uint2 g_bcast[2 * 8 * 16];
__device__ __align__(128) unsigned g_gate[S_];
__device__ __align__(1024) __nv_bfloat16 g_o[S_ * D_];
#define TSTAMP(i)
#define GSTAMP(i)

constexpr int STAGES = 6, KT = 32;
constexpr int A_BYTES = 256 * 64, B_BYTES = 192 * 64, STAGE_BYTES = A_BYTES + B_BYTES;
constexpr int SM_RA = 0;
constexpr int SM_RB = STAGES * A_BYTES;
constexpr int SM_PHIK = 0;
constexpr int SM_V = 65536;
constexpr int SM_O = SM_V;
constexpr int NA2 = 5, NB2 = 7;
#define XT_IN_A 1
constexpr int SM_XT = (XT_IN_A ? SM_RA : SM_RB) + 2 * 16384;
constexpr int SM_XR = STAGES * STAGE_BYTES;
constexpr int SM_MOE = SM_XR;
constexpr int SM_XSEL = SM_XR + 36864;
constexpr int SM_RED = SM_XSEL + 2048;
constexpr int SM_WPHI = 212992;
constexpr int SM_KVB = SM_WPHI + 4096;
constexpr int SM_ONES = SM_KVB + 12288;
constexpr int SM_BAR = SM_ONES + 1024;
constexpr int SM_INFO = SM_BAR + 1008;
constexpr int SM_GATE = SM_BAR + 1024;
constexpr int SM_UPD = SM_GATE + 512;
constexpr int SM_TS = SM_UPD + 256;
constexpr int SM_TOTAL = SM_TS + 256;
static_assert(SM_TOTAL <= 232448 && ZB <= 4608, "smem");
static_assert(SM_WPHI % 1024 == 0 && SM_KVB % 1024 == 0 && SM_ONES % 1024 == 0, "align");
static_assert(SM_MOE + 40960 <= SM_WPHI && SM_RB + NB2 * 16384 <= SM_WPHI, "map");
#define QUAD 1
#define KV_OVL 0
#define K_SEQ 0
#define Q_UNROLL 1
#define EXPT 0
#define PF_START 0
#define PF_OFF 0
#define KV_DELAY 400
#define O_YIELD 1
#define TAILV -1
#define NFIRST 5
#define Q_AFTER B_PHI + 1
#define LEAD2 4
#define EVEN_FFN 1
#define KEY_SLEEP 0
#define B5_AFTER B_F2 + 2
#define REG_C 192
#define REG_K 88
#define STR2(x) #x
#define STR(x) STR2(x)
#define XT_H 0
#define EARLY_MAP 1
#define TILE_MODE 1
#define NPRE 1
#define O_OVL 1
#define LATE_SZ 8192
#define LATE_SLEEP 0
#define URG_STEP 0
#define LEAD_AT 1
#define XR_AFTER 3
#define LATE_DELAY 300
#define LATE_STEP 400

constexpr int B_FULL = 0, B_XR = 6, B_WPHI = 10;
constexpr int B_EMPTY = 11, B_XRD = 17;
constexpr int B_INIT = 123;
constexpr int B_ST = 18, B_MOE = 20, B_XSEL = 24, B_H = 25, B_RDY = 26, B_Y = 27, B_XT = 28, B_PEER = 30;
constexpr int B_FB2 = 31, B_F2 = 47;
constexpr int B_DB = 79;
constexpr int B_GO = 95;
constexpr int B_KVB = 111, B_OP = 112, B_MOEE = 116;
constexpr int B_PHI = 120, B_XTD = 122;
constexpr int NBAR = 123;
__host__ __device__ constexpr int bar_count(int i) {
  return (LEAD2 && i == B_F2 + 32 - LEAD2) ? 2 : i < B_DB ? 1 : i < B_GO ? 2 : (XT_IN_A && i == B_GO + 3) ? 9 : i < B_GO + NA2 ? 1 : i == B_GO + NA2 ? 5 : i < B_KVB ? 3 : i < B_PHI ? 4 : 8;
}

struct Maps { CUtensorMap x, w, wo, wphi, wg, wu, wd, tg, tu, td, to, xr, xt, out; int tile[NCTA / 2 + 1]; };

__device__ __forceinline__ uint32_t pack_bf16(float lo, float hi) {
  uint32_t r; asm("cvt.rn.bf16x2.f32 %0, %1, %2;" : "=r"(r) : "f"(hi), "f"(lo)); return r;
}
__device__ __forceinline__ float bf_lo(uint32_t v) { return __uint_as_float(v << 16); }
__device__ __forceinline__ float bf_hi(uint32_t v) { return __uint_as_float(v & 0xffff0000u); }
__device__ __forceinline__ float round_bf16(float v) { return __bfloat162float(__float2bfloat16_rn(v)); }
__device__ __forceinline__ float ex2(float v) { float r; asm("ex2.approx.ftz.f32 %0, %1;" : "=f"(r) : "f"(v)); return r; }
__device__ __forceinline__ float rcp(float v) { float r; asm("rcp.approx.ftz.f32 %0, %1;" : "=f"(r) : "f"(v)); return r; }
__device__ __forceinline__ void stsm4(uint32_t addr, uint32_t r0, uint32_t r1, uint32_t r2, uint32_t r3) {
  asm volatile("stmatrix.sync.aligned.m8n8.x4.shared.b16 [%0], {%1, %2, %3, %4};" :: "r"(addr), "r"(r0), "r"(r1), "r"(r2), "r"(r3) : "memory");
}
__device__ __forceinline__ void stsm2(uint32_t addr, uint32_t r0, uint32_t r1) {
  asm volatile("stmatrix.sync.aligned.m8n8.x2.shared.b16 [%0], {%1, %2};" :: "r"(addr), "r"(r0), "r"(r1) : "memory");
}
__device__ __forceinline__ uint2 lds64(uint32_t addr) {
  uint2 v; asm volatile("ld.shared.v2.u32 {%0, %1}, [%2];" : "=r"(v.x), "=r"(v.y) : "r"(addr) : "memory"); return v;
}
__device__ __forceinline__ void lds128x4(uint32_t addr, uint4& a, uint4& b, uint4& c, uint4& d) {
  asm volatile("ld.shared.v4.u32 {%0, %1, %2, %3}, [%16];\nld.shared.v4.u32 {%4, %5, %6, %7}, [%16 + 128];\n"
               "ld.shared.v4.u32 {%8, %9, %10, %11}, [%16 + 256];\nld.shared.v4.u32 {%12, %13, %14, %15}, [%16 + 384];"
    : "=r"(a.x), "=r"(a.y), "=r"(a.z), "=r"(a.w), "=r"(b.x), "=r"(b.y), "=r"(b.z), "=r"(b.w),
      "=r"(c.x), "=r"(c.y), "=r"(c.z), "=r"(c.w), "=r"(d.x), "=r"(d.y), "=r"(d.z), "=r"(d.w) : "r"(addr) : "memory");
}
__device__ __forceinline__ void ldsm4(uint32_t addr, uint32_t& r0, uint32_t& r1, uint32_t& r2, uint32_t& r3) {
  asm volatile("ldmatrix.sync.aligned.m8n8.x4.shared.b16 {%0, %1, %2, %3}, [%4];" : "=r"(r0), "=r"(r1), "=r"(r2), "=r"(r3) : "r"(addr) : "memory");
}
__device__ __forceinline__ uint4 lds128(uint32_t addr) {
  uint4 v; asm volatile("ld.shared.v4.u32 {%0, %1, %2, %3}, [%4];" : "=r"(v.x), "=r"(v.y), "=r"(v.z), "=r"(v.w) : "r"(addr) : "memory"); return v;
}
__device__ __forceinline__ void sts128(uint32_t addr, uint4 v) {
  asm volatile("st.shared.v4.u32 [%0], {%1, %2, %3, %4};" :: "r"(addr), "r"(v.x), "r"(v.y), "r"(v.z), "r"(v.w) : "memory");
}
__device__ __forceinline__ float lds_f32(uint32_t addr) { float v; asm volatile("ld.shared.f32 %0, [%1];" : "=f"(v) : "r"(addr) : "memory"); return v; }
__device__ __forceinline__ void sts_f32(uint32_t addr, float v) { asm volatile("st.shared.f32 [%0], %1;" :: "r"(addr), "f"(v) : "memory"); }
__device__ __forceinline__ uint32_t lds_u32(uint32_t addr) { uint32_t v; asm volatile("ld.shared.u32 %0, [%1];" : "=r"(v) : "r"(addr) : "memory"); return v; }
__device__ __forceinline__ void sts_u32(uint32_t addr, uint32_t v) { asm volatile("st.shared.u32 [%0], %1;" :: "r"(addr), "r"(v) : "memory"); }
__device__ __forceinline__ unsigned clock32() { unsigned c; asm volatile("mov.u32 %0, %%clock;" : "=r"(c)); return c; }
__device__ __forceinline__ bool elect_one() {
  uint32_t p; asm volatile("{\n.reg .pred q;\nelect.sync _|q, 0xffffffff;\nselp.u32 %0, 1, 0, q;\n}" : "=r"(p)); return p;
}
__device__ __forceinline__ void bar_sync(int id, int n) { asm volatile("bar.sync %0, %1;" :: "r"(id), "r"(n) : "memory"); }
__device__ __forceinline__ void fence_async_smem() { asm volatile("fence.proxy.async.shared::cta;" ::: "memory"); }
__device__ __forceinline__ void fence_async_all() { asm volatile("fence.proxy.async;" ::: "memory"); }
__device__ __forceinline__ void fence_gpu() { asm volatile("fence.acq_rel.gpu;" ::: "memory"); }
__device__ __forceinline__ unsigned ld_acquire(const unsigned* p) { unsigned v; asm volatile("ld.acquire.gpu.global.u32 %0, [%1];" : "=r"(v) : "l"(p) : "memory"); return v; }
__device__ __forceinline__ void red_release(unsigned* p, unsigned v) { asm volatile("red.release.gpu.global.add.u32 [%0], %1;" :: "l"(p), "r"(v) : "memory"); }
__device__ __forceinline__ void st_release(unsigned* p, unsigned v) { asm volatile("st.release.gpu.global.u32 [%0], %1;" :: "l"(p), "r"(v) : "memory"); }
__device__ __forceinline__ unsigned ld_relaxed(const unsigned* p) { unsigned v; asm volatile("ld.relaxed.gpu.global.u32 %0, [%1];" : "=r"(v) : "l"(p) : "memory"); return v; }
__device__ __forceinline__ void red_relaxed(unsigned* p, unsigned v) { asm volatile("red.relaxed.gpu.global.add.u32 [%0], %1;" :: "l"(p), "r"(v) : "memory"); }
__device__ __forceinline__ void st_relaxed(unsigned* p, unsigned v) { asm volatile("st.relaxed.gpu.global.u32 [%0], %1;" :: "l"(p), "r"(v) : "memory"); }
__device__ __forceinline__ void st_relaxed2(uint2* p, unsigned a, unsigned b) { asm volatile("st.relaxed.gpu.global.v2.u32 [%0], {%1, %2};" :: "l"(p), "r"(a), "r"(b) : "memory"); }
template <int SLEEP>
__device__ __forceinline__ unsigned wait_tagged(const uint2* p, unsigned tag) {
  uint2 v;
  int it = 0;
  do {
    if (SLEEP && it > 0) __nanosleep(SLEEP);
    asm volatile("ld.relaxed.gpu.global.v2.u32 {%0, %1}, [%2];" : "=r"(v.x), "=r"(v.y) : "l"(p) : "memory");
    if (++it > (1 << 20)) __trap();
  } while (!__all_sync(0xffffffffu, v.y == tag));
  return v.x;
}
__device__ __forceinline__ void wait_counter(const unsigned* p, unsigned target) {
#pragma unroll 1
  for (int it = 0; it < (1 << 20); it++) { if ((int)(ld_relaxed(p) - target) >= 0) return; }
  __trap();
}
__device__ __forceinline__ float4 ldg_l2(const float* p) {
  float4 v; asm volatile("ld.relaxed.gpu.global.v4.f32 {%0, %1, %2, %3}, [%4];" : "=f"(v.x), "=f"(v.y), "=f"(v.z), "=f"(v.w) : "l"(p) : "memory"); return v;
}
__device__ __forceinline__ float ldg_l2_f(const float* p) { float v; asm volatile("ld.relaxed.gpu.global.f32 %0, [%1];" : "=f"(v) : "l"(p) : "memory"); return v; }
__device__ __forceinline__ void sts64(uint32_t addr, float a, float b) { asm volatile("st.shared.v2.f32 [%0], {%1, %2};" :: "r"(addr), "f"(a), "f"(b) : "memory"); }
__device__ __forceinline__ void bulk_load(uint32_t dst, const void* src, uint32_t bytes, uint32_t bar) {
  asm volatile("cp.async.bulk.shared::cluster.global.mbarrier::complete_tx::bytes [%0], [%1], %2, [%3];" :: "r"(dst), "l"(src), "r"(bytes), "r"(bar) : "memory");
}
__device__ __forceinline__ void bulk_prefetch(const void* src, uint32_t bytes) {
  asm volatile("cp.async.bulk.prefetch.L2.global [%0], %1;" :: "l"(src), "r"(bytes) : "memory");
}
__device__ __forceinline__ void tma_store_2d(const CUtensorMap* tm, uint32_t src, int c0, int c1) {
  asm volatile("cp.async.bulk.tensor.2d.global.shared::cta.bulk_group [%0, {%2, %3}], [%1];" :: "l"(tm), "r"(src), "r"(c0), "r"(c1) : "memory");
}
__device__ __forceinline__ void bulk_store(void* dst, uint32_t src, uint32_t bytes) {
  asm volatile("cp.async.bulk.global.shared::cta.bulk_group [%0], [%1], %2;" :: "l"(dst), "r"(src), "r"(bytes) : "memory");
}
__device__ __forceinline__ void bulk_reduce_f32(void* dst, uint32_t src, uint32_t bytes) {
  asm volatile("cp.reduce.async.bulk.global.shared::cta.bulk_group.add.f32 [%0], [%1], %2;" :: "l"(dst), "r"(src), "r"(bytes) : "memory");
}
__device__ __forceinline__ void tma_load_3d(uint32_t dst, const CUtensorMap* tm, int c0, int c1, int c2, uint32_t bar) {
  asm volatile("cp.async.bulk.tensor.3d.shared::cluster.global.mbarrier::complete_tx::bytes [%0], [%1, {%3, %4, %5}], [%2];"
    :: "r"(dst), "l"(tm), "r"(bar), "r"(c0), "r"(c1), "r"(c2) : "memory");
}
__device__ __forceinline__ void cp_async16(uint32_t dst, const void* src) { asm volatile("cp.async.cg.shared.global [%0], [%1], 16;" :: "r"(dst), "l"(src) : "memory"); }
__device__ __forceinline__ void cp_async_commit() { asm volatile("cp.async.commit_group;" ::: "memory"); }
template <int N> __device__ __forceinline__ void cp_async_wait() { asm volatile("cp.async.wait_group %0;" :: "n"(N) : "memory"); }
__device__ __forceinline__ void prefetch_map(const CUtensorMap* tm) { asm volatile("prefetch.tensormap [%0];" :: "l"(tm) : "memory"); }
__device__ __forceinline__ void bulk_commit() { asm volatile("cp.async.bulk.commit_group;" ::: "memory"); }
__device__ __forceinline__ void bulk_wait0() { asm volatile("cp.async.bulk.wait_group 0;" ::: "memory"); }
__device__ __forceinline__ void bulk_wait0_read() { asm volatile("cp.async.bulk.wait_group.read 0;" ::: "memory"); }
__device__ __forceinline__ void mma16816(float& d0, float& d1, float& d2, float& d3, uint32_t a0, uint32_t a1, uint32_t a2, uint32_t a3, uint32_t b0, uint32_t b1) {
  asm volatile("mma.sync.aligned.m16n8k16.row.col.f32.bf16.bf16.f32 {%0, %1, %2, %3}, {%4, %5, %6, %7}, {%8, %9}, {%0, %1, %2, %3};"
    : "+f"(d0), "+f"(d1), "+f"(d2), "+f"(d3) : "r"(a0), "r"(a1), "r"(a2), "r"(a3), "r"(b0), "r"(b1));
}
__device__ __forceinline__ uint32_t hmul2(uint32_t a, uint32_t b) { uint32_t r; asm("mul.rn.bf16x2 %0, %1, %2;" : "=r"(r) : "r"(a), "r"(b)); return r; }
__device__ __forceinline__ uint32_t hfma2(uint32_t a, uint32_t b, uint32_t c) { uint32_t r; asm("fma.rn.bf16x2 %0, %1, %2, %3;" : "=r"(r) : "r"(a), "r"(b), "r"(c)); return r; }
__device__ __forceinline__ uint32_t hadd2(uint32_t a, uint32_t b) { uint32_t r; asm("add.rn.bf16x2 %0, %1, %2;" : "=r"(r) : "r"(a), "r"(b)); return r; }
__device__ __forceinline__ float sigmoidf_(float v) { return rcp(1.0f + ex2(v * -1.4426950408889634f)); }

__device__ __forceinline__ void hedgehog(const float (&p)[16], uint32_t (&phi)[16]) {
  float mx0 = p[0], mn0 = p[0], mx1 = p[2], mn1 = p[2];
#pragma unroll
  for (int j = 0; j < 4; j++) {
    mx0 = fmaxf(mx0, fmaxf(p[4 * j], p[4 * j + 1])); mn0 = fminf(mn0, fminf(p[4 * j], p[4 * j + 1]));
    mx1 = fmaxf(mx1, fmaxf(p[4 * j + 2], p[4 * j + 3])); mn1 = fminf(mn1, fminf(p[4 * j + 2], p[4 * j + 3]));
  }
#pragma unroll
  for (int o = 1; o <= 2; o <<= 1) {
    mx0 = fmaxf(mx0, __shfl_xor_sync(0xffffffffu, mx0, o)); mn0 = fminf(mn0, __shfl_xor_sync(0xffffffffu, mn0, o));
    mx1 = fmaxf(mx1, __shfl_xor_sync(0xffffffffu, mx1, o)); mn1 = fminf(mn1, __shfl_xor_sync(0xffffffffu, mn1, o));
  }
  float ep[16], en[16];
  float sp0 = 0.f, sn0 = 0.f, sp1 = 0.f, sn1 = 0.f;
#pragma unroll
  for (int j = 0; j < 4; j++) {
#pragma unroll
    for (int c = 0; c < 2; c++) {
      ep[4 * j + c] = ex2(p[4 * j + c] - mx0); en[4 * j + c] = ex2(mn0 - p[4 * j + c]);
      ep[4 * j + 2 + c] = ex2(p[4 * j + 2 + c] - mx1); en[4 * j + 2 + c] = ex2(mn1 - p[4 * j + 2 + c]);
      sp0 += ep[4 * j + c]; sn0 += en[4 * j + c]; sp1 += ep[4 * j + 2 + c]; sn1 += en[4 * j + 2 + c];
    }
  }
#pragma unroll
  for (int o = 1; o <= 2; o <<= 1) {
    sp0 += __shfl_xor_sync(0xffffffffu, sp0, o); sn0 += __shfl_xor_sync(0xffffffffu, sn0, o);
    sp1 += __shfl_xor_sync(0xffffffffu, sp1, o); sn1 += __shfl_xor_sync(0xffffffffu, sn1, o);
  }
  sp0 = rcp(sp0); sn0 = rcp(sn0); sp1 = rcp(sp1); sn1 = rcp(sn1);
#pragma unroll
  for (int j = 0; j < 4; j++) {
    phi[2 * j] = pack_bf16(ep[4 * j] * sp0, ep[4 * j + 1] * sp0);
    phi[2 * j + 1] = pack_bf16(ep[4 * j + 2] * sp1, ep[4 * j + 3] * sp1);
    phi[8 + 2 * j] = pack_bf16(en[4 * j + 1] * sn0, en[4 * j] * sn0);
    phi[8 + 2 * j + 1] = pack_bf16(en[4 * j + 3] * sn1, en[4 * j + 2] * sn1);
  }
}

__device__ __noinline__ void hedgehog_slow(float* buf, int n) {
#pragma unroll 1
  for (int u = 0; u < n; u++) {
    float p[16]; uint32_t phi[16];
#pragma unroll
    for (int i = 0; i < 16; i++) p[i] = buf[u * 16 + i];
    hedgehog(p, phi);
#pragma unroll
    for (int i = 0; i < 16; i++) buf[u * 16 + i] = __uint_as_float(phi[i]);
  }
}

__device__ __forceinline__ void store_phi_k(const uint32_t (&phi)[16], uint32_t a) {
#pragma unroll
  for (int jj = 0; jj < 4; jj++) stsm4(a ^ (jj << 5), phi[4 * jj], phi[4 * jj + 1], phi[4 * jj + 2], phi[4 * jj + 3]);
}
__device__ __forceinline__ void hand_over_smem(uint32_t bar, bool ok) {
  fence_async_smem();
  __syncwarp();
  if (elect_one() & ok) mbar_arrive(bar);
}
__device__ __noinline__ void redo_phi_k(float* buf, unsigned done, uint32_t pa, uint32_t bar) {
  hedgehog_slow(buf, 4);
#pragma unroll 1
  for (int u = 0; u < 4; u++) {
    if ((done >> u) & 1) continue;
    uint32_t phi[16];
#pragma unroll
    for (int i = 0; i < 16; i++) phi[i] = __float_as_uint(buf[u * 16 + i]);
    store_phi_k(phi, pa + (~u & 1) * 32768 + (u >> 1) * 4096);
    if (u >= 2) hand_over_smem(bar + (u - 2) * 8, true);
  }
}

__device__ __forceinline__ uint32_t dup_lo(uint32_t v) { uint32_t r; asm("{\n.reg .b16 l, h;\nmov.b32 {l, h}, %1;\nmov.b32 %0, {l, l};\n}" : "=r"(r) : "r"(v)); return r; }
__device__ __forceinline__ uint32_t dup_hi(uint32_t v) { uint32_t r; asm("{\n.reg .b16 l, h;\nmov.b32 {l, h}, %1;\nmov.b32 %0, {h, h};\n}" : "=r"(r) : "r"(v)); return r; }
struct HState { uint32_t a[16]; float s[5]; };
__device__ __forceinline__ void hedgehog_fast1(const float (&p)[16], HState& a) {
  float sm[8], m[8], r[8];
#pragma unroll
  for (int i = 0; i < 8; i++) {
    const float t0 = ex2(p[2 * i]), t1 = ex2(p[2 * i + 1]);
    a.a[i] = pack_bf16(t0, t1); sm[i] = t0 + t1; m[i] = t0 * t1;
  }
  float mq[4];
#pragma unroll
  for (int i = 0; i < 4; i++) {
    mq[i] = m[2 * i] * m[2 * i + 1];
    const float R = rcp(mq[i]);
    r[2 * i] = R * m[2 * i + 1]; r[2 * i + 1] = R * m[2 * i];
  }
  a.s[4] = (mq[0] + mq[1]) + (mq[2] + mq[3]);
#pragma unroll
  for (int i = 0; i < 4; i++) {
    const uint32_t rr = pack_bf16(r[2 * i], r[2 * i + 1]);
    a.a[8 + 2 * i] = hmul2(a.a[2 * i], dup_lo(rr)); a.a[9 + 2 * i] = hmul2(a.a[2 * i + 1], dup_hi(rr));
  }
#pragma unroll
  for (int c = 0; c < 2; c++) {
    a.s[2 * c] = (sm[c] + sm[2 + c]) + (sm[4 + c] + sm[6 + c]);
    a.s[2 * c + 1] = fmaf(r[6 + c], sm[6 + c], fmaf(r[4 + c], sm[4 + c], fmaf(r[2 + c], sm[2 + c], r[c] * sm[c])));
  }
}
template <bool NORM>
__device__ __forceinline__ bool hedgehog_fast2(const HState& a, uint32_t (&phi)[16], float& s0, float& s1) {
  float s[4] = {a.s[0], a.s[1], a.s[2], a.s[3]};
#pragma unroll
  for (int o = 1; o <= 2; o <<= 1)
#pragma unroll
    for (int i = 0; i < 4; i++) s[i] += __shfl_xor_sync(0xffffffffu, s[i], o);
  const bool ok = ((s[0] + s[1]) + (s[2] + s[3]) <= 7.2e16f) & (a.s[4] <= 1.3e36f);
  if (NORM) {
    const float R0 = rcp(s[0] * s[1]), R1 = rcp(s[2] * s[3]);
    const uint32_t n0 = pack_bf16(R0 * s[1], R0 * s[0]), n1 = pack_bf16(R1 * s[3], R1 * s[2]);
#pragma unroll
    for (int i = 0; i < 8; i++) { phi[i] = hmul2(a.a[i], dup_lo((i & 1) ? n1 : n0)); phi[8 + i] = hmul2(a.a[8 + i], dup_hi((i & 1) ? n1 : n0)); }
  } else {
    const uint32_t n = pack_bf16(s[0] * rcp(s[1]), s[2] * rcp(s[3]));
    s0 = s[0]; s1 = s[2];
#pragma unroll
    for (int i = 0; i < 8; i++) { phi[i] = a.a[i]; phi[8 + i] = hmul2(a.a[8 + i], (i & 1) ? dup_hi(n) : dup_lo(n)); }
  }
  return ok;
}
template <bool NORM>
__device__ __forceinline__ bool hedgehog_fast(const float (&p)[16], uint32_t (&phi)[16], float& s0, float& s1) {
  HState a;
  hedgehog_fast1(p, a);
  return hedgehog_fast2<NORM>(a, phi, s0, s1);
}

template <int OFF>
__device__ __forceinline__ void pack_frags(const float (&acc)[96], uint32_t (&a)[16]) {
#pragma unroll
  for (int i = 0; i < 16; i++) a[i] = pack_bf16(acc[OFF + 2 * i], acc[OFF + 2 * i + 1]);
#pragma unroll
  for (int i = 0; i < 16; i++) asm volatile("" : "+r"(a[i]) :: "memory");
}
__device__ __forceinline__ void issue_feat(const uint32_t (&a)[16], float (&p0)[16], float (&p1)[16], uint32_t wphi) {
  wgmma_fence();
#pragma unroll
  for (int kk = 0; kk < 2; kk++) {
    wgmma_rs_n32<1, H64>(p0, a[4 * kk], a[4 * kk + 1], a[4 * kk + 2], a[4 * kk + 3], dlo(wphi + kk * 1024, 16), kk);
    wgmma_rs_n32<1, H64>(p1, a[8 + 4 * kk], a[8 + 4 * kk + 1], a[8 + 4 * kk + 2], a[8 + 4 * kk + 3], dlo(wphi + 2048 + kk * 1024, 16), kk);
  }
  wgmma_commit();
}
__device__ __forceinline__ void keep_alive(const uint32_t (&a)[16]) {
#pragma unroll
  for (int i = 0; i < 16; i++) asm volatile("" :: "r"(a[i]) : "memory");
}

__device__ __forceinline__ void fma8(float (&a)[8], float xv, const uint4& w) {
  a[0] = fmaf(xv, bf_lo(w.x), a[0]); a[1] = fmaf(xv, bf_hi(w.x), a[1]);
  a[2] = fmaf(xv, bf_lo(w.y), a[2]); a[3] = fmaf(xv, bf_hi(w.y), a[3]);
  a[4] = fmaf(xv, bf_lo(w.z), a[4]); a[5] = fmaf(xv, bf_hi(w.z), a[5]);
  a[6] = fmaf(xv, bf_lo(w.w), a[6]); a[7] = fmaf(xv, bf_hi(w.w), a[7]);
}

template <int J0, int J1>
__device__ __forceinline__ void stage_out(const float (&acc)[64], uint32_t xa) {
#pragma unroll
  for (int jj = J0; jj < J1; jj++)
    stsm4((xa ^ ((jj & 3) << 5)) + (jj >> 2) * 16384, pack_bf16(acc[8 * jj], acc[8 * jj + 1]), pack_bf16(acc[8 * jj + 2], acc[8 * jj + 3]),
          pack_bf16(acc[8 * jj + 4], acc[8 * jj + 5]), pack_bf16(acc[8 * jj + 6], acc[8 * jj + 7]));
}
__device__ __forceinline__ float lds_bf16(uint32_t addr) {
  unsigned short v; asm volatile("ld.shared.u16 %0, [%1];" : "=h"(v) : "r"(addr) : "memory"); return __uint_as_float((uint32_t)v << 16);
}
__device__ __noinline__ void redo_rows(const __nv_bfloat16* pieces, const __nv_bfloat16* wo_cols, const unsigned* done, const __nv_bfloat16* xrows,
                                       uint32_t xa, int wi, uint32_t gate, int routed, uint32_t upd) {
  const int lane = threadIdx.x & 31;
  int it = 0;
  while (!__all_sync(0xffffffffu, ld_acquire(done + (lane & 15)) != 0)) { if (++it > (1 << 20)) __trap(); }
  float acc[64];
  const int g = lane >> 2, q = lane & 3, r0 = wi * 16 + g;
#pragma unroll
  for (int i = 0; i < 32; i++) {
    const int r = g + (i & 1) * 8, c = (i >> 1) * 8 + q * 2;
    uint32_t v = *reinterpret_cast<const uint32_t*>(xrows + (size_t)r * D_ + c);
    if (r == routed) v = hadd2(v, lds_u32(upd + c * 2));
    const float og = round_bf16(1.0f - lds_bf16(gate + r * 2));
    acc[2 * i] = og * bf_lo(v); acc[2 * i + 1] = og * bf_hi(v);
  }
#pragma unroll 1
  for (int ks = 0; ks < 64; ks++) {
    const unsigned* pc = reinterpret_cast<const unsigned*>(pieces + (ks >> 2) * 4096) + r0 * 32 + q;
    const int c0 = ((2 * (ks & 3)) ^ (r0 & 7)) * 4, c1 = ((2 * (ks & 3) + 1) ^ (r0 & 7)) * 4;
    const uint32_t a0 = ld_relaxed(pc + c0), a1 = ld_relaxed(pc + 256 + c0), a2 = ld_relaxed(pc + c1), a3 = ld_relaxed(pc + 256 + c1);
    const unsigned short* wp = reinterpret_cast<const unsigned short*>(wo_cols) + (size_t)(ks * 16 + 2 * q) * D_ + g;
#pragma unroll
    for (int nb = 0; nb < 16; nb++) {
      const uint32_t b0 = wp[nb * 8] | ((uint32_t)wp[nb * 8 + D_] << 16), b1 = wp[nb * 8 + 8 * D_] | ((uint32_t)wp[nb * 8 + 9 * D_] << 16);
      mma16816(acc[4 * nb], acc[4 * nb + 1], acc[4 * nb + 2], acc[4 * nb + 3], a0, a1, a2, a3, b0, b1);
    }
  }
  __syncwarp();
  stage_out<0, 8>(acc, xa);
}

__global__ void __cluster_dims__(2, 1, 1) __launch_bounds__(512, 1)
fused_kernel(const __grid_constant__ Maps maps, const __nv_bfloat16* __restrict__ x,
             const __nv_bfloat16* __restrict__ wo, const __nv_bfloat16* __restrict__ w_r, const __nv_bfloat16* __restrict__ gate_w) {
  extern __shared__ __align__(1024) uint8_t smem_raw[];
  if (threadIdx.x == 0) { prefetch_map(&maps.w); prefetch_map(&maps.x); }
  const int tid = threadIdx.x, warp = __shfl_sync(0xffffffffu, tid >> 5, 0), lane = tid & 31;
  const int rank = blockIdx.x & 1;
  const unsigned cl = blockIdx.x >> 1, hi = (cl - 36) * 37 >> 8, lo7 = cl - 36 - hi * 7;
  const unsigned col = cl < 4 ? 7 : cl < 36 ? (cl & 3) + (~cl & 4) * 2 : lo7 + (lo7 < 3 ? 4 : 9), pos = cl < 4 ? cl : cl < 36 ? (cl - 4) >> 3 : hi;
  const int b = cl < 64 ? (col & 7) * 16 + (col & 8) + pos * 2 + rank : blockIdx.x;
  const int e = blockIdx.x;
  const int tg = b >> 4, hp = b & 15;
  const int half = hp >> 3, ct = hp & 7;
  constexpr uint32_t SB0 = 1024;
  const uint32_t sb = SB0 + ((uint32_t)rank << 24);
  auto BAR = [&](int i) { return sb + SM_BAR + 8 * i; };
  auto load_stage = [&](int kt, int s, bool mc) {
    const uint32_t a = sb + SM_RA + s * A_BYTES, full = BAR(B_FULL + s);
    mbar_expect_tx(full, STAGE_BYTES);
    tma_load_3d(sb + SM_RB + s * B_BYTES, &maps.w, hp * 64, kt * 32, 0, full);
    if (mc) tma_load_2d_mc(a + rank * 8192, &maps.x, kt * 32, tg * 256 + rank * 128, full);
    else { tma_load_2d(a, &maps.x, kt * 32, tg * 256, full); tma_load_2d(a + 8192, &maps.x, kt * 32, tg * 256 + 128, full); }
  };
  auto slice_of = [&](int i) { return (i < 2 ? ct ^ i : i < 8 ? i - 2 * (i - 2 < (ct & 6)) : i) ^ (half * 8); };
  auto load_b2 = [&](int i) {
    const int j = slice_of(i), sl = i + 4 - (i >= 3) * NB2 - (i >= 10) * NB2;
    mbar_expect_tx(BAR(B_FB2 + i), 16384);
    tma_load_3d(sb + SM_RB + sl * 16384, &maps.wo, 0, j * 64, ct * 2, BAR(B_FB2 + i));
  };
  auto load_xt = [&](int w) {
    mbar_expect_tx(BAR(B_XT + w), 16384);
    tma_load_2d(sb + SM_XT + w * 8192, &maps.xt, ct * 128, tg * 256 + half * 128 + w * 64, BAR(B_XT + w));
    tma_load_2d(sb + SM_XT + w * 8192 + 16384, &maps.xt, ct * 128 + 64, tg * 256 + half * 128 + w * 64, BAR(B_XT + w));
  };
  auto o_piece = [&](int hf, int mb, int j) { return g_o + (size_t)((((tg * 2 + hf) * 2 + mb) * 16 + j) * 4096); };

  if (b >= NCTA) {
    if (warp == 0 && b == NCTA) {
      const unsigned tag = (ld_relaxed(&g_bcast[0].y) + 1) & 0xfffu;
      unsigned val = 0;
#pragma unroll 1
      for (int round = 0; round < 2; round++) {
        const unsigned* arr = (round ? g_ready : g_key) + lane * 4;
        unsigned k[16], bad;
        int it = 0;
        do {
          bad = 0;
#pragma unroll
          for (int a = 0; a < 4; a++)
            asm volatile("ld.relaxed.gpu.global.v4.u32 {%0, %1, %2, %3}, [%4];" : "=r"(k[4 * a]), "=r"(k[4 * a + 1]), "=r"(k[4 * a + 2]), "=r"(k[4 * a + 3])
                         : "l"(arr + (round ? 0 : a * NCTA)) : "memory");
#pragma unroll
          for (int i = 0; i < 16; i++) bad |= k[i] ^ tag;
          if (++it > (1 << 20)) __trap();
        } while (!__all_sync(0xffffffffu, (bad & 0xfffu) == 0));
        if (round == 0) {
#pragma unroll
          for (int c = 0; c < 4; c++) {
            const unsigned m = max(max(k[c], k[4 + c]), max(k[8 + c], k[12 + c]));
            val = max(val, (m & 0xffff0000u) | ((127u - (lane * 4 + c)) << 4) | ((m >> 12) & 15u));
          }
          val = __reduce_max_sync(0xffffffffu, val);
        }
        if (lane < 8) st_relaxed2(g_bcast + round * 128 + lane * 16, val, tag);
        const uint32_t* xr = reinterpret_cast<const uint32_t*>(x + (size_t)(2047u - (val & 0x7ffu)) * D_);
        float l = 0.f;
#pragma unroll 4
        for (int i = lane; i < 512; i += 32) {
          const uint32_t pr = hmul2(__ldg(xr + i), __ldg(reinterpret_cast<const uint32_t*>(gate_w) + i));
          l += bf_lo(pr) + bf_hi(pr);
        }
#pragma unroll
        for (int o = 1; o <= 16; o <<= 1) l += __shfl_xor_sync(0xffffffffu, l, o);
        val = __float_as_uint(round_bf16(sigmoidf_(round_bf16(l)))) >> 16;
      }
    }
    return;
  }
  if (warp == 8) {
    if (elect_one()) {
      mbar_init(BAR(0), 1);
      if (NPRE > 1) { mbar_init(BAR(1), 1); mbar_init(BAR(2), 1); }
      if (NPRE > 0) fence_async_smem();
      TSTAMP(40);
      if (NPRE > 0) load_stage(0, 0, false);
      if (NPRE > 1) load_stage(1, 1, false);
      if (NPRE > 2) load_stage(2, 2, false);
      TSTAMP(41);
    }
  } else if (elect_one()) {
    const int i = 3 + warp - (warp > 8);
    mbar_init(BAR(i), i < B_EMPTY ? 1 : 4);
    if (NPRE < 2 && warp >= 14) mbar_init(BAR(warp - 13), 1);
    if (warp == 13) mbar_init(BAR(B_INIT), 3);
  }
  asm volatile("fence.mbarrier_init.release.cluster;" ::: "memory");
  __syncwarp();
  asm volatile("barrier.cluster.arrive.relaxed.aligned;" ::: "memory");
  auto cluster_wait = [&]() { asm volatile("barrier.cluster.wait.aligned;" ::: "memory"); };

  if (warp >= 12) {
    asm volatile("setmaxnreg.dec.sync.aligned.u32 40;");
    const int aw = warp - 12;
    cluster_wait();
    const unsigned old_key = ld_relaxed(g_key + aw * NCTA + b);
    const uint32_t zero = smem_u32(smem_raw) ^ sb;
    {
      float r[4], l[4];
#pragma unroll
      for (int t = 0; t < 4; t++) { r[t] = 0.f; l[t] = 0.f; }
      uint32_t xa = sb + SM_XR + aw * 1024 + lane * 8, wa = sb + SM_XR + 32768 + lane * 8;
#pragma unroll 1
      for (int i = 0; i < 8; i++) {
        if (!(i & 1)) mbar_wait(BAR(B_XR) + i * 4, 0);
        if (tid == 384 && i == 6) TSTAMP(30);
        uint2 wr = lds64(wa);
        const uint2 gw = lds64(wa + 2048);
        uint2 xv[4];
#pragma unroll
        for (int t = 0; t < 4; t++) xv[t] = lds64(xa + t * 256);
        xa += 4096; wa += 256;
        wr.x |= (xv[1].x | xv[2].x | xv[3].x) & zero;
#pragma unroll
        for (int t = 0; t < 4; t++) { r[t] = fmaf(bf_lo(xv[t].x), bf_lo(wr.x), r[t]); l[t] = fmaf(bf_lo(xv[t].x), bf_lo(gw.x), l[t]); }
#pragma unroll
        for (int t = 0; t < 4; t++) { r[t] = fmaf(bf_hi(xv[t].x), bf_hi(wr.x), r[t]); l[t] = fmaf(bf_hi(xv[t].x), bf_hi(gw.x), l[t]); }
#pragma unroll
        for (int t = 0; t < 4; t++) { r[t] = fmaf(bf_lo(xv[t].y), bf_lo(wr.y), r[t]); l[t] = fmaf(bf_lo(xv[t].y), bf_lo(gw.y), l[t]); }
#pragma unroll
        for (int t = 0; t < 4; t++) { r[t] = fmaf(bf_hi(xv[t].y), bf_hi(wr.y), r[t]); l[t] = fmaf(bf_hi(xv[t].y), bf_hi(gw.y), l[t]); }
      }
      float u[4];
#pragma unroll
      for (int t = 0; t < 4; t++) u[t] = ((lane & 4) ? l[t] : r[t]) + __shfl_xor_sync(0xffffffffu, (lane & 4) ? r[t] : l[t], 4);
      const float v0 = ((lane & 1) ? u[1] : u[0]) + __shfl_xor_sync(0xffffffffu, (lane & 1) ? u[0] : u[1], 1);
      const float v1 = ((lane & 1) ? u[3] : u[2]) + __shfl_xor_sync(0xffffffffu, (lane & 1) ? u[2] : u[3], 1);
      float v = ((lane & 2) ? v1 : v0) + __shfl_xor_sync(0xffffffffu, (lane & 2) ? v0 : v1, 2);
      v += __shfl_xor_sync(0xffffffffu, v, 8);
      v += __shfl_xor_sync(0xffffffffu, v, 16);
      v = round_bf16(v);
      unsigned k = __float_as_uint(v) >> 16;
      k = (k & 0x8000u) ? (~k & 0xffffu) : (k | 0x8000u);
      k = __reduce_max_sync(0xffffffffu, lane < 4 ? (k << 4) | (15u - (aw * 4 + lane)) : 0u);
      mbar_wait(BAR(B_INIT), 0);
      const unsigned tag = (old_key + 1) & 0xfffu;
      if (lane == 0) st_relaxed(g_key + aw * NCTA + b, (k << 12) | tag);
      if ((lane >> 2) == 1) st_relaxed(g_gate + b * 16 + aw * 4 + (lane & 3), __float_as_uint(round_bf16(sigmoidf_(v))) | tag);
    }
    if (tid == 384) { TSTAMP(31); GSTAMP(60); }
    fence_async_smem();
    __syncwarp();
    if (elect_one()) mbar_arrive(BAR(B_XRD));
    mbar_wait_bounded(BAR(B_XSEL), 0);
    if (tid == 384) TSTAMP(36);
    float ag[8];
#pragma unroll
    for (int i = 0; i < 8; i++) ag[i] = 0.f;
    if (e < NMOE) {
      const uint32_t lw = sb + SM_MOE + aw * 2048 + (lane >> 3) * 512 + (lane & 7) * 16;
      uint32_t lx = sb + SM_XSEL + aw * 32 + (lane >> 3) * 8, fb = BAR(B_MOE), wa = lw;
      bool got = false;
#pragma unroll 1
      for (int m = 0; m < 12; m++) {
#pragma unroll
        for (int c = 0; c < 2; c++) {
          if (!got) mbar_wait(fb + c * 8, (m >> 1) & 1);
          uint4 w0, w1, w2, w3;
          lds128x4(wa + c * 8192, w0, w1, w2, w3);
          uint2 xv = lds64(lx + c * 128);
          got = mbar_test(c ? fb ^ 16 : fb + 8, ((m + c) >> 1) & 1);
          const uint32_t dep = ((w0.x | w1.x | w2.x) | w3.x) & zero;
          xv.x |= dep;
          if (elect_one()) mbar_arrive(fb + dep + (B_MOEE - B_MOE + c) * 8);
          fma8(ag, bf_lo(xv.x), w0); fma8(ag, bf_hi(xv.x), w1); fma8(ag, bf_lo(xv.y), w2); fma8(ag, bf_hi(xv.y), w3);
        }
        fb ^= 16; wa = 2 * lw + 16384 - wa; lx += 256;
        if (m == 7) {
          int ln;
          asm volatile("mov.u32 %0, %%laneid;" : "=r"(ln));
#pragma unroll
          for (int i = 0; i < 4; i++) ag[i] = ((ln & 16) ? ag[4 + i] : ag[i]) + __shfl_xor_sync(0xffffffffu, (ln & 16) ? ag[i] : ag[4 + i], 16);
          const float v0 = ((ln & 8) ? ag[2] : ag[0]) + __shfl_xor_sync(0xffffffffu, (ln & 8) ? ag[0] : ag[2], 8);
          const float v1 = ((ln & 8) ? ag[3] : ag[1]) + __shfl_xor_sync(0xffffffffu, (ln & 8) ? ag[1] : ag[3], 8);
          const uint32_t own = (uint32_t)(ln & 4) << 22;
          asm volatile("st.async.shared::cluster.mbarrier::complete_tx::bytes.v2.f32 [%0], {%1, %2}, [%3];"
                       :: "r"(own + SB0 + SM_RED + rank * 512 + aw * 128 + (ln & 3) * 32 + (ln >> 3) * 8), "f"(v0), "f"(v1), "r"(own + SB0 + SM_BAR + 8 * B_H) : "memory");
          if (tid == 384) TSTAMP(39);
          mbar_wait_bounded(BAR(B_H), 0);
          const uint32_t ra = sb + SM_RED + ln * 4;
          float gv = round_bf16((lds_f32(ra) + lds_f32(ra + 128)) + (lds_f32(ra + 256) + lds_f32(ra + 384)));
          const float uv = round_bf16((lds_f32(ra + 512) + lds_f32(ra + 640)) + (lds_f32(ra + 768) + lds_f32(ra + 896)));
          gv = round_bf16(gv * sigmoidf_(gv));
          lx = sb + SM_XSEL + aw * 32;
          asm volatile("st.shared.b16 [%0], %1;" :: "r"(lx + (ln >> 2) * 128 + (ln & 3) * 2), "h"(__bfloat16_as_ushort(__float2bfloat16_rn(gv * uv))) : "memory");
          __syncwarp();
#pragma unroll
          for (int i = 0; i < 8; i++) ag[i] = 0.f;
          if (tid == 384) TSTAMP(33);
        }
      }
      mbar_wait(BAR(B_RDY), 0);
#pragma unroll
      for (int j = 0; j < 3; j++)
        asm volatile("red.global.add.v4.f32 [%0], {%1, %2, %3, %4};" :: "l"(g_z.y + (e & (NY - 1)) * 2 * D_ + (j * 128 + aw * 32 + lane) * 4),
                     "f"(ag[3 * j]), "f"(ag[3 * j + 1]), "f"(j < 2 ? ag[3 * j + 2] : 0.f), "f"(1.0f) : "memory");
    }
    fence_async_smem();
    if (tid == 384) TSTAMP(34);
    bar_sync(4, 128);
    if (aw < 3) {
      if (aw == 0) mbar_wait(BAR(B_PHI), 0);
      if (elect_one()) load_b2(aw);
      if (aw) {
#pragma unroll 1
        for (int i = 0; i < 16; i++) {
          mbar_wait_bounded(BAR(B_FB2 + i), 0);
          if (i == 0) mbar_wait(BAR(B_OP + half * 2 + aw - 1), 0);
          if (elect_one()) mbar_expect_tx(BAR(B_F2 + (aw - 1) * 16 + i), i ? 8192 : 0);
        }
      }
    } else {
      const uint4 info = lds128(sb + SM_INFO);
      int it = 0;
      if ((info.y >> 7) == tg * 2 + half) {
        mbar_wait(BAR(B_RDY), 0);
        const float rs = round_bf16(sigmoidf_(__uint_as_float(info.z)));
        float y[9];
        do {
          __nanosleep(100);
#pragma unroll
          for (int i = 0; i < 9; i++) y[i] = 0.f;
#pragma unroll 1
          for (int c = lane >> 4; c < NY; c += 2) {
            const float* yp = g_z.y + c * 2 * D_ + (ct * 16 + (lane & 15)) * 4;
            const float4 a0 = ldg_l2(yp), a1 = ldg_l2(yp + 512), a2 = ldg_l2(yp + 1024);
            y[0] += a0.x; y[1] += a0.y; y[2] += a0.z; y[3] += a1.x; y[4] += a1.y; y[5] += a1.z; y[6] += a2.x; y[7] += a2.y;
            y[8] += a0.w + a1.w + a2.w;
          }
#pragma unroll
          for (int i = 0; i < 9; i++) y[i] += __shfl_xor_sync(0xffffffffu, y[i], 16);
          if (++it > (1 << 20)) __trap();
        } while (!__all_sync(0xffffffffu, y[8] == 3.f * NMOE));
        const int w = (info.y >> 6) & 1, r = info.y & 63;
        mbar_wait(BAR(B_XT + w), 0);
        if (lane < 16) {
          const uint32_t ad = sb + SM_XT + w * 8192 + (lane >> 3) * 16384 + r * 128 + (((lane & 7) ^ (r & 7)) << 4), rs2 = pack_bf16(rs, rs);
          const uint4 xv = lds128(ad);
          const uint4 u = make_uint4(hmul2(pack_bf16(y[0], y[1]), rs2), hmul2(pack_bf16(y[2], y[3]), rs2), hmul2(pack_bf16(y[4], y[5]), rs2), hmul2(pack_bf16(y[6], y[7]), rs2));
          sts128(sb + SM_UPD + lane * 16, u);
          sts128(ad, make_uint4(hadd2(xv.x, u.x), hadd2(xv.y, u.y), hadd2(xv.z, u.z), hadd2(xv.w, u.w)));
        }
        asm volatile("fence.acq_rel.cta;" ::: "memory");
        __syncwarp();
        if (elect_one()) mbar_arrive(BAR(B_Y));
      }
    }
  } else if (warp >= 8) {
    asm volatile("setmaxnreg.dec.sync.aligned.u32 24;");
    cluster_wait();
    if (tid == 256) TSTAMP(58);
    if (warp != 8) {
      if (elect_one()) {
        if (smem_u32(smem_raw) != sb) __trap();
#pragma unroll 1
        for (int i = B_ST + warp - 9; i < NBAR; i += 3) mbar_init(BAR(i), bar_count(i));
        asm volatile("fence.mbarrier_init.release.cluster;" ::: "memory");
      }
#pragma unroll
      for (int i = 0; i < (ZB + 1535) / 1536; i++) sts128(sb + SM_KVB + (i * 96 + tid - 288) * 16, make_uint4(0, 0, 0, 0));
      if (warp < 11) sts128(sb + SM_ONES + (tid - 288) * 16, make_uint4(0x3f803f80u, 0x3f803f80u, 0x3f803f80u, 0x3f803f80u));
      hand_over_smem(BAR(B_INIT), true);
      if (tid == 288) TSTAMP(57);
    }
    if (warp == 8) {
      int s = NPRE, ph = 1;
#pragma unroll 1
      for (int kt = NPRE; kt < KT; kt++) {
        mbar_wait_bounded(BAR(B_EMPTY + s), ph);
        if (elect_one()) {
          load_stage(kt, s, true);
          const unsigned xc = kt - XR_AFTER;
          if (xc < 4) {
            mbar_expect_tx(BAR(B_XR + xc), xc ? 8192 : 12288);
            tma_load_2d(sb + SM_XR + xc * 8192, &maps.xr, xc * 256, b * 16, BAR(B_XR + xc));
            tma_load_2d(sb + SM_XR + xc * 8192 + 4096, &maps.xr, xc * 256 + 128, b * 16, BAR(B_XR + xc));
            if (xc == 0) { bulk_load(sb + SM_XR + 32768, w_r, 2048, BAR(B_XR)); bulk_load(sb + SM_XR + 34816, gate_w, 2048, BAR(B_XR)); }
          }
          const int pg = kt - STAGES - PF_START + PF_OFF;
          if (pg >= (e < NMOE ? PF_OFF : 24) && pg < 26 && (EXPT != 3 || pg >= 24)) {
            const CUtensorMap* tm = &maps.tg + (pg < 16 ? (b & 1) : pg < 24 ? 2 : 3);
            const int c0 = pg < 16 ? (e >> 1) * 64 : 0, c1 = (pg < 16 ? pg : pg < 24 ? e * 8 + pg - 16 : b * 2 + pg - 24) * 64;
            asm volatile("cp.async.bulk.prefetch.tensor.2d.L2.global [%0, {%1, %2}];" :: "l"(tm), "r"(c0), "r"(c1) : "memory");
          }
        }
        if (++s == STAGES) { s = 0; ph ^= 1; }
      }
      mbar_wait(BAR(B_EMPTY + 1), 1);
#pragma unroll 1
      for (int i = 3; i < (XT_IN_A ? NB2 : 5); i++)
        if (elect_one()) { if (!XT_IN_A) load_xt(i - 3); load_b2(i); }
    } else if (warp == 9) {
      const unsigned tag = (ld_relaxed(g_ready + b) + 1) & 0xfffu;
      if (elect_one()) {
        mbar_expect_tx(BAR(B_WPHI), 4096);
        tma_load_2d(sb + SM_WPHI, &maps.wphi, 0, hp * 64, BAR(B_WPHI));
      }
      mbar_wait(BAR(B_WPHI), 0);
#pragma unroll 1
      for (uint32_t ad = sb + SM_WPHI + lane * 16; ad < sb + SM_WPHI + 4096; ad += 512) {
        constexpr float L = 1.4426950408889634f;
        const uint4 w = lds128(ad);
        sts128(ad, make_uint4(pack_bf16(bf_lo(w.x) * L, bf_hi(w.x) * L), pack_bf16(bf_lo(w.y) * L, bf_hi(w.y) * L),
                              pack_bf16(bf_lo(w.z) * L, bf_hi(w.z) * L), pack_bf16(bf_lo(w.w) * L, bf_hi(w.w) * L)));
      }
      fence_async_smem();
      mbar_wait(BAR(B_XRD), 0);
      const unsigned best = __shfl_sync(0xffffffffu, wait_tagged<KEY_SLEEP>(g_bcast + tg * 16, tag), 0);
      const unsigned idx = 2047u - (best & 0x7ffu);
      unsigned u = best >> 16;
      u = (u & 0x8000u) ? (u & 0x7fffu) : (~u & 0xffffu);
      if (elect_one()) {
        sts128(sb + SM_INFO, make_uint4(tag, idx, u << 16, 0));
        mbar_expect_tx(BAR(B_H), 1024);
        mbar_expect_tx(BAR(B_XSEL), 2048);
        bulk_load(sb + SM_XSEL, x + (size_t)idx * D_, 2048, BAR(B_XSEL));
        TSTAMP(32); GSTAMP(61);
        bulk_store(reinterpret_cast<char*>(&g_z) + b * ZB, sb + SM_KVB, ZB);
      }
      bulk_commit(); bulk_wait0();
      fence_gpu();
      __syncwarp();
      if (lane == 0) { st_relaxed(g_ready + b, tag); TSTAMP(42); }
      int it = 0;
#pragma unroll 1
      for (int c = 0; c < 2; c++) {
        uint4 gv;
        do {
          asm volatile("ld.relaxed.gpu.global.v4.u32 {%0, %1, %2, %3}, [%4];" : "=r"(gv.x), "=r"(gv.y), "=r"(gv.z), "=r"(gv.w)
                       : "l"(g_gate + tg * 256 + c * 128 + lane * 4) : "memory");
          if (++it > (1 << 20)) __trap();
        } while (!__all_sync(0xffffffffu, (((gv.x ^ tag) | (gv.y ^ tag) | (gv.z ^ tag) | (gv.w ^ tag)) & 0xfffu) == 0));
        sts64(sb + SM_GATE + c * 256 + lane * 8, __uint_as_float(__byte_perm(gv.x, gv.y, 0x7632)), __uint_as_float(__byte_perm(gv.z, gv.w, 0x7632)));
      }
      const unsigned gsel = wait_tagged<200>(g_bcast + 128 + tg * 16, tag);
      if ((idx >> 8) == tg && lane == 0) asm volatile("st.shared.b16 [%0], %1;" :: "r"(sb + SM_GATE + (idx & 255) * 2), "h"((unsigned short)gsel) : "memory");
      __syncwarp();
      if (elect_one()) { mbar_arrive(BAR(B_RDY)); TSTAMP(43); }
    } else if (e < NMOE) {
      const int w = warp & 1;
      const CUtensorMap* tm = &maps.wg + rank;
      int c0 = (e >> 1) * 64, c1 = 0, c2 = 4 * w;
      uint32_t bar = BAR(B_MOE + w);
      mbar_wait(BAR(B_XRD), 0);
#pragma unroll 1
      for (int m = 0; m < 12; m++) {
        mbar_wait(bar + (B_MOEE - B_MOE) * 8, ((m >> 1) & 1) ^ 1);
        if (elect_one()) {
          mbar_expect_tx(bar, 8192);
          tma_load_3d(sb + SM_MOE + w * 8192 + (m & 1) * 16384, tm, c0, c1, c2, bar);
        }
        bar ^= 16;
        if (m < 7) c2 += 8; else c1 += 8;
        if (m == 7) { tm = &maps.wd; c0 = 0; c1 = e * 32 + w * 4; c2 = 0; }
      }
    }
    const int wi = warp - 8, st = tid - 256;
    bar_sync(5, 128);
    asm volatile("setmaxnreg.inc.sync.aligned.u32 " STR(REG_K) ";");
    {
      auto kv_half = [&](float (&d)[20], int h, int mb) {
#pragma unroll
        for (int i = 0; i < 8; i++)
          wgmma_ss_n40<1, 1, H128, H64>(d, dlo(SB0 + SM_PHIK + 32768, 16) - h * 2048 + (((i & 2) << 2) + (i & 4) + mb * 2 + (i & 1)) * 128,
                                        dlo(SB0 + SM_V, SM_ONES - SM_V) + (h * 16 + (i & 4) * 2 + mb * 4 + (i & 3)) * (64 - (64 << 16)), (mb | i) != 0);
      };
      auto kv_out = [&](float (&d)[20], int h) {
        fence_regs(d);
        float* dst = g_z.kv + (hp * 2 + h) * KVH + st * 2;
        const int q = lane & 3;
        uint32_t w[8];
#pragma unroll
        for (int i = 0; i < 8; i++) w[i] = pack_bf16(d[2 * i], d[2 * i + 1]);
#pragma unroll
        for (int c = 0; c < 4; c++)
          asm volatile("red.global.add.noftz.v2.bf16x2 [%0], {%1, %2};" :: "l"(dst + c * 256), "r"(w[2 * c]), "r"(q == c ? 0x3f80u : w[2 * c + 1]) : "memory");
        asm volatile("red.global.add.noftz.v2.bf16x2 [%0], {%1, %2};" :: "l"(dst + 1024), "r"((q & 2) ? ((q & 1) ? w[7] : w[5]) : ((q & 1) ? w[3] : w[1])),
                     "r"(q == 0 ? 0x3f80u : q == 1 ? pack_bf16(d[16], d[18]) : 0u) : "memory");
      };
#pragma unroll 1
      for (int h = 0; h < 2; h++) {
        float kv[20];
        mbar_wait_bounded(BAR(B_PHI + h), 0);
        if (st == 0) TSTAMP(23 + h);
        wgmma_fence();
        kv_half(kv, h, 0); kv_half(kv, h, 1);
        wgmma_commit();
        wgmma_wait<0>();
        if (st == 0) TSTAMP(21 + h);
        kv_out(kv, h);
        bar_sync(5, 128);
        if (XT_IN_A && h == XT_H && wi < 2 && elect_one()) load_xt(wi);
      }
      if (wi == 3 && elect_one()) mbar_arrive_cluster(BAR(B_PEER) ^ (1u << 24));
      if (st == 0) TSTAMP(13);
      const int f = wi * 16 + (lane & 15), sw = (f >> 1) & 3, chi = lane >> 4;
      uint2 v[10];
      const float* src = g_z.kv + hp * 2 * KVH + st * 2;
      const int q = lane & 3;
      { const unsigned c0 = clock32(); while (clock32() - c0 < KV_DELAY) {} }
      int it = 0;
      unsigned need = 0x3ff;
#pragma unroll
      for (int i = 0; i < 10; i++) v[i] = make_uint2(0, 0);
      do {
        if (++it > (1 << 20)) __trap();
        unsigned bad = 0;
        if (st == 0 && it == 1) TSTAMP(35);
#pragma unroll
        for (int i = 0; i < 10; i++)
          asm volatile("{\n.reg .pred p;\nsetp.ne.u32 p, %3, 0;\n@p ld.relaxed.gpu.global.v2.u32 {%0, %1}, [%2];\n}"
                       : "+r"(v[i].x), "+r"(v[i].y) : "l"(src + i * 256), "r"(need & (1u << i)) : "memory");
#pragma unroll
        for (int i = 0; i < 10; i++) bad |= (v[i].y != 0x4100u) << i;
        need = __reduce_or_sync(0xffffffffu, bad & ((0x21u << q) | (q ? 0u : 0x210u)));
        if (st == 0 && it == 1) TSTAMP(20);
      } while (need);
      uint32_t zz[2];
#pragma unroll
      for (int h = 0; h < 2; h++) {
        const uint2* w = v + h * 5;
        const uint32_t kb = sb + SM_KVB + h * 4096 + f * 64;
        zz[h] = __shfl_sync(0xffffffffu, w[4].y, (lane & 28) + 1);
        stsm4(kb + ((chi ^ sw) << 4), w[0].x, q == 0 ? w[4].x : w[0].y, w[1].x, q == 1 ? w[4].x : w[1].y);
        stsm4(kb + (((2 + chi) ^ sw) << 4), w[2].x, q == 2 ? w[4].x : w[2].y, w[3].x, q == 3 ? w[4].x : w[3].y);
      }
      stsm4(sb + SM_KVB + 8192 + f * 64 + ((chi ^ sw) << 4), zz[0], zz[0] >> 16, zz[1], zz[1] >> 16);
      fence_async_smem();
      __syncwarp();
      if (elect_one()) mbar_arrive(BAR(B_KVB));
    }
    {
      const int pm = wi >> 1;
      if (wi & 1) {
        const int hf = half ^ pm;
        mbar_wait(BAR(B_PEER), 0);
        mbar_wait_bounded(BAR(B_OP + hf * 2), 0);
        const unsigned c0 = clock32();
        while (clock32() - c0 < (unsigned)(pm ? LATE_DELAY + ct * LATE_STEP : (ct >> 2) * URG_STEP)) {}
        __syncwarp();
        auto to_partner = [&](int mb) {
          asm volatile("cp.async.bulk.shared::cluster.shared::cta.mbarrier::complete_tx::bytes [%0], [%1], 8192, [%2];"
                       :: "r"((sb ^ (1u << 24)) + SM_RA + mb * 8192), "r"(sb + SM_O + mb * 8192), "r"(BAR(B_F2 + mb * 16 + 1) ^ (1u << 24)) : "memory");
        };
        unsigned* hint = g_z.hint + (tg * 2 + hf) * 32 + hp;
        const int sz = pm ? LATE_SZ : 8192;
#pragma unroll 1
        for (int o = 0; o < 16384; o += sz) {
          const int mb = o >> 13;
          if (o == 8192) mbar_wait(BAR(B_OP + hf * 2 + 1), 0);
          if (elect_one()) bulk_store(reinterpret_cast<char*>(o_piece(hf, mb, hp)) + (o & 8191), sb + SM_O + pm * 16384 + o, sz);
          bulk_commit();
          if (pm == 0 && elect_one()) to_partner(mb);
          bulk_wait0();
          __syncwarp();
          if (((o + sz) & 8191) == 0 && lane == 0) { st_relaxed(hint + mb * 16, 1); TSTAMP((pm ? 37 : 15) + mb); }
        }
        if (lane == 0) mbar_arrive(BAR(B_ST + pm));
        if (pm == 0) {
          if (lane < 2) mbar_arrive_cluster((lane << 24) + SB0 + SM_BAR + 8 * (B_GO + NA2));
          mbar_wait(BAR(B5_AFTER), 0);
#pragma unroll 1
          for (int i = XT_IN_A ? NB2 : 5; i < 16; i++) {
            mbar_wait(i < NB2 ? BAR(B_XTD) : BAR(B_DB + i - NB2), 0);
            if (elect_one()) load_b2(i);
          }
        } else {
          mbar_wait(BAR(B_ST), 0);
          fence_gpu();
          if (lane == 0) st_relaxed(g_z.done + b, 1);
        }
      } else if (pm) {
        const __nv_bfloat16* src = o_piece(half, rank, half * 8);
        uint32_t dst = sb + SM_RA + 16384 + rank * 8192;
        mbar_wait(BAR(B_PEER), 0);
#pragma unroll 1
        for (int i = 2; i < 16; i++) {
          if (i == (ct & 6) + 2) src += 2 * 4096;
          if (i == 8) src -= half * 16 * 4096;
          mbar_wait_bounded(BAR(B_GO + i), 0);
          if (elect_one()) {
            asm volatile("cp.async.bulk.shared::cluster.global.mbarrier::complete_tx::bytes.multicast::cluster [%0], [%1], 8192, [%2], %3;"
                         :: "r"(dst), "l"(src), "r"(BAR(B_F2 + rank * 16 + i)), "h"((uint16_t)3) : "memory");
            if (i == 2) TSTAMP(19);
          }
          src += 4096;
          dst += (i == 5 || i == 10) ? -4 * 16384 : 16384;
        }
      } else {
        const unsigned* flag = g_z.hint + (tg * 2 + half) * 32 + rank * 16 + slice_of(lane & 15);
        bool seen = lane < 2 || lane > 15;
        mbar_wait(BAR(B_OP + half * 2 + rank), 0);
        int it = 0;
        do {
          if (ld_relaxed(flag) != 0 && !seen) {
            mbar_arrive(BAR(B_GO) + lane * 8);
            seen = true;
          }
          if (++it > (1 << 20)) __trap();
        } while (!__all_sync(0xffffffffu, seen));
      }
    }
  } else {
    asm volatile("setmaxnreg.inc.sync.aligned.u32 224;");
    const int wg = warp >> 2, wi = warp & 3;
    cluster_wait();
    if (tid == 0) TSTAMP(59);
    float acc0[96], acc1[96];
    {
      int s = 0, ph = 0, sprev = 0;
#pragma unroll 1
      for (int kt = 0; kt < KT - STAGES; kt++) {
        mbar_wait(BAR(B_FULL + s), ph);
        if (kt == 0 && tid == 0) TSTAMP(1);
        if (tid == 0 && !(kt & 1)) TSTAMP(44 + kt / 2);
        const uint32_t da = dlo(SB0 + SM_RA, 16) + s * (A_BYTES >> 4) + wg * 512;
        const uint32_t db = dlo(SB0 + SM_RB, 4096) + s * (B_BYTES >> 4);
        wgmma_fence();
#pragma unroll
        for (int k = 0; k < 2; k++) {
          wgmma_ss_n192<0, 1, H64, H128>(acc0, da + k * 2, db + k * 128, (kt | k) != 0);
          wgmma_ss_n192<0, 1, H64, H128>(acc1, da + 256 + k * 2, db + k * 128, (kt | k) != 0);
        }
        wgmma_commit();
        wgmma_wait<1>();
        if (kt > 0 && wi < 2 && elect_one()) mbar_arrive_cluster((wi << 24) + SB0 + SM_BAR + 8 * (B_EMPTY + sprev));
        sprev = s;
        if (++s == STAGES) { s = 0; ph ^= 1; }
      }
#pragma unroll 1
      for (int kt = 0; kt < STAGES; kt++) {
        mbar_wait(BAR(B_FULL + s), ph);
        const uint32_t da = dlo(SB0 + SM_RA, 16) + s * (A_BYTES >> 4) + wg * 512;
        const uint32_t db = dlo(SB0 + SM_RB, 4096) + s * (B_BYTES >> 4);
        wgmma_fence();
        wgmma_ss_n192<0, 1, H64, H128>(acc0, da, db, 1);
        wgmma_ss_n192<0, 1, H64, H128>(acc0, da + 2, db + 128, 1);
        wgmma_commit();
        wgmma_wait<1>();
        if (kt == 0 && wi < 2 && elect_one()) mbar_arrive_cluster((wi << 24) + SB0 + SM_BAR + 8 * (B_EMPTY + 1));
        if (++s == STAGES) { s = 0; ph ^= 1; }
      }
      mbar_wait(BAR(B_RDY), 0);
    }
    const int trow = wg * 128 + wi * 16 + (lane & 15);
    const int chi = lane >> 4;
    uint32_t ak[16], aq[2][16];
    float p[4][16];
    auto catch_one = [&](int i) {
      const int s = (2 + (i >> 1)) % STAGES;
      wgmma_ss_n192<0, 1, H64, H128>(acc1, dlo(SB0 + SM_RA + s * A_BYTES + 4096 + (i & 1) * 32, 16) + wg * 512, dlo(SB0 + SM_RB + s * B_BYTES + (i & 1) * 2048, 4096), 1);
    };
    auto catch_up = [&](int s) { wgmma_fence(); catch_one(2 * s - 4); catch_one(2 * s - 3); wgmma_commit(); };
    auto store_v = [&](const float (&acc)[96], int mb) {
#pragma unroll
      for (int h = 0; h < 2; h++)
#pragma unroll
        for (int jj = 0; jj < 2; jj++) {
          const int o = 64 + h * 16 + jj * 8;
          stsm4(sb + SM_V + h * 16384 + (trow + mb * 64) * 64 + (((2 * jj + chi) ^ ((trow >> 1) & 3)) << 4),
                pack_bf16(acc[o], acc[o + 1]), pack_bf16(acc[o + 2], acc[o + 3]), pack_bf16(acc[o + 4], acc[o + 5]), pack_bf16(acc[o + 6], acc[o + 7]));
        }
    };
    const uint32_t pa = sb + SM_PHIK + (wi >> 1) * 16384 + wg * 8192 + (trow & 31) * 128 + ((chi ^ (trow & 7)) << 4);
    auto store_phi = [&](const uint32_t (&phi)[16], int h, int mb) { store_phi_k(phi, pa + (1 - h) * 32768 + mb * 4096); };
    auto hand_over = [&](int i, bool ok) { hand_over_smem(BAR(B_PHI + i), ok); };
    bool okk[3];
    {
      HState hs;
      uint32_t phi[16];
      float d0, d1;
      catch_up(2);
      wgmma_wait<1>();
      fence_regs(acc0);
      if (tid == 0) TSTAMP(2);
      store_v(acc0, 0);
      pack_frags<32>(acc0, ak);
      issue_feat(ak, p[0], p[1], SB0 + SM_WPHI);
      catch_up(3);
      pack_frags<0>(acc0, aq[0]);
      wgmma_wait<1>();
      fence_regs(p[0]); fence_regs(p[1]); keep_alive(ak);
      wgmma_fence();
#pragma unroll
      for (int i = 4; i < 4 + NFIRST; i++) catch_one(i);
      okk[0] = hedgehog_fast<true>(p[0], phi, d0, d1);
      store_phi(phi, 0, 0);
#pragma unroll
      for (int i = 4 + NFIRST; i < 12; i++) catch_one(i);
      wgmma_commit();
      okk[0] &= hedgehog_fast<true>(p[1], phi, d0, d1);
      store_phi(phi, 1, 0);
      if (tid == 0) TSTAMP(17);
      wgmma_wait<0>();
      fence_regs(acc1);
      if (tid == 0) TSTAMP(27);
      if (wi < 2 && elect_one()) mbar_arrive_cluster((wi << 24) + SB0 + SM_BAR + 8 * (B_EMPTY + 1));
      pack_frags<32>(acc1, ak);
      issue_feat(ak, p[2], p[3], SB0 + SM_WPHI);
      store_v(acc1, 1);
      pack_frags<0>(acc1, aq[1]);
      wgmma_wait<0>();
      fence_regs(p[2]); fence_regs(p[3]); keep_alive(ak);
      asm volatile("setmaxnreg.dec.sync.aligned.u32 " STR(REG_C) ";");
      if (tid == 0) TSTAMP(28);
      HState h2;
      hedgehog_fast1(p[2], hs);
      hedgehog_fast1(p[3], h2);
      okk[1] = __all_sync(0xffffffffu, okk[0] & hedgehog_fast2<true>(hs, phi, d0, d1));
      store_phi(phi, 0, 1);
      hand_over(0, okk[1]);
      h2.s[0] += lds_f32(sb + SM_INFO + 12);
      okk[2] = __all_sync(0xffffffffu, okk[0] & hedgehog_fast2<true>(h2, phi, d0, d1));
      store_phi(phi, 1, 1);
      hand_over(1, okk[2]);
    }
    if (__builtin_expect(!(okk[1] & okk[2]), 0)) {
      __align__(16) float buf[64];
#pragma unroll
      for (int i = 0; i < 64; i++) buf[i] = p[i >> 4][i & 15];
      redo_phi_k(buf, okk[1] * 5 + okk[2] * 10, pa, BAR(B_PHI));
    }
    if (wi == 0 && lane == 0) TSTAMP(wg ? 29 : 3);
    uint32_t pq[4][16];
    float sc[8];
    issue_feat(aq[0], p[0], p[1], SB0 + SM_WPHI);
    issue_feat(aq[1], p[2], p[3], SB0 + SM_WPHI);
    mbar_wait(BAR(Q_AFTER), 0);
    wgmma_wait<0>();
#pragma unroll
    for (int u = 0; u < 4; u++) fence_regs(p[u]);
    keep_alive(aq[0]); keep_alive(aq[1]);
    if (tid == 0) TSTAMP(4);
    {
      bool ok = true;
#pragma unroll
      for (int u = 0; u < 4; u++) ok &= hedgehog_fast<false>(p[u], pq[u], sc[2 * u], sc[2 * u + 1]);
      if (__builtin_expect(!__all_sync(0xffffffffu, ok), 0)) {
        __align__(16) float buf[64];
#pragma unroll
        for (int i = 0; i < 64; i++) buf[i] = p[i >> 4][i & 15];
        hedgehog_slow(buf, 4);
#pragma unroll
        for (int i = 0; i < 64; i++) pq[i >> 4][i & 15] = __float_as_uint(buf[i]);
#pragma unroll
        for (int i = 0; i < 8; i++) sc[i] = 1.0f;
      }
    }
    if (tid == 0) TSTAMP(5);
    float acc[64];
    const int wq = wg ^ half;
    const uint32_t xo = wq * 8192 + wi * 2048 + (lane & 15) * 128 + ((chi ^ (lane & 7)) << 4);
    const uint32_t ga = sb + SM_GATE + (half * 128 + wq * 64 + wi * 16) * 2;
    mbar_wait(BAR(B_XT + wq), 0);
    float gt[4];
#pragma unroll
    for (int i = 0; i < 4; i++) gt[i] = lds_bf16(sb + SM_GATE + (wg * 128 + (i >> 1) * 64 + wi * 16 + (i & 1) * 8 + (lane >> 2)) * 2);
    const float g0 = lds_bf16(ga + (lane >> 2) * 2), g1 = lds_bf16(ga + 16 + (lane >> 2) * 2);
    const unsigned routed = lds_u32(sb + SM_INFO + 4);
    const uint32_t par = lds_u32(sb + SM_INFO) & 1, tmask = (lane & 3) ? ~0u : ~1u, tbit = (lane & 3) ? 0u : par;
    mbar_wait(BAR(B_KVB), 0);
    if (tid == 0) TSTAMP(7);
    if (wg != half) mbar_wait(BAR(B_OP + half * 2 + O_YIELD - 1), 0);
    {
      float nd[4][20];
#pragma unroll
      for (int u = 0; u < 4; u++)
#pragma unroll
        for (int i = 0; i < 16; i++) asm volatile("" : "+r"(pq[u][i]) :: "memory");
      auto num = [&](int mb, int k0, int k1) {
#pragma unroll
        for (int kk = k0; kk < k1; kk++)
#pragma unroll
          for (int h = 0; h < 2; h++) {
            const int u = mb * 2 + h;
            wgmma_rs_n40<1, H64>(nd[u], pq[u][4 * kk], pq[u][4 * kk + 1], pq[u][4 * kk + 2], pq[u][4 * kk + 3],
                                 dlo(SB0 + SM_KVB + h * 4096 + kk * 1024, 8192 - h * 4096 + h * 16), kk != 0);
          }
        wgmma_commit();
      };
      wgmma_fence();
      num(0, 0, 4);
      if (O_OVL == 2) num(1, 0, 4);
#pragma unroll
      for (int mb = 0; mb < 2; mb++) {
        if (O_OVL == 2 && mb == 0) wgmma_wait<1>(); else wgmma_wait<0>();
        fence_regs(nd[2 * mb]); fence_regs(nd[2 * mb + 1]);
        if (O_OVL == 1 && mb == 0) { wgmma_fence(); num(1, 0, 4); }
        if (tid == 0 && mb == 0) TSTAMP(18);
#pragma unroll
        for (int h = 0; h < 2; h++) {
          const int u = mb * 2 + h;
          const float i0 = gt[2 * mb] * rcp(fmaf(sc[2 * u], 1e-6f, nd[u][16])), i1 = gt[2 * mb + 1] * rcp(fmaf(sc[2 * u + 1], 1e-6f, nd[u][18]));
#pragma unroll
          for (int jj = 0; jj < 2; jj++) {
            const int o = jj * 8;
            stsm4(sb + SM_O + (wg ^ half) * 16384 + ((trow & 63) + mb * 64) * 128 + (((h * 4 + 2 * jj + chi) ^ (trow & 7)) << 4),
                  (pack_bf16(nd[u][o] * i0, nd[u][o + 1] * i0) & tmask) | tbit, (pack_bf16(nd[u][o + 2] * i1, nd[u][o + 3] * i1) & tmask) | tbit,
                  pack_bf16(nd[u][o + 4] * i0, nd[u][o + 5] * i0), pack_bf16(nd[u][o + 6] * i1, nd[u][o + 7] * i1));
          }
        }
        fence_async_smem();
        __syncwarp();
        if (elect_one()) mbar_arrive(BAR(B_OP + wg * 2 + mb));
        if (!O_OVL && mb == 0) { wgmma_fence(); num(1, 0, 4); }
      }
#pragma unroll
      for (int u = 0; u < 4; u++)
#pragma unroll
        for (int i = 0; i < 16; i++) asm volatile("" :: "r"(pq[u][i]) : "memory");
    }
    if (tid == 0) TSTAMP(8);
    uint32_t stale = 0;
    {
      const uint32_t ca = sb - SB0 - (dlo(0, 16) << 4) + wi * 2048 + (lane >> 2) * 128 + ((((lane & 3) * 2) ^ (lane >> 2)) << 4);
      const uint32_t da_end = dlo(SB0 + SM_RA + NA2 * 16384, 16) + wq * 512, f_end = BAR(B_F2 + wq * 16 + 16);
      uint32_t da = da_end - 1024, db = dlo(SB0 + SM_RB + 4 * 16384, 8192), f = f_end - 128;
      uint32_t xs[32];
#pragma unroll
      for (int i = 0; i < 2; i++) {
        mbar_wait(f + i * 8, 0);
        wgmma_fence();
#pragma unroll
        for (int k = 0; k < 4; k++) wgmma_ss_n128<0, 1, H128, H128>(acc, da - i * 4096 + k * 2, db + i * 1024 + k * 128, (i | k) != 0);
        wgmma_commit();
        if (i == 0) {
          if ((routed >> 4) == tg * 16 + half * 8 + wq * 4 + wi) mbar_wait_bounded(BAR(B_Y), 0);
#pragma unroll
          for (int jj = 0; jj < 8; jj++)
            ldsm4(((sb + SM_XT + xo) ^ ((jj & 3) << 5)) + (jj >> 2) * 16384, xs[4 * jj], xs[4 * jj + 1], xs[4 * jj + 2], xs[4 * jj + 3]);
          fence_async_smem();
          __syncwarp();
          if (elect_one()) mbar_arrive_cluster(((XT_IN_A ? wq : rank) << 24) + SB0 + SM_BAR + 8 * (XT_IN_A ? B_GO + 3 : B_XTD));
        }
      }
      const float og0 = round_bf16(1.0f - g0), og1 = round_bf16(1.0f - g1);
      da -= 3072; db += 2048; f += 16;
      wgmma_wait<0>();
      fence_regs(acc);
      uint32_t dn = SB0 + SM_BAR + (wi ? (wq << 24) + 8 * (B_GO + NA2) : (rank << 24) + 8 * B_DB);
      if (wi < 2 && elect_one()) mbar_arrive_cluster(dn);
#pragma unroll
      for (int i = 0; i < 32; i++) { acc[2 * i] = fmaf((i & 1) ? og1 : og0, bf_lo(xs[i]), acc[2 * i]); acc[2 * i + 1] = fmaf((i & 1) ? og1 : og0, bf_hi(xs[i]), acc[2 * i + 1]); }
      fence_regs(acc);
      bool got = false;
#pragma unroll 1
      do {
        if (!got) mbar_wait(f, 0);
        wgmma_fence();
        wgmma_ss_n128<0, 1, H128, H128>(acc, da, db, 1);
        const uint32_t ta = ca + (da << 4), t0 = lds_u32(ta), t1 = lds_u32(ta + 1024);
        got = mbar_test(f + 8, 0);
#pragma unroll
        for (int k = 1; k < 4; k++) wgmma_ss_n128<0, 1, H128, H128>(acc, da + k * 2, db + k * 128, 1);
        wgmma_commit();
        da += 1024; if (da == da_end) da -= NA2 * 1024;
        db += 1024; if (db == dlo(SB0 + SM_RB + NB2 * 16384, 8192)) db -= NB2 * 1024;
        f += 8;
        stale |= (t0 ^ par) | (t1 ^ par);
        if (LEAD2 && wq == 0 && wi == 2 && f == f_end - 8 * LEAD_AT && elect_one()) mbar_arrive(BAR(B_F2 + 32 - LEAD2));
        wgmma_wait<1>();
        dn += 8;
        if (wi < 2 && f <= f_end - 32 && elect_one()) mbar_arrive_cluster(dn);
      } while (f != f_end);
      const uint32_t xa = sb + SM_RA + xo, xt = sb + SM_RA + wq * 8192 + wi * 2048;
      const int orow = tg * 256 + half * 128 + wq * 64 + wi * 16;
      const bool redo = __any_sync(0xffffffffu, stale & 1);
      wgmma_wait<0>();
      fence_regs(acc);
      if (wi == 0 && lane == 0) TSTAMP(wq ? 25 : 11);
      stage_out<0, 4>(acc, xa);
      fence_async_smem();
      __syncwarp();
      if (!redo && elect_one()) tma_store_2d(&maps.out, xt, ct * 128, orow);
      stage_out<4, 8>(acc, xa);
      if (__builtin_expect(redo, 0))
        redo_rows(o_piece(half, wq, 0), wo + ct * 128, g_z.done + tg * 16, x + (size_t)orow * D_ + ct * 128, xa, wi, ga, (int)routed - orow, sb + SM_UPD);
      fence_async_smem();
      __syncwarp();
      if (elect_one()) {
        tma_store_2d(&maps.out, xt + 16384, ct * 128 + 64, orow);
        if (redo) tma_store_2d(&maps.out, xt, ct * 128, orow);
      }
      bulk_commit();
      bulk_wait0_read();
    }
  }
}

typedef CUresult (*PFN_encodeTiled)(CUtensorMap*, CUtensorMapDataType, cuuint32_t, void*, const cuuint64_t*, const cuuint64_t*,
                                    const cuuint32_t*, const cuuint32_t*, CUtensorMapInterleave, CUtensorMapSwizzle,
                                    CUtensorMapL2promotion, CUtensorMapFloatOOBfill);
static void make_map(PFN_encodeTiled fn, CUtensorMap* m, const void* ptr, uint64_t rows, uint64_t cols, uint32_t brows, uint32_t bcols,
                     CUtensorMapSwizzle sw, CUtensorMapL2promotion prom) {
  cuuint64_t dims[2] = {cols, rows}; cuuint64_t strides[1] = {cols * 2}; cuuint32_t box[2] = {bcols, brows}; cuuint32_t es[2] = {1, 1};
  fn(m, CU_TENSOR_MAP_DATA_TYPE_BFLOAT16, 2, const_cast<void*>(ptr), dims, strides, box, es, CU_TENSOR_MAP_INTERLEAVE_NONE, sw, prom,
     CU_TENSOR_MAP_FLOAT_OOB_FILL_NONE);
}

extern "C" void kernel_launch(void* const* d_in, const int* in_sizes, int n_in, void* d_out, int out_size) {
  const __nv_bfloat16* x = (const __nv_bfloat16*)d_in[0];
  const __nv_bfloat16* wqkv = (const __nv_bfloat16*)d_in[1];
  const __nv_bfloat16* wphi = (const __nv_bfloat16*)d_in[2];
  const __nv_bfloat16* wo = (const __nv_bfloat16*)d_in[3];
  const __nv_bfloat16* w_r = (const __nv_bfloat16*)d_in[5];
  const __nv_bfloat16* w_gate = (const __nv_bfloat16*)d_in[6];
  const __nv_bfloat16* w_up = (const __nv_bfloat16*)d_in[7];
  const __nv_bfloat16* w_down = (const __nv_bfloat16*)d_in[8];
  const __nv_bfloat16* gate_w = (const __nv_bfloat16*)d_in[9];
  void* fp = nullptr; cudaDriverEntryPointQueryResult qr;
  cudaGetDriverEntryPoint("cuTensorMapEncodeTiled", &fp, cudaEnableDefault, &qr);
  PFN_encodeTiled fn = (PFN_encodeTiled)fp;
  Maps m;
  const CUtensorMapL2promotion P128 = CU_TENSOR_MAP_L2_PROMOTION_L2_128B;
  make_map(fn, &m.x, x, S_, D_, 128, 32, CU_TENSOR_MAP_SWIZZLE_64B, P128);
  {
    cuuint64_t dims[3] = {D_, D_, 3}; cuuint64_t strides[2] = {3 * D_ * 2, D_ * 2}; cuuint32_t box[3] = {64, 32, 3}; cuuint32_t es[3] = {1, 1, 1};
    fn(&m.w, CU_TENSOR_MAP_DATA_TYPE_BFLOAT16, 3, (void*)wqkv, dims, strides, box, es, CU_TENSOR_MAP_INTERLEAVE_NONE,
       CU_TENSOR_MAP_SWIZZLE_128B, P128, CU_TENSOR_MAP_FLOAT_OOB_FILL_NONE);
  }
  {
    cuuint64_t dims[3] = {64, D_, 16}; cuuint64_t strides[2] = {D_ * 2, 128}; cuuint32_t box[3] = {64, 64, 2}; cuuint32_t es[3] = {1, 1, 1};
    fn(&m.wo, CU_TENSOR_MAP_DATA_TYPE_BFLOAT16, 3, (void*)wo, dims, strides, box, es, CU_TENSOR_MAP_INTERLEAVE_NONE,
       CU_TENSOR_MAP_SWIZZLE_128B, P128, CU_TENSOR_MAP_FLOAT_OOB_FILL_NONE);
  }
  make_map(fn, &m.wphi, wphi, 1024, 32, 64, 32, CU_TENSOR_MAP_SWIZZLE_64B, P128);
  for (int i = 0; i < 3; i++) {
    cuuint64_t dims[3] = {i < 2 ? (cuuint64_t)F_ : 64, i < 2 ? (cuuint64_t)16 : F_, i < 2 ? (cuuint64_t)64 : 16};
    cuuint64_t strides[2] = {i < 2 ? (cuuint64_t)F_ * 2 : D_ * 2, i < 2 ? (cuuint64_t)F_ * 32 : 128};
    cuuint32_t box[3] = {64, i < 2 ? 16u : 4u, i < 2 ? 4u : 16u}; cuuint32_t es[3] = {1, 1, 1};
    fn(&m.wg + i, CU_TENSOR_MAP_DATA_TYPE_BFLOAT16, 3, (void*)(i == 0 ? w_gate : i == 1 ? w_up : w_down), dims, strides, box, es,
       CU_TENSOR_MAP_INTERLEAVE_NONE, CU_TENSOR_MAP_SWIZZLE_NONE, P128, CU_TENSOR_MAP_FLOAT_OOB_FILL_NONE);
  }
  make_map(fn, &m.xt, x, S_, D_, 64, 64, CU_TENSOR_MAP_SWIZZLE_128B, P128);
  make_map(fn, &m.out, d_out, S_, D_, 16, 64, CU_TENSOR_MAP_SWIZZLE_128B, P128);
  make_map(fn, &m.xr, x, S_, D_, 16, 128, CU_TENSOR_MAP_SWIZZLE_NONE, P128);
  make_map(fn, &m.tg, w_gate, D_, F_, 64, 64, CU_TENSOR_MAP_SWIZZLE_NONE, P128);
  make_map(fn, &m.tu, w_up, D_, F_, 64, 64, CU_TENSOR_MAP_SWIZZLE_NONE, P128);
  make_map(fn, &m.td, w_down, F_ * 16, 64, 64, 64, CU_TENSOR_MAP_SWIZZLE_NONE, P128);
  make_map(fn, &m.to, wo, D_ * 16, 64, 64, 64, CU_TENSOR_MAP_SWIZZLE_NONE, P128);
  for (int cl = 0; cl < NCTA / 2; cl++) {
    const int col = cl < 4 ? 7 : cl < 36 ? ((cl - 4) & 3) + ((cl - 4) & 4) * 2 : (cl - 36) % 7 + ((cl - 36) % 7 < 3 ? 4 : 9);
    const int pos = cl < 4 ? cl : cl < 36 ? (cl - 4) >> 3 : (cl - 36) / 7;
    m.tile[cl] = ((col & 7) * 16 + (col >> 3) * 8 + pos * 2) | (EVEN_FFN ? cl * 2 : (col & 7) * 16 + (col >> 3) * 8 + pos * 2) << 8;
  }
  m.tile[NCTA / 2] = NCTA;
  cudaFuncSetAttribute(fused_kernel, cudaFuncAttributeMaxDynamicSharedMemorySize, SM_TOTAL);
  fused_kernel<<<NCTA + 2, 512, SM_TOTAL>>>(m, x, wo, w_r, gate_w);
}
```

```cpp
#include <cuda_runtime.h>
#include <cuda_bf16.h>
#include <cuda.h>
#include <stdint.h>

__device__ __forceinline__ uint32_t smem_u32(const void* p) { return (uint32_t)__cvta_generic_to_shared(p); }
__device__ __forceinline__ void mbar_init(uint32_t bar, uint32_t cnt) { asm volatile("mbarrier.init.shared::cta.b64 [%0], %1;" :: "r"(bar), "r"(cnt) : "memory"); }
__device__ __forceinline__ void mbar_expect_tx(uint32_t bar, uint32_t bytes) { asm volatile("mbarrier.arrive.expect_tx.shared::cta.b64 _, [%0], %1;" :: "r"(bar), "r"(bytes) : "memory"); }
__device__ __forceinline__ void mbar_arrive(uint32_t bar) { asm volatile("mbarrier.arrive.shared::cta.b64 _, [%0];" :: "r"(bar) : "memory"); }
__device__ __forceinline__ bool mbar_try_wait(uint32_t bar, uint32_t parity) {
  uint32_t ok;
  asm volatile("{\n.reg .pred p;\nmbarrier.try_wait.parity.shared::cta.b64 p, [%1], %2;\nselp.u32 %0, 1, 0, p;\n}" : "=r"(ok) : "r"(bar), "r"(parity) : "memory");
  return ok;
}
__device__ __forceinline__ bool mbar_test(uint32_t bar, uint32_t parity) {
  uint32_t ok;
  asm volatile("{\n.reg .pred p;\nmbarrier.test_wait.parity.shared::cta.b64 p, [%1], %2;\nselp.u32 %0, 1, 0, p;\n}" : "=r"(ok) : "r"(bar), "r"(parity) : "memory");
  return ok;
}
__device__ __forceinline__ void mbar_wait(uint32_t bar, uint32_t parity) {
  asm volatile("{\n.reg .pred p;\nWAIT: mbarrier.try_wait.parity.shared::cta.b64 p, [%0], %1;\n@!p bra.uni WAIT;\n}" :: "r"(bar), "r"(parity) : "memory");
}
__device__ __forceinline__ void mbar_wait_bounded(uint32_t bar, uint32_t parity) {
#pragma unroll 1
  for (int it = 0; it < (1 << 22); it++) { if (mbar_try_wait(bar, parity)) return; }
  __trap();
}
__device__ __forceinline__ void tma_load_2d(uint32_t dst, const CUtensorMap* tm, int c0, int c1, uint32_t bar) {
  asm volatile("cp.async.bulk.tensor.2d.shared::cluster.global.mbarrier::complete_tx::bytes [%0], [%1, {%3, %4}], [%2];"
    :: "r"(dst), "l"(tm), "r"(bar), "r"(c0), "r"(c1) : "memory");
}
__device__ __forceinline__ void tma_load_2d_mc(uint32_t dst, const CUtensorMap* tm, int c0, int c1, uint32_t bar) {
  asm volatile("cp.async.bulk.tensor.2d.shared::cluster.global.mbarrier::complete_tx::bytes.multicast::cluster [%0], [%1, {%3, %4}], [%2], %5;"
    :: "r"(dst), "l"(tm), "r"(bar), "r"(c0), "r"(c1), "h"((uint16_t)3) : "memory");
}
__device__ __forceinline__ void mbar_arrive_cluster(uint32_t bar) { asm volatile("mbarrier.arrive.shared::cluster.b64 _, [%0];" :: "r"(bar) : "memory"); }
__device__ __forceinline__ void wgmma_fence() { asm volatile("wgmma.fence.sync.aligned;" ::: "memory"); }
__device__ __forceinline__ void wgmma_commit() { asm volatile("wgmma.commit_group.sync.aligned;" ::: "memory"); }
template <int N> __device__ __forceinline__ void wgmma_wait() { asm volatile("wgmma.wait_group.sync.aligned %0;" :: "n"(N) : "memory"); }
template <int N> __device__ __forceinline__ void fence_regs(float (&d)[N]) {
#pragma unroll
  for (int i = 0; i < N; i++) asm volatile("" : "+f"(d[i]) :: "memory");
}
__host__ __device__ constexpr uint32_t dlo(uint32_t addr, uint32_t lbo) { return (addr >> 4) | ((lbo >> 4) << 16); }
constexpr uint32_t H128 = (1024 >> 4) | (1u << 30);
constexpr uint32_t H64 = (512 >> 4) | (2u << 30);

template <int TA, int TB, uint32_t HA, uint32_t HB>
__device__ __forceinline__ void wgmma_ss_n192(float (&d)[96], uint32_t da, uint32_t db, int scale_d) {
  asm volatile("{\n.reg .pred p;\n.reg .b64 da, db;\nsetp.ne.b32 p, %98, 0;\nmov.b64 da, {%96, %101};\nmov.b64 db, {%97, %102};\n"
    "wgmma.mma_async.sync.aligned.m64n192k16.f32.bf16.bf16 {%0, %1, %2, %3, %4, %5, %6, %7, %8, %9, %10, %11, %12, %13, %14, %15, %16, %17, %18, %19, %20, %21, %22, %23, %24, %25, %26, %27, %28, %29, %30, %31, %32, %33, %34, %35, %36, %37, %38, %39, %40, %41, %42, %43, %44, %45, %46, %47, %48, %49, %50, %51, %52, %53, %54, %55, %56, %57, %58, %59, %60, %61, %62, %63, %64, %65, %66, %67, %68, %69, %70, %71, %72, %73, %74, %75, %76, %77, %78, %79, %80, %81, %82, %83, %84, %85, %86, %87, %88, %89, %90, %91, %92, %93, %94, %95}, da, db, p, 1, 1, %99, %100;\n}\n"
    : "+f"(d[0]), "+f"(d[1]), "+f"(d[2]), "+f"(d[3]), "+f"(d[4]), "+f"(d[5]), "+f"(d[6]), "+f"(d[7]), "+f"(d[8]), "+f"(d[9]), "+f"(d[10]), "+f"(d[11]), "+f"(d[12]), "+f"(d[13]), "+f"(d[14]), "+f"(d[15]), "+f"(d[16]), "+f"(d[17]), "+f"(d[18]), "+f"(d[19]), "+f"(d[20]), "+f"(d[21]), "+f"(d[22]), "+f"(d[23]), "+f"(d[24]), "+f"(d[25]), "+f"(d[26]), "+f"(d[27]), "+f"(d[28]), "+f"(d[29]), "+f"(d[30]), "+f"(d[31]), "+f"(d[32]), "+f"(d[33]), "+f"(d[34]), "+f"(d[35]), "+f"(d[36]), "+f"(d[37]), "+f"(d[38]), "+f"(d[39]), "+f"(d[40]), "+f"(d[41]), "+f"(d[42]), "+f"(d[43]), "+f"(d[44]), "+f"(d[45]), "+f"(d[46]), "+f"(d[47]), "+f"(d[48]), "+f"(d[49]), "+f"(d[50]), "+f"(d[51]), "+f"(d[52]), "+f"(d[53]), "+f"(d[54]), "+f"(d[55]), "+f"(d[56]), "+f"(d[57]), "+f"(d[58]), "+f"(d[59]), "+f"(d[60]), "+f"(d[61]), "+f"(d[62]), "+f"(d[63]), "+f"(d[64]), "+f"(d[65]), "+f"(d[66]), "+f"(d[67]), "+f"(d[68]), "+f"(d[69]), "+f"(d[70]), "+f"(d[71]), "+f"(d[72]), "+f"(d[73]), "+f"(d[74]), "+f"(d[75]), "+f"(d[76]), "+f"(d[77]), "+f"(d[78]), "+f"(d[79]), "+f"(d[80]), "+f"(d[81]), "+f"(d[82]), "+f"(d[83]), "+f"(d[84]), "+f"(d[85]), "+f"(d[86]), "+f"(d[87]), "+f"(d[88]), "+f"(d[89]), "+f"(d[90]), "+f"(d[91]), "+f"(d[92]), "+f"(d[93]), "+f"(d[94]), "+f"(d[95])
    : "r"(da), "r"(db), "r"(scale_d), "n"(TA), "n"(TB), "n"(HA), "n"(HB));
}

template <int TA, int TB, uint32_t HA, uint32_t HB>
__device__ __forceinline__ void wgmma_ss_n128(float (&d)[64], uint32_t da, uint32_t db, int scale_d) {
  asm volatile("{\n.reg .pred p;\n.reg .b64 da, db;\nsetp.ne.b32 p, %66, 0;\nmov.b64 da, {%64, %69};\nmov.b64 db, {%65, %70};\n"
    "wgmma.mma_async.sync.aligned.m64n128k16.f32.bf16.bf16 {%0, %1, %2, %3, %4, %5, %6, %7, %8, %9, %10, %11, %12, %13, %14, %15, %16, %17, %18, %19, %20, %21, %22, %23, %24, %25, %26, %27, %28, %29, %30, %31, %32, %33, %34, %35, %36, %37, %38, %39, %40, %41, %42, %43, %44, %45, %46, %47, %48, %49, %50, %51, %52, %53, %54, %55, %56, %57, %58, %59, %60, %61, %62, %63}, da, db, p, 1, 1, %67, %68;\n}\n"
    : "+f"(d[0]), "+f"(d[1]), "+f"(d[2]), "+f"(d[3]), "+f"(d[4]), "+f"(d[5]), "+f"(d[6]), "+f"(d[7]), "+f"(d[8]), "+f"(d[9]), "+f"(d[10]), "+f"(d[11]), "+f"(d[12]), "+f"(d[13]), "+f"(d[14]), "+f"(d[15]), "+f"(d[16]), "+f"(d[17]), "+f"(d[18]), "+f"(d[19]), "+f"(d[20]), "+f"(d[21]), "+f"(d[22]), "+f"(d[23]), "+f"(d[24]), "+f"(d[25]), "+f"(d[26]), "+f"(d[27]), "+f"(d[28]), "+f"(d[29]), "+f"(d[30]), "+f"(d[31]), "+f"(d[32]), "+f"(d[33]), "+f"(d[34]), "+f"(d[35]), "+f"(d[36]), "+f"(d[37]), "+f"(d[38]), "+f"(d[39]), "+f"(d[40]), "+f"(d[41]), "+f"(d[42]), "+f"(d[43]), "+f"(d[44]), "+f"(d[45]), "+f"(d[46]), "+f"(d[47]), "+f"(d[48]), "+f"(d[49]), "+f"(d[50]), "+f"(d[51]), "+f"(d[52]), "+f"(d[53]), "+f"(d[54]), "+f"(d[55]), "+f"(d[56]), "+f"(d[57]), "+f"(d[58]), "+f"(d[59]), "+f"(d[60]), "+f"(d[61]), "+f"(d[62]), "+f"(d[63])
    : "r"(da), "r"(db), "r"(scale_d), "n"(TA), "n"(TB), "n"(HA), "n"(HB));
}

template <int TA, int TB, uint32_t HA, uint32_t HB>
__device__ __forceinline__ void wgmma_ss_n40(float (&d)[20], uint32_t da, uint32_t db, int scale_d) {
  asm volatile("{\n.reg .pred p;\n.reg .b64 da, db;\nsetp.ne.b32 p, %22, 0;\nmov.b64 da, {%20, %25};\nmov.b64 db, {%21, %26};\n"
    "wgmma.mma_async.sync.aligned.m64n40k16.f32.bf16.bf16 {%0, %1, %2, %3, %4, %5, %6, %7, %8, %9, %10, %11, %12, %13, %14, %15, %16, %17, %18, %19}, da, db, p, 1, 1, %23, %24;\n}\n"
    : "+f"(d[0]), "+f"(d[1]), "+f"(d[2]), "+f"(d[3]), "+f"(d[4]), "+f"(d[5]), "+f"(d[6]), "+f"(d[7]), "+f"(d[8]), "+f"(d[9]), "+f"(d[10]), "+f"(d[11]), "+f"(d[12]), "+f"(d[13]), "+f"(d[14]), "+f"(d[15]), "+f"(d[16]), "+f"(d[17]), "+f"(d[18]), "+f"(d[19])
    : "r"(da), "r"(db), "r"(scale_d), "n"(TA), "n"(TB), "n"(HA), "n"(HB));
}

template <int TB, uint32_t HB>
__device__ __forceinline__ void wgmma_rs_n32(float (&d)[16], uint32_t a0, uint32_t a1, uint32_t a2, uint32_t a3, uint32_t db, int scale_d) {
  asm volatile("{\n.reg .pred p;\n.reg .b64 db;\nsetp.ne.b32 p, %21, 0;\nmov.b64 db, {%20, %23};\n"
    "wgmma.mma_async.sync.aligned.m64n32k16.f32.bf16.bf16 {%0, %1, %2, %3, %4, %5, %6, %7, %8, %9, %10, %11, %12, %13, %14, %15}, {%16, %17, %18, %19}, db, p, 1, 1, %22;\n}\n"
    : "+f"(d[0]), "+f"(d[1]), "+f"(d[2]), "+f"(d[3]), "+f"(d[4]), "+f"(d[5]), "+f"(d[6]), "+f"(d[7]), "+f"(d[8]), "+f"(d[9]), "+f"(d[10]), "+f"(d[11]), "+f"(d[12]), "+f"(d[13]), "+f"(d[14]), "+f"(d[15])
    : "r"(a0), "r"(a1), "r"(a2), "r"(a3), "r"(db), "r"(scale_d), "n"(TB), "n"(HB));
}

template <int TB, uint32_t HB>
__device__ __forceinline__ void wgmma_rs_n40(float (&d)[20], uint32_t a0, uint32_t a1, uint32_t a2, uint32_t a3, uint32_t db, int scale_d) {
  asm volatile("{\n.reg .pred p;\n.reg .b64 db;\nsetp.ne.b32 p, %25, 0;\nmov.b64 db, {%24, %27};\n"
    "wgmma.mma_async.sync.aligned.m64n40k16.f32.bf16.bf16 {%0, %1, %2, %3, %4, %5, %6, %7, %8, %9, %10, %11, %12, %13, %14, %15, %16, %17, %18, %19}, {%20, %21, %22, %23}, db, p, 1, 1, %26;\n}\n"
    : "+f"(d[0]), "+f"(d[1]), "+f"(d[2]), "+f"(d[3]), "+f"(d[4]), "+f"(d[5]), "+f"(d[6]), "+f"(d[7]), "+f"(d[8]), "+f"(d[9]), "+f"(d[10]), "+f"(d[11]), "+f"(d[12]), "+f"(d[13]), "+f"(d[14]), "+f"(d[15]), "+f"(d[16]), "+f"(d[17]), "+f"(d[18]), "+f"(d[19])
    : "r"(a0), "r"(a1), "r"(a2), "r"(a3), "r"(db), "r"(scale_d), "n"(TB), "n"(HB));
}

constexpr int S_ = 2048, D_ = 1024, F_ = 3584;
constexpr int NCTA = 128;
#define NMOE_ 112
constexpr int NMOE = NMOE_;
#define KV16 1
constexpr int KVH = 5 * 128 * 2;

#define NY 8
struct Zeroed {
  float kv[32 * KVH];
  float y[NY * 2 * D_];
  unsigned hint[512];
  unsigned done[128];
  unsigned pad[384];
};
constexpr int ZB = KVH + 32 + NY * 64;
static_assert(sizeof(Zeroed) == NCTA * ZB, "zeroed block");
__device__ __align__(128) Zeroed g_z;
__device__ __align__(128) unsigned g_key[4 * NCTA];
__device__ __align__(128) unsigned g_ready[NCTA];
__device__ __align__(128) uint2 g_bcast[2 * 8 * 16];
__device__ __align__(128) unsigned g_gate[S_];
__device__ __align__(1024) __nv_bfloat16 g_o[S_ * D_];
#define TSTAMP(i)
#define GSTAMP(i)

constexpr int STAGES = 6, KT = 32;
constexpr int A_BYTES = 256 * 64, B_BYTES = 192 * 64, STAGE_BYTES = A_BYTES + B_BYTES;
constexpr int SM_RA = 0;
constexpr int SM_RB = STAGES * A_BYTES;
constexpr int SM_PHIK = 0;
constexpr int SM_V = 65536;
constexpr int SM_O = SM_V;
constexpr int NA2 = 5, NB2 = 7;
#define XT_IN_A 1
constexpr int SM_XT = (XT_IN_A ? SM_RA : SM_RB) + 2 * 16384;
constexpr int SM_XR = STAGES * STAGE_BYTES;
constexpr int SM_MOE = SM_XR;
constexpr int SM_XSEL = SM_XR + 36864;
constexpr int SM_RED = SM_XSEL + 2048;
constexpr int SM_WPHI = 212992;
constexpr int SM_KVB = SM_WPHI + 4096;
constexpr int SM_ONES = SM_KVB + 12288;
constexpr int SM_BAR = SM_ONES + 1024;
constexpr int SM_INFO = SM_BAR + 1008;
constexpr int SM_GATE = SM_BAR + 1024;
constexpr int SM_UPD = SM_GATE + 512;
constexpr int SM_TS = SM_UPD + 256;
constexpr int SM_TOTAL = SM_TS + 256;
static_assert(SM_TOTAL <= 232448 && ZB <= 4608, "smem");
static_assert(SM_WPHI % 1024 == 0 && SM_KVB % 1024 == 0 && SM_ONES % 1024 == 0, "align");
static_assert(SM_MOE + 40960 <= SM_WPHI && SM_RB + NB2 * 16384 <= SM_WPHI, "map");
#define QUAD 1
#define Q_UNROLL 1
#define HINT_U 0
#define HINT_L 0
#define COLMAP 0xefdb9ca875316420ull
#define INIT_FENCE 0
#define EXPT 0
#define PF_START 0
#define PF_OFF 0
#define KV_DELAY 400
#define O_YIELD 1
#define TAILV -1
#define NFIRST 5
#define Q_AFTER B_PHI + 1
#define LEAD2 4
#define EVEN_FFN 1
#define KEY_SLEEP 0
#define B5_AFTER B_F2 + 2
#define REG_C 192
#define REG_K 88
#define STR2(x) #x
#define STR(x) STR2(x)
#define XT_H 0
#define EARLY_MAP 1
#define TILE_MODE 1
#define NPRE 1
#define O_OVL 1
#define LATE_SZ 8192
#define LATE_SLEEP 0
#define URG_STEP 0
#define LEAD_AT 1
#define XR_AFTER 3
#define LATE_DELAY 300
#define LATE_STEP 400

constexpr int B_FULL = 0, B_XR = 6, B_WPHI = 10;
constexpr int B_EMPTY = 11, B_XRD = 17;
constexpr int B_INIT = 123;
constexpr int B_ST = 18, B_MOE = 20, B_XSEL = 24, B_H = 25, B_RDY = 26, B_Y = 27, B_XT = 28, B_PEER = 30;
constexpr int B_FB2 = 31, B_F2 = 47;
constexpr int B_DB = 79;
constexpr int B_GO = 95;
constexpr int B_KVB = 111, B_OP = 112, B_MOEE = 116;
constexpr int B_PHI = 120, B_XTD = 122;
constexpr int NBAR = 123;
__host__ __device__ constexpr int bar_count(int i) {
  return (LEAD2 && i == B_F2 + 32 - LEAD2) ? 2 : i < B_DB ? 1 : i < B_GO ? 2 : (XT_IN_A && i == B_GO + 3) ? 9 : i < B_GO + NA2 ? 1 : i == B_GO + NA2 ? 5 : i < B_KVB ? 3 : i < B_PHI ? 4 : 8;
}

struct Maps { CUtensorMap x, w, wo, wphi, wg, wu, wd, tg, tu, td, to, xr, xt, out; int tile[NCTA / 2 + 1]; };

__device__ __forceinline__ uint32_t pack_bf16(float lo, float hi) {
  uint32_t r; asm("cvt.rn.bf16x2.f32 %0, %1, %2;" : "=r"(r) : "f"(hi), "f"(lo)); return r;
}
__device__ __forceinline__ float bf_lo(uint32_t v) { return __uint_as_float(v << 16); }
__device__ __forceinline__ float bf_hi(uint32_t v) { return __uint_as_float(v & 0xffff0000u); }
__device__ __forceinline__ float round_bf16(float v) { return __bfloat162float(__float2bfloat16_rn(v)); }
__device__ __forceinline__ float ex2(float v) { float r; asm("ex2.approx.ftz.f32 %0, %1;" : "=f"(r) : "f"(v)); return r; }
__device__ __forceinline__ float rcp(float v) { float r; asm("rcp.approx.ftz.f32 %0, %1;" : "=f"(r) : "f"(v)); return r; }
__device__ __forceinline__ void stsm4(uint32_t addr, uint32_t r0, uint32_t r1, uint32_t r2, uint32_t r3) {
  asm volatile("stmatrix.sync.aligned.m8n8.x4.shared.b16 [%0], {%1, %2, %3, %4};" :: "r"(addr), "r"(r0), "r"(r1), "r"(r2), "r"(r3) : "memory");
}
__device__ __forceinline__ void stsm2(uint32_t addr, uint32_t r0, uint32_t r1) {
  asm volatile("stmatrix.sync.aligned.m8n8.x2.shared.b16 [%0], {%1, %2};" :: "r"(addr), "r"(r0), "r"(r1) : "memory");
}
__device__ __forceinline__ uint2 lds64(uint32_t addr) {
  uint2 v; asm volatile("ld.shared.v2.u32 {%0, %1}, [%2];" : "=r"(v.x), "=r"(v.y) : "r"(addr) : "memory"); return v;
}
__device__ __forceinline__ void lds128x4(uint32_t addr, uint4& a, uint4& b, uint4& c, uint4& d) {
  asm volatile("ld.shared.v4.u32 {%0, %1, %2, %3}, [%16];\nld.shared.v4.u32 {%4, %5, %6, %7}, [%16 + 128];\n"
               "ld.shared.v4.u32 {%8, %9, %10, %11}, [%16 + 256];\nld.shared.v4.u32 {%12, %13, %14, %15}, [%16 + 384];"
    : "=r"(a.x), "=r"(a.y), "=r"(a.z), "=r"(a.w), "=r"(b.x), "=r"(b.y), "=r"(b.z), "=r"(b.w),
      "=r"(c.x), "=r"(c.y), "=r"(c.z), "=r"(c.w), "=r"(d.x), "=r"(d.y), "=r"(d.z), "=r"(d.w) : "r"(addr) : "memory");
}
__device__ __forceinline__ void ldsm4(uint32_t addr, uint32_t& r0, uint32_t& r1, uint32_t& r2, uint32_t& r3) {
  asm volatile("ldmatrix.sync.aligned.m8n8.x4.shared.b16 {%0, %1, %2, %3}, [%4];" : "=r"(r0), "=r"(r1), "=r"(r2), "=r"(r3) : "r"(addr) : "memory");
}
__device__ __forceinline__ uint4 lds128(uint32_t addr) {
  uint4 v; asm volatile("ld.shared.v4.u32 {%0, %1, %2, %3}, [%4];" : "=r"(v.x), "=r"(v.y), "=r"(v.z), "=r"(v.w) : "r"(addr) : "memory"); return v;
}
__device__ __forceinline__ void sts128(uint32_t addr, uint4 v) {
  asm volatile("st.shared.v4.u32 [%0], {%1, %2, %3, %4};" :: "r"(addr), "r"(v.x), "r"(v.y), "r"(v.z), "r"(v.w) : "memory");
}
__device__ __forceinline__ float lds_f32(uint32_t addr) { float v; asm volatile("ld.shared.f32 %0, [%1];" : "=f"(v) : "r"(addr) : "memory"); return v; }
__device__ __forceinline__ void sts_f32(uint32_t addr, float v) { asm volatile("st.shared.f32 [%0], %1;" :: "r"(addr), "f"(v) : "memory"); }
__device__ __forceinline__ uint32_t lds_u32(uint32_t addr) { uint32_t v; asm volatile("ld.shared.u32 %0, [%1];" : "=r"(v) : "r"(addr) : "memory"); return v; }
__device__ __forceinline__ void sts_u32(uint32_t addr, uint32_t v) { asm volatile("st.shared.u32 [%0], %1;" :: "r"(addr), "r"(v) : "memory"); }
__device__ __forceinline__ unsigned clock32() { unsigned c; asm volatile("mov.u32 %0, %%clock;" : "=r"(c)); return c; }
__device__ __forceinline__ bool elect_one() {
  uint32_t p; asm volatile("{\n.reg .pred q;\nelect.sync _|q, 0xffffffff;\nselp.u32 %0, 1, 0, q;\n}" : "=r"(p)); return p;
}
__device__ __forceinline__ void bar_sync(int id, int n) { asm volatile("bar.sync %0, %1;" :: "r"(id), "r"(n) : "memory"); }
__device__ __forceinline__ void fence_async_smem() { asm volatile("fence.proxy.async.shared::cta;" ::: "memory"); }
__device__ __forceinline__ void fence_async_all() { asm volatile("fence.proxy.async;" ::: "memory"); }
__device__ __forceinline__ void fence_gpu() { asm volatile("fence.acq_rel.gpu;" ::: "memory"); }
__device__ __forceinline__ unsigned ld_acquire(const unsigned* p) { unsigned v; asm volatile("ld.acquire.gpu.global.u32 %0, [%1];" : "=r"(v) : "l"(p) : "memory"); return v; }
__device__ __forceinline__ void red_release(unsigned* p, unsigned v) { asm volatile("red.release.gpu.global.add.u32 [%0], %1;" :: "l"(p), "r"(v) : "memory"); }
__device__ __forceinline__ void st_release(unsigned* p, unsigned v) { asm volatile("st.release.gpu.global.u32 [%0], %1;" :: "l"(p), "r"(v) : "memory"); }
__device__ __forceinline__ unsigned ld_relaxed(const unsigned* p) { unsigned v; asm volatile("ld.relaxed.gpu.global.u32 %0, [%1];" : "=r"(v) : "l"(p) : "memory"); return v; }
__device__ __forceinline__ void red_relaxed(unsigned* p, unsigned v) { asm volatile("red.relaxed.gpu.global.add.u32 [%0], %1;" :: "l"(p), "r"(v) : "memory"); }
__device__ __forceinline__ void st_relaxed(unsigned* p, unsigned v) { asm volatile("st.relaxed.gpu.global.u32 [%0], %1;" :: "l"(p), "r"(v) : "memory"); }
__device__ __forceinline__ void st_relaxed2(uint2* p, unsigned a, unsigned b) { asm volatile("st.relaxed.gpu.global.v2.u32 [%0], {%1, %2};" :: "l"(p), "r"(a), "r"(b) : "memory"); }
template <int SLEEP>
__device__ __forceinline__ unsigned wait_tagged(const uint2* p, unsigned tag) {
  uint2 v;
  int it = 0;
  do {
    if (SLEEP && it > 0) __nanosleep(SLEEP);
    asm volatile("ld.relaxed.gpu.global.v2.u32 {%0, %1}, [%2];" : "=r"(v.x), "=r"(v.y) : "l"(p) : "memory");
    if (++it > (1 << 20)) __trap();
  } while (!__all_sync(0xffffffffu, v.y == tag));
  return v.x;
}
__device__ __forceinline__ void wait_counter(const unsigned* p, unsigned target) {
#pragma unroll 1
  for (int it = 0; it < (1 << 20); it++) { if ((int)(ld_relaxed(p) - target) >= 0) return; }
  __trap();
}
__device__ __forceinline__ float4 ldg_l2(const float* p) {
  float4 v; asm volatile("ld.relaxed.gpu.global.v4.f32 {%0, %1, %2, %3}, [%4];" : "=f"(v.x), "=f"(v.y), "=f"(v.z), "=f"(v.w) : "l"(p) : "memory"); return v;
}
__device__ __forceinline__ float ldg_l2_f(const float* p) { float v; asm volatile("ld.relaxed.gpu.global.f32 %0, [%1];" : "=f"(v) : "l"(p) : "memory"); return v; }
__device__ __forceinline__ void sts64(uint32_t addr, float a, float b) { asm volatile("st.shared.v2.f32 [%0], {%1, %2};" :: "r"(addr), "f"(a), "f"(b) : "memory"); }
__device__ __forceinline__ void bulk_load(uint32_t dst, const void* src, uint32_t bytes, uint32_t bar) {
  asm volatile("cp.async.bulk.shared::cluster.global.mbarrier::complete_tx::bytes [%0], [%1], %2, [%3];" :: "r"(dst), "l"(src), "r"(bytes), "r"(bar) : "memory");
}
__device__ __forceinline__ void bulk_prefetch(const void* src, uint32_t bytes) {
  asm volatile("cp.async.bulk.prefetch.L2.global [%0], %1;" :: "l"(src), "r"(bytes) : "memory");
}
__device__ __forceinline__ void tma_store_2d(const CUtensorMap* tm, uint32_t src, int c0, int c1) {
  asm volatile("cp.async.bulk.tensor.2d.global.shared::cta.bulk_group [%0, {%2, %3}], [%1];" :: "l"(tm), "r"(src), "r"(c0), "r"(c1) : "memory");
}
__device__ __forceinline__ void bulk_store(void* dst, uint32_t src, uint32_t bytes) {
  asm volatile("cp.async.bulk.global.shared::cta.bulk_group [%0], [%1], %2;" :: "l"(dst), "r"(src), "r"(bytes) : "memory");
}
__device__ __forceinline__ void bulk_reduce_f32(void* dst, uint32_t src, uint32_t bytes) {
  asm volatile("cp.reduce.async.bulk.global.shared::cta.bulk_group.add.f32 [%0], [%1], %2;" :: "l"(dst), "r"(src), "r"(bytes) : "memory");
}
__device__ __forceinline__ void tma_load_3d(uint32_t dst, const CUtensorMap* tm, int c0, int c1, int c2, uint32_t bar) {
  asm volatile("cp.async.bulk.tensor.3d.shared::cluster.global.mbarrier::complete_tx::bytes [%0], [%1, {%3, %4, %5}], [%2];"
    :: "r"(dst), "l"(tm), "r"(bar), "r"(c0), "r"(c1), "r"(c2) : "memory");
}
__device__ __forceinline__ void cp_async16(uint32_t dst, const void* src) { asm volatile("cp.async.cg.shared.global [%0], [%1], 16;" :: "r"(dst), "l"(src) : "memory"); }
__device__ __forceinline__ void cp_async_commit() { asm volatile("cp.async.commit_group;" ::: "memory"); }
template <int N> __device__ __forceinline__ void cp_async_wait() { asm volatile("cp.async.wait_group %0;" :: "n"(N) : "memory"); }
__device__ __forceinline__ void prefetch_map(const CUtensorMap* tm) { asm volatile("prefetch.tensormap [%0];" :: "l"(tm) : "memory"); }
__device__ __forceinline__ void bulk_commit() { asm volatile("cp.async.bulk.commit_group;" ::: "memory"); }
__device__ __forceinline__ void bulk_wait0() { asm volatile("cp.async.bulk.wait_group 0;" ::: "memory"); }
__device__ __forceinline__ void bulk_wait0_read() { asm volatile("cp.async.bulk.wait_group.read 0;" ::: "memory"); }
__device__ __forceinline__ void mma16816(float& d0, float& d1, float& d2, float& d3, uint32_t a0, uint32_t a1, uint32_t a2, uint32_t a3, uint32_t b0, uint32_t b1) {
  asm volatile("mma.sync.aligned.m16n8k16.row.col.f32.bf16.bf16.f32 {%0, %1, %2, %3}, {%4, %5, %6, %7}, {%8, %9}, {%0, %1, %2, %3};"
    : "+f"(d0), "+f"(d1), "+f"(d2), "+f"(d3) : "r"(a0), "r"(a1), "r"(a2), "r"(a3), "r"(b0), "r"(b1));
}
__device__ __forceinline__ uint32_t hmul2(uint32_t a, uint32_t b) { uint32_t r; asm("mul.rn.bf16x2 %0, %1, %2;" : "=r"(r) : "r"(a), "r"(b)); return r; }
__device__ __forceinline__ uint32_t hfma2(uint32_t a, uint32_t b, uint32_t c) { uint32_t r; asm("fma.rn.bf16x2 %0, %1, %2, %3;" : "=r"(r) : "r"(a), "r"(b), "r"(c)); return r; }
__device__ __forceinline__ uint32_t hadd2(uint32_t a, uint32_t b) { uint32_t r; asm("add.rn.bf16x2 %0, %1, %2;" : "=r"(r) : "r"(a), "r"(b)); return r; }
__device__ __forceinline__ float sigmoidf_(float v) { return rcp(1.0f + ex2(v * -1.4426950408889634f)); }

__device__ __forceinline__ void hedgehog(const float (&p)[16], uint32_t (&phi)[16]) {
  float mx0 = p[0], mn0 = p[0], mx1 = p[2], mn1 = p[2];
#pragma unroll
  for (int j = 0; j < 4; j++) {
    mx0 = fmaxf(mx0, fmaxf(p[4 * j], p[4 * j + 1])); mn0 = fminf(mn0, fminf(p[4 * j], p[4 * j + 1]));
    mx1 = fmaxf(mx1, fmaxf(p[4 * j + 2], p[4 * j + 3])); mn1 = fminf(mn1, fminf(p[4 * j + 2], p[4 * j + 3]));
  }
#pragma unroll
  for (int o = 1; o <= 2; o <<= 1) {
    mx0 = fmaxf(mx0, __shfl_xor_sync(0xffffffffu, mx0, o)); mn0 = fminf(mn0, __shfl_xor_sync(0xffffffffu, mn0, o));
    mx1 = fmaxf(mx1, __shfl_xor_sync(0xffffffffu, mx1, o)); mn1 = fminf(mn1, __shfl_xor_sync(0xffffffffu, mn1, o));
  }
  float ep[16], en[16];
  float sp0 = 0.f, sn0 = 0.f, sp1 = 0.f, sn1 = 0.f;
#pragma unroll
  for (int j = 0; j < 4; j++) {
#pragma unroll
    for (int c = 0; c < 2; c++) {
      ep[4 * j + c] = ex2(p[4 * j + c] - mx0); en[4 * j + c] = ex2(mn0 - p[4 * j + c]);
      ep[4 * j + 2 + c] = ex2(p[4 * j + 2 + c] - mx1); en[4 * j + 2 + c] = ex2(mn1 - p[4 * j + 2 + c]);
      sp0 += ep[4 * j + c]; sn0 += en[4 * j + c]; sp1 += ep[4 * j + 2 + c]; sn1 += en[4 * j + 2 + c];
    }
  }
#pragma unroll
  for (int o = 1; o <= 2; o <<= 1) {
    sp0 += __shfl_xor_sync(0xffffffffu, sp0, o); sn0 += __shfl_xor_sync(0xffffffffu, sn0, o);
    sp1 += __shfl_xor_sync(0xffffffffu, sp1, o); sn1 += __shfl_xor_sync(0xffffffffu, sn1, o);
  }
  sp0 = rcp(sp0); sn0 = rcp(sn0); sp1 = rcp(sp1); sn1 = rcp(sn1);
#pragma unroll
  for (int j = 0; j < 4; j++) {
    phi[2 * j] = pack_bf16(ep[4 * j] * sp0, ep[4 * j + 1] * sp0);
    phi[2 * j + 1] = pack_bf16(ep[4 * j + 2] * sp1, ep[4 * j + 3] * sp1);
    phi[8 + 2 * j] = pack_bf16(en[4 * j + 1] * sn0, en[4 * j] * sn0);
    phi[8 + 2 * j + 1] = pack_bf16(en[4 * j + 3] * sn1, en[4 * j + 2] * sn1);
  }
}

__device__ __noinline__ void hedgehog_slow(float* buf, int n) {
#pragma unroll 1
  for (int u = 0; u < n; u++) {
    float p[16]; uint32_t phi[16];
#pragma unroll
    for (int i = 0; i < 16; i++) p[i] = buf[u * 16 + i];
    hedgehog(p, phi);
#pragma unroll
    for (int i = 0; i < 16; i++) buf[u * 16 + i] = __uint_as_float(phi[i]);
  }
}

__device__ __forceinline__ void store_phi_k(const uint32_t (&phi)[16], uint32_t a) {
#pragma unroll
  for (int jj = 0; jj < 4; jj++) stsm4(a ^ (jj << 5), phi[4 * jj], phi[4 * jj + 1], phi[4 * jj + 2], phi[4 * jj + 3]);
}
__device__ __forceinline__ void hand_over_smem(uint32_t bar, bool ok) {
  fence_async_smem();
  __syncwarp();
  if (elect_one() & ok) mbar_arrive(bar);
}
__device__ __noinline__ void redo_phi_k(float* buf, unsigned done, uint32_t pa, uint32_t bar) {
  hedgehog_slow(buf, 4);
#pragma unroll 1
  for (int u = 0; u < 4; u++) {
    if ((done >> u) & 1) continue;
    uint32_t phi[16];
#pragma unroll
    for (int i = 0; i < 16; i++) phi[i] = __float_as_uint(buf[u * 16 + i]);
    store_phi_k(phi, pa + (~u & 1) * 32768 + (u >> 1) * 4096);
    if (u >= 2) hand_over_smem(bar + (u - 2) * 8, true);
  }
}

__device__ __forceinline__ uint32_t dup_lo(uint32_t v) { uint32_t r; asm("{\n.reg .b16 l, h;\nmov.b32 {l, h}, %1;\nmov.b32 %0, {l, l};\n}" : "=r"(r) : "r"(v)); return r; }
__device__ __forceinline__ uint32_t dup_hi(uint32_t v) { uint32_t r; asm("{\n.reg .b16 l, h;\nmov.b32 {l, h}, %1;\nmov.b32 %0, {h, h};\n}" : "=r"(r) : "r"(v)); return r; }
struct HState { uint32_t a[16]; float s[5]; };
__device__ __forceinline__ void hedgehog_fast1(const float (&p)[16], HState& a) {
  float sm[8], m[8], r[8];
#pragma unroll
  for (int i = 0; i < 8; i++) {
    const float t0 = ex2(p[2 * i]), t1 = ex2(p[2 * i + 1]);
    a.a[i] = pack_bf16(t0, t1); sm[i] = t0 + t1; m[i] = t0 * t1;
  }
  float mq[4];
#pragma unroll
  for (int i = 0; i < 4; i++) {
    mq[i] = m[2 * i] * m[2 * i + 1];
    const float R = rcp(mq[i]);
    r[2 * i] = R * m[2 * i + 1]; r[2 * i + 1] = R * m[2 * i];
  }
  a.s[4] = (mq[0] + mq[1]) + (mq[2] + mq[3]);
#pragma unroll
  for (int i = 0; i < 4; i++) {
    const uint32_t rr = pack_bf16(r[2 * i], r[2 * i + 1]);
    a.a[8 + 2 * i] = hmul2(a.a[2 * i], dup_lo(rr)); a.a[9 + 2 * i] = hmul2(a.a[2 * i + 1], dup_hi(rr));
  }
#pragma unroll
  for (int c = 0; c < 2; c++) {
    a.s[2 * c] = (sm[c] + sm[2 + c]) + (sm[4 + c] + sm[6 + c]);
    a.s[2 * c + 1] = fmaf(r[6 + c], sm[6 + c], fmaf(r[4 + c], sm[4 + c], fmaf(r[2 + c], sm[2 + c], r[c] * sm[c])));
  }
}
template <bool NORM>
__device__ __forceinline__ bool hedgehog_fast2(const HState& a, uint32_t (&phi)[16], float& s0, float& s1) {
  float s[4] = {a.s[0], a.s[1], a.s[2], a.s[3]};
#pragma unroll
  for (int o = 1; o <= 2; o <<= 1)
#pragma unroll
    for (int i = 0; i < 4; i++) s[i] += __shfl_xor_sync(0xffffffffu, s[i], o);
  const bool ok = ((s[0] + s[1]) + (s[2] + s[3]) <= 7.2e16f) & (a.s[4] <= 1.3e36f);
  if (NORM) {
    const float R0 = rcp(s[0] * s[1]), R1 = rcp(s[2] * s[3]);
    const uint32_t n0 = pack_bf16(R0 * s[1], R0 * s[0]), n1 = pack_bf16(R1 * s[3], R1 * s[2]);
#pragma unroll
    for (int i = 0; i < 8; i++) { phi[i] = hmul2(a.a[i], dup_lo((i & 1) ? n1 : n0)); phi[8 + i] = hmul2(a.a[8 + i], dup_hi((i & 1) ? n1 : n0)); }
  } else {
    const uint32_t n = pack_bf16(s[0] * rcp(s[1]), s[2] * rcp(s[3]));
    s0 = s[0]; s1 = s[2];
#pragma unroll
    for (int i = 0; i < 8; i++) { phi[i] = a.a[i]; phi[8 + i] = hmul2(a.a[8 + i], (i & 1) ? dup_hi(n) : dup_lo(n)); }
  }
  return ok;
}
template <bool NORM>
__device__ __forceinline__ bool hedgehog_fast(const float (&p)[16], uint32_t (&phi)[16], float& s0, float& s1) {
  HState a;
  hedgehog_fast1(p, a);
  return hedgehog_fast2<NORM>(a, phi, s0, s1);
}

template <int OFF>
__device__ __forceinline__ void pack_frags(const float (&acc)[96], uint32_t (&a)[16]) {
#pragma unroll
  for (int i = 0; i < 16; i++) a[i] = pack_bf16(acc[OFF + 2 * i], acc[OFF + 2 * i + 1]);
#pragma unroll
  for (int i = 0; i < 16; i++) asm volatile("" : "+r"(a[i]) :: "memory");
}
__device__ __forceinline__ void issue_feat(const uint32_t (&a)[16], float (&p0)[16], float (&p1)[16], uint32_t wphi) {
  wgmma_fence();
#pragma unroll
  for (int kk = 0; kk < 2; kk++) {
    wgmma_rs_n32<1, H64>(p0, a[4 * kk], a[4 * kk + 1], a[4 * kk + 2], a[4 * kk + 3], dlo(wphi + kk * 1024, 16), kk);
    wgmma_rs_n32<1, H64>(p1, a[8 + 4 * kk], a[8 + 4 * kk + 1], a[8 + 4 * kk + 2], a[8 + 4 * kk + 3], dlo(wphi + 2048 + kk * 1024, 16), kk);
  }
  wgmma_commit();
}
__device__ __forceinline__ void keep_alive(const uint32_t (&a)[16]) {
#pragma unroll
  for (int i = 0; i < 16; i++) asm volatile("" :: "r"(a[i]) : "memory");
}

__device__ __forceinline__ void fma8(float (&a)[8], float xv, const uint4& w) {
  a[0] = fmaf(xv, bf_lo(w.x), a[0]); a[1] = fmaf(xv, bf_hi(w.x), a[1]);
  a[2] = fmaf(xv, bf_lo(w.y), a[2]); a[3] = fmaf(xv, bf_hi(w.y), a[3]);
  a[4] = fmaf(xv, bf_lo(w.z), a[4]); a[5] = fmaf(xv, bf_hi(w.z), a[5]);
  a[6] = fmaf(xv, bf_lo(w.w), a[6]); a[7] = fmaf(xv, bf_hi(w.w), a[7]);
}

template <int J0, int J1>
__device__ __forceinline__ void stage_out(const float (&acc)[64], uint32_t xa) {
#pragma unroll
  for (int jj = J0; jj < J1; jj++)
    stsm4((xa ^ ((jj & 3) << 5)) + (jj >> 2) * 16384, pack_bf16(acc[8 * jj], acc[8 * jj + 1]), pack_bf16(acc[8 * jj + 2], acc[8 * jj + 3]),
          pack_bf16(acc[8 * jj + 4], acc[8 * jj + 5]), pack_bf16(acc[8 * jj + 6], acc[8 * jj + 7]));
}
__device__ __forceinline__ float lds_bf16(uint32_t addr) {
  unsigned short v; asm volatile("ld.shared.u16 %0, [%1];" : "=h"(v) : "r"(addr) : "memory"); return __uint_as_float((uint32_t)v << 16);
}
__device__ __noinline__ void redo_rows(const __nv_bfloat16* pieces, const __nv_bfloat16* wo_cols, const unsigned* done, const __nv_bfloat16* xrows,
                                       uint32_t xa, int wi, uint32_t gate, int routed, uint32_t upd) {
  const int lane = threadIdx.x & 31;
  int it = 0;
  while (!__all_sync(0xffffffffu, ld_acquire(done + (lane & 15)) != 0)) { if (++it > (1 << 20)) __trap(); }
  float acc[64];
  const int g = lane >> 2, q = lane & 3, r0 = wi * 16 + g;
#pragma unroll
  for (int i = 0; i < 32; i++) {
    const int r = g + (i & 1) * 8, c = (i >> 1) * 8 + q * 2;
    uint32_t v = *reinterpret_cast<const uint32_t*>(xrows + (size_t)r * D_ + c);
    if (r == routed) v = hadd2(v, lds_u32(upd + c * 2));
    const float og = round_bf16(1.0f - lds_bf16(gate + r * 2));
    acc[2 * i] = og * bf_lo(v); acc[2 * i + 1] = og * bf_hi(v);
  }
#pragma unroll 1
  for (int ks = 0; ks < 64; ks++) {
    const unsigned* pc = reinterpret_cast<const unsigned*>(pieces + (ks >> 2) * 4096) + r0 * 32 + q;
    const int c0 = ((2 * (ks & 3)) ^ (r0 & 7)) * 4, c1 = ((2 * (ks & 3) + 1) ^ (r0 & 7)) * 4;
    const uint32_t a0 = ld_relaxed(pc + c0), a1 = ld_relaxed(pc + 256 + c0), a2 = ld_relaxed(pc + c1), a3 = ld_relaxed(pc + 256 + c1);
    const unsigned short* wp = reinterpret_cast<const unsigned short*>(wo_cols) + (size_t)(ks * 16 + 2 * q) * D_ + g;
#pragma unroll
    for (int nb = 0; nb < 16; nb++) {
      const uint32_t b0 = wp[nb * 8] | ((uint32_t)wp[nb * 8 + D_] << 16), b1 = wp[nb * 8 + 8 * D_] | ((uint32_t)wp[nb * 8 + 9 * D_] << 16);
      mma16816(acc[4 * nb], acc[4 * nb + 1], acc[4 * nb + 2], acc[4 * nb + 3], a0, a1, a2, a3, b0, b1);
    }
  }
  __syncwarp();
  stage_out<0, 8>(acc, xa);
}

__global__ void __cluster_dims__(2, 1, 1) __launch_bounds__(512, 1)
fused_kernel(const __grid_constant__ Maps maps, const __nv_bfloat16* __restrict__ x,
             const __nv_bfloat16* __restrict__ wo, const __nv_bfloat16* __restrict__ w_r, const __nv_bfloat16* __restrict__ gate_w) {
  extern __shared__ __align__(1024) uint8_t smem_raw[];
  if (threadIdx.x == 0) { prefetch_map(&maps.w); prefetch_map(&maps.x); }
  const int tid = threadIdx.x, warp = __shfl_sync(0xffffffffu, tid >> 5, 0), lane = tid & 31;
  const int rank = blockIdx.x & 1;
  const unsigned cl = blockIdx.x >> 1, hi = (cl - 36) * 37 >> 8, lo7 = cl - 36 - hi * 7;
  const bool r8 = cl < 36;
  const unsigned c4 = cl - 4, col = cl < 4 ? 15 : r8 ? c4 & 7 : 8 + lo7, pos = cl < 4 ? cl : r8 ? c4 >> 3 : hi;
  const int b = ((unsigned)(COLMAP >> (4 * col)) & 15) * 8 + pos * 2 + rank;
  const int e = blockIdx.x;
  const int tg = b >> 4, hp = b & 15;
  const int half = hp >> 3, ct = hp & 7;
  constexpr uint32_t SB0 = 1024;
  const uint32_t sb = SB0 + ((uint32_t)rank << 24);
  auto BAR = [&](int i) { return sb + SM_BAR + 8 * i; };
  auto load_stage = [&](int kt, int s, bool mc) {
    const uint32_t a = sb + SM_RA + s * A_BYTES, full = BAR(B_FULL + s);
    mbar_expect_tx(full, STAGE_BYTES);
    tma_load_3d(sb + SM_RB + s * B_BYTES, &maps.w, hp * 64, kt * 32, 0, full);
    if (mc) tma_load_2d_mc(a + rank * 8192, &maps.x, kt * 32, tg * 256 + rank * 128, full);
    else { tma_load_2d(a, &maps.x, kt * 32, tg * 256, full); tma_load_2d(a + 8192, &maps.x, kt * 32, tg * 256 + 128, full); }
  };
  auto slice_of = [&](int i) { return (i < 2 ? ct ^ i : i < 8 ? i - 2 * (i - 2 < (ct & 6)) : i) ^ (half * 8); };
  auto load_b2 = [&](int i) {
    const int j = slice_of(i), sl = i + 4 - (i >= 3) * NB2 - (i >= 10) * NB2;
    mbar_expect_tx(BAR(B_FB2 + i), 16384);
    tma_load_3d(sb + SM_RB + sl * 16384, &maps.wo, 0, j * 64, ct * 2, BAR(B_FB2 + i));
  };
  auto load_xt = [&](int w) {
    mbar_expect_tx(BAR(B_XT + w), 16384);
    tma_load_2d(sb + SM_XT + w * 8192, &maps.xt, ct * 128, tg * 256 + half * 128 + w * 64, BAR(B_XT + w));
    tma_load_2d(sb + SM_XT + w * 8192 + 16384, &maps.xt, ct * 128 + 64, tg * 256 + half * 128 + w * 64, BAR(B_XT + w));
  };
  auto o_piece = [&](int hf, int mb, int j) { return g_o + (size_t)((((tg * 2 + hf) * 2 + mb) * 16 + j) * 4096); };

  if (blockIdx.x >= NCTA) {
    if (warp == 0 && blockIdx.x == NCTA) {
      const unsigned tag = (ld_relaxed(&g_bcast[0].y) + 1) & 0xfffu;
      unsigned val = 0;
#pragma unroll 1
      for (int round = 0; round < 2; round++) {
        const unsigned* arr = (round ? g_ready : g_key) + lane * 4;
        unsigned k[16], bad;
        int it = 0;
        do {
          bad = 0;
#pragma unroll
          for (int a = 0; a < 4; a++)
            asm volatile("ld.relaxed.gpu.global.v4.u32 {%0, %1, %2, %3}, [%4];" : "=r"(k[4 * a]), "=r"(k[4 * a + 1]), "=r"(k[4 * a + 2]), "=r"(k[4 * a + 3])
                         : "l"(arr + (round ? 0 : a * NCTA)) : "memory");
#pragma unroll
          for (int i = 0; i < 16; i++) bad |= k[i] ^ tag;
          if (++it > (1 << 20)) __trap();
        } while (!__all_sync(0xffffffffu, (bad & 0xfffu) == 0));
        if (round == 0) {
#pragma unroll
          for (int c = 0; c < 4; c++) {
            const unsigned m = max(max(k[c], k[4 + c]), max(k[8 + c], k[12 + c]));
            val = max(val, (m & 0xffff0000u) | ((127u - (lane * 4 + c)) << 4) | ((m >> 12) & 15u));
          }
          val = __reduce_max_sync(0xffffffffu, val);
        }
        if (lane < 8) st_relaxed2(g_bcast + round * 128 + lane * 16, val, tag);
        const uint32_t* xr = reinterpret_cast<const uint32_t*>(x + (size_t)(2047u - (val & 0x7ffu)) * D_);
        float l = 0.f;
#pragma unroll 4
        for (int i = lane; i < 512; i += 32) {
          const uint32_t pr = hmul2(__ldg(xr + i), __ldg(reinterpret_cast<const uint32_t*>(gate_w) + i));
          l += bf_lo(pr) + bf_hi(pr);
        }
#pragma unroll
        for (int o = 1; o <= 16; o <<= 1) l += __shfl_xor_sync(0xffffffffu, l, o);
        val = __float_as_uint(round_bf16(sigmoidf_(round_bf16(l)))) >> 16;
      }
    }
    return;
  }
  if (warp == 8) {
    if (elect_one()) {
      mbar_init(BAR(0), 1);
      if (NPRE > 1) { mbar_init(BAR(1), 1); mbar_init(BAR(2), 1); }
      if (NPRE > 0 && INIT_FENCE) fence_async_smem();
      TSTAMP(40);
      if (NPRE > 0) load_stage(0, 0, false);
      if (NPRE > 1) load_stage(1, 1, false);
      if (NPRE > 2) load_stage(2, 2, false);
      TSTAMP(41);
    }
  } else if (elect_one()) {
    const int i = 3 + warp - (warp > 8);
    mbar_init(BAR(i), i < B_EMPTY ? 1 : 4);
    if (NPRE < 2 && warp >= 14) mbar_init(BAR(warp - 13), 1);
    if (warp == 13) mbar_init(BAR(B_INIT), 3);
  }
  asm volatile("fence.mbarrier_init.release.cluster;" ::: "memory");
  __syncwarp();
  asm volatile("barrier.cluster.arrive.relaxed.aligned;" ::: "memory");
  auto cluster_wait = [&]() { asm volatile("barrier.cluster.wait.aligned;" ::: "memory"); };

  if (warp >= 12) {
    asm volatile("setmaxnreg.dec.sync.aligned.u32 40;");
    const int aw = warp - 12;
    cluster_wait();
    const unsigned old_key = ld_relaxed(g_key + aw * NCTA + b);
    const uint32_t zero = smem_u32(smem_raw) ^ sb;
    {
      float r[4], l[4];
#pragma unroll
      for (int t = 0; t < 4; t++) { r[t] = 0.f; l[t] = 0.f; }
      uint32_t xa = sb + SM_XR + aw * 1024 + lane * 8, wa = sb + SM_XR + 32768 + lane * 8;
#pragma unroll 1
      for (int i = 0; i < 8; i++) {
        if (!(i & 1)) mbar_wait(BAR(B_XR) + i * 4, 0);
        if (tid == 384 && i == 6) TSTAMP(30);
        uint2 wr = lds64(wa);
        const uint2 gw = lds64(wa + 2048);
        uint2 xv[4];
#pragma unroll
        for (int t = 0; t < 4; t++) xv[t] = lds64(xa + t * 256);
        xa += 4096; wa += 256;
        wr.x |= (xv[1].x | xv[2].x | xv[3].x) & zero;
#pragma unroll
        for (int t = 0; t < 4; t++) { r[t] = fmaf(bf_lo(xv[t].x), bf_lo(wr.x), r[t]); l[t] = fmaf(bf_lo(xv[t].x), bf_lo(gw.x), l[t]); }
#pragma unroll
        for (int t = 0; t < 4; t++) { r[t] = fmaf(bf_hi(xv[t].x), bf_hi(wr.x), r[t]); l[t] = fmaf(bf_hi(xv[t].x), bf_hi(gw.x), l[t]); }
#pragma unroll
        for (int t = 0; t < 4; t++) { r[t] = fmaf(bf_lo(xv[t].y), bf_lo(wr.y), r[t]); l[t] = fmaf(bf_lo(xv[t].y), bf_lo(gw.y), l[t]); }
#pragma unroll
        for (int t = 0; t < 4; t++) { r[t] = fmaf(bf_hi(xv[t].y), bf_hi(wr.y), r[t]); l[t] = fmaf(bf_hi(xv[t].y), bf_hi(gw.y), l[t]); }
      }
      float u[4];
#pragma unroll
      for (int t = 0; t < 4; t++) u[t] = ((lane & 4) ? l[t] : r[t]) + __shfl_xor_sync(0xffffffffu, (lane & 4) ? r[t] : l[t], 4);
      const float v0 = ((lane & 1) ? u[1] : u[0]) + __shfl_xor_sync(0xffffffffu, (lane & 1) ? u[0] : u[1], 1);
      const float v1 = ((lane & 1) ? u[3] : u[2]) + __shfl_xor_sync(0xffffffffu, (lane & 1) ? u[2] : u[3], 1);
      float v = ((lane & 2) ? v1 : v0) + __shfl_xor_sync(0xffffffffu, (lane & 2) ? v0 : v1, 2);
      v += __shfl_xor_sync(0xffffffffu, v, 8);
      v += __shfl_xor_sync(0xffffffffu, v, 16);
      v = round_bf16(v);
      unsigned k = __float_as_uint(v) >> 16;
      k = (k & 0x8000u) ? (~k & 0xffffu) : (k | 0x8000u);
      k = __reduce_max_sync(0xffffffffu, lane < 4 ? (k << 4) | (15u - (aw * 4 + lane)) : 0u);
      mbar_wait(BAR(B_INIT), 0);
      const unsigned tag = (old_key + 1) & 0xfffu;
      if (lane == 0) st_relaxed(g_key + aw * NCTA + b, (k << 12) | tag);
      if ((lane >> 2) == 1) st_relaxed(g_gate + b * 16 + aw * 4 + (lane & 3), __float_as_uint(round_bf16(sigmoidf_(v))) | tag);
    }
    if (tid == 384) { TSTAMP(31); GSTAMP(60); }
    fence_async_smem();
    __syncwarp();
    if (elect_one()) mbar_arrive(BAR(B_XRD));
    mbar_wait_bounded(BAR(B_XSEL), 0);
    if (tid == 384) TSTAMP(36);
    float ag[8];
#pragma unroll
    for (int i = 0; i < 8; i++) ag[i] = 0.f;
    if (e < NMOE) {
      const uint32_t lw = sb + SM_MOE + aw * 2048 + (lane >> 3) * 512 + (lane & 7) * 16;
      uint32_t lx = sb + SM_XSEL + aw * 32 + (lane >> 3) * 8, fb = BAR(B_MOE), wa = lw;
      bool got = false;
#pragma unroll 1
      for (int m = 0; m < 12; m++) {
#pragma unroll
        for (int c = 0; c < 2; c++) {
          if (!got) mbar_wait(fb + c * 8, (m >> 1) & 1);
          uint4 w0, w1, w2, w3;
          lds128x4(wa + c * 8192, w0, w1, w2, w3);
          uint2 xv = lds64(lx + c * 128);
          got = mbar_test(c ? fb ^ 16 : fb + 8, ((m + c) >> 1) & 1);
          const uint32_t dep = ((w0.x | w1.x | w2.x) | w3.x) & zero;
          xv.x |= dep;
          if (elect_one()) mbar_arrive(fb + dep + (B_MOEE - B_MOE + c) * 8);
          fma8(ag, bf_lo(xv.x), w0); fma8(ag, bf_hi(xv.x), w1); fma8(ag, bf_lo(xv.y), w2); fma8(ag, bf_hi(xv.y), w3);
        }
        fb ^= 16; wa = 2 * lw + 16384 - wa; lx += 256;
        if (m == 7) {
          int ln;
          asm volatile("mov.u32 %0, %%laneid;" : "=r"(ln));
#pragma unroll
          for (int i = 0; i < 4; i++) ag[i] = ((ln & 16) ? ag[4 + i] : ag[i]) + __shfl_xor_sync(0xffffffffu, (ln & 16) ? ag[i] : ag[4 + i], 16);
          const float v0 = ((ln & 8) ? ag[2] : ag[0]) + __shfl_xor_sync(0xffffffffu, (ln & 8) ? ag[0] : ag[2], 8);
          const float v1 = ((ln & 8) ? ag[3] : ag[1]) + __shfl_xor_sync(0xffffffffu, (ln & 8) ? ag[1] : ag[3], 8);
          const uint32_t own = (uint32_t)(ln & 4) << 22;
          asm volatile("st.async.shared::cluster.mbarrier::complete_tx::bytes.v2.f32 [%0], {%1, %2}, [%3];"
                       :: "r"(own + SB0 + SM_RED + rank * 512 + aw * 128 + (ln & 3) * 32 + (ln >> 3) * 8), "f"(v0), "f"(v1), "r"(own + SB0 + SM_BAR + 8 * B_H) : "memory");
          if (tid == 384) TSTAMP(39);
          mbar_wait_bounded(BAR(B_H), 0);
          const uint32_t ra = sb + SM_RED + ln * 4;
          float gv = round_bf16((lds_f32(ra) + lds_f32(ra + 128)) + (lds_f32(ra + 256) + lds_f32(ra + 384)));
          const float uv = round_bf16((lds_f32(ra + 512) + lds_f32(ra + 640)) + (lds_f32(ra + 768) + lds_f32(ra + 896)));
          gv = round_bf16(gv * sigmoidf_(gv));
          lx = sb + SM_XSEL + aw * 32;
          asm volatile("st.shared.b16 [%0], %1;" :: "r"(lx + (ln >> 2) * 128 + (ln & 3) * 2), "h"(__bfloat16_as_ushort(__float2bfloat16_rn(gv * uv))) : "memory");
          __syncwarp();
#pragma unroll
          for (int i = 0; i < 8; i++) ag[i] = 0.f;
          if (tid == 384) TSTAMP(33);
        }
      }
      mbar_wait(BAR(B_RDY), 0);
#pragma unroll
      for (int j = 0; j < 3; j++)
        asm volatile("red.global.add.v4.f32 [%0], {%1, %2, %3, %4};" :: "l"(g_z.y + (e & (NY - 1)) * 2 * D_ + (j * 128 + aw * 32 + lane) * 4),
                     "f"(ag[3 * j]), "f"(ag[3 * j + 1]), "f"(j < 2 ? ag[3 * j + 2] : 0.f), "f"(1.0f) : "memory");
    }
    fence_async_smem();
    if (tid == 384) TSTAMP(34);
    bar_sync(4, 128);
    if (aw < 3) {
      if (aw == 0) mbar_wait(BAR(B_PHI), 0);
      if (elect_one()) load_b2(aw);
      if (aw) {
#pragma unroll 1
        for (int i = 0; i < 16; i++) {
          mbar_wait_bounded(BAR(B_FB2 + i), 0);
          if (i == 0) mbar_wait(BAR(B_OP + half * 2 + aw - 1), 0);
          if (elect_one()) mbar_expect_tx(BAR(B_F2 + (aw - 1) * 16 + i), i ? 8192 : 0);
        }
      }
    } else {
      const uint4 info = lds128(sb + SM_INFO);
      int it = 0;
      if ((info.y >> 7) == tg * 2 + half) {
        mbar_wait(BAR(B_RDY), 0);
        const float rs = round_bf16(sigmoidf_(__uint_as_float(info.z)));
        float y[9];
        do {
          __nanosleep(100);
#pragma unroll
          for (int i = 0; i < 9; i++) y[i] = 0.f;
#pragma unroll 1
          for (int c = lane >> 4; c < NY; c += 2) {
            const float* yp = g_z.y + c * 2 * D_ + (ct * 16 + (lane & 15)) * 4;
            const float4 a0 = ldg_l2(yp), a1 = ldg_l2(yp + 512), a2 = ldg_l2(yp + 1024);
            y[0] += a0.x; y[1] += a0.y; y[2] += a0.z; y[3] += a1.x; y[4] += a1.y; y[5] += a1.z; y[6] += a2.x; y[7] += a2.y;
            y[8] += a0.w + a1.w + a2.w;
          }
#pragma unroll
          for (int i = 0; i < 9; i++) y[i] += __shfl_xor_sync(0xffffffffu, y[i], 16);
          if (++it > (1 << 20)) __trap();
        } while (!__all_sync(0xffffffffu, y[8] == 3.f * NMOE));
        const int w = (info.y >> 6) & 1, r = info.y & 63;
        mbar_wait(BAR(B_XT + w), 0);
        if (lane < 16) {
          const uint32_t ad = sb + SM_XT + w * 8192 + (lane >> 3) * 16384 + r * 128 + (((lane & 7) ^ (r & 7)) << 4), rs2 = pack_bf16(rs, rs);
          const uint4 xv = lds128(ad);
          const uint4 u = make_uint4(hmul2(pack_bf16(y[0], y[1]), rs2), hmul2(pack_bf16(y[2], y[3]), rs2), hmul2(pack_bf16(y[4], y[5]), rs2), hmul2(pack_bf16(y[6], y[7]), rs2));
          sts128(sb + SM_UPD + lane * 16, u);
          sts128(ad, make_uint4(hadd2(xv.x, u.x), hadd2(xv.y, u.y), hadd2(xv.z, u.z), hadd2(xv.w, u.w)));
        }
        asm volatile("fence.acq_rel.cta;" ::: "memory");
        __syncwarp();
        if (elect_one()) mbar_arrive(BAR(B_Y));
      }
    }
  } else if (warp >= 8) {
    asm volatile("setmaxnreg.dec.sync.aligned.u32 24;");
    cluster_wait();
    if (tid == 256) TSTAMP(58);
    if (warp != 8) {
      if (elect_one()) {
        if (smem_u32(smem_raw) != sb) __trap();
#pragma unroll 1
        for (int i = B_ST + warp - 9; i < NBAR; i += 3) mbar_init(BAR(i), bar_count(i));
        asm volatile("fence.mbarrier_init.release.cluster;" ::: "memory");
      }
#pragma unroll
      for (int i = 0; i < (ZB + 1535) / 1536; i++) sts128(sb + SM_KVB + (i * 96 + tid - 288) * 16, make_uint4(0, 0, 0, 0));
      if (warp < 11) sts128(sb + SM_ONES + (tid - 288) * 16, make_uint4(0x3f803f80u, 0x3f803f80u, 0x3f803f80u, 0x3f803f80u));
      hand_over_smem(BAR(B_INIT), true);
      if (tid == 288) TSTAMP(57);
    }
    if (warp == 8) {
      int s = NPRE, ph = 1;
#pragma unroll 1
      for (int kt = NPRE; kt < KT; kt++) {
        mbar_wait_bounded(BAR(B_EMPTY + s), ph);
        if (elect_one()) {
          load_stage(kt, s, true);
          const unsigned xc = kt - XR_AFTER;
          if (xc < 4) {
            mbar_expect_tx(BAR(B_XR + xc), xc ? 8192 : 12288);
            tma_load_2d(sb + SM_XR + xc * 8192, &maps.xr, xc * 256, b * 16, BAR(B_XR + xc));
            tma_load_2d(sb + SM_XR + xc * 8192 + 4096, &maps.xr, xc * 256 + 128, b * 16, BAR(B_XR + xc));
            if (xc == 0) { bulk_load(sb + SM_XR + 32768, w_r, 2048, BAR(B_XR)); bulk_load(sb + SM_XR + 34816, gate_w, 2048, BAR(B_XR)); }
          }
          const int pg = kt - STAGES - PF_START + PF_OFF;
          if (pg >= (e < NMOE ? PF_OFF : 24) && pg < 26 && (EXPT != 3 || pg >= 24)) {
            const CUtensorMap* tm = &maps.tg + (pg < 16 ? (b & 1) : pg < 24 ? 2 : 3);
            const int c0 = pg < 16 ? (e >> 1) * 64 : 0, c1 = (pg < 16 ? pg : pg < 24 ? e * 8 + pg - 16 : b * 2 + pg - 24) * 64;
            asm volatile("cp.async.bulk.prefetch.tensor.2d.L2.global [%0, {%1, %2}];" :: "l"(tm), "r"(c0), "r"(c1) : "memory");
          }
        }
        if (++s == STAGES) { s = 0; ph ^= 1; }
      }
      mbar_wait(BAR(B_EMPTY + 1), 1);
#pragma unroll 1
      for (int i = 3; i < (XT_IN_A ? NB2 : 5); i++)
        if (elect_one()) { if (!XT_IN_A) load_xt(i - 3); load_b2(i); }
    } else if (warp == 9) {
      const unsigned tag = (ld_relaxed(g_ready + b) + 1) & 0xfffu;
      if (elect_one()) {
        mbar_expect_tx(BAR(B_WPHI), 4096);
        tma_load_2d(sb + SM_WPHI, &maps.wphi, 0, hp * 64, BAR(B_WPHI));
      }
      mbar_wait(BAR(B_WPHI), 0);
#pragma unroll 1
      for (uint32_t ad = sb + SM_WPHI + lane * 16; ad < sb + SM_WPHI + 4096; ad += 512) {
        constexpr float L = 1.4426950408889634f;
        const uint4 w = lds128(ad);
        sts128(ad, make_uint4(pack_bf16(bf_lo(w.x) * L, bf_hi(w.x) * L), pack_bf16(bf_lo(w.y) * L, bf_hi(w.y) * L),
                              pack_bf16(bf_lo(w.z) * L, bf_hi(w.z) * L), pack_bf16(bf_lo(w.w) * L, bf_hi(w.w) * L)));
      }
      fence_async_smem();
      mbar_wait(BAR(B_XRD), 0);
      const unsigned best = __shfl_sync(0xffffffffu, wait_tagged<KEY_SLEEP>(g_bcast + tg * 16, tag), 0);
      const unsigned idx = 2047u - (best & 0x7ffu);
      unsigned u = best >> 16;
      u = (u & 0x8000u) ? (u & 0x7fffu) : (~u & 0xffffu);
      if (elect_one()) {
        sts128(sb + SM_INFO, make_uint4(tag, idx, u << 16, 0));
        mbar_expect_tx(BAR(B_H), 1024);
        mbar_expect_tx(BAR(B_XSEL), 2048);
        bulk_load(sb + SM_XSEL, x + (size_t)idx * D_, 2048, BAR(B_XSEL));
        TSTAMP(32); GSTAMP(61);
        bulk_store(reinterpret_cast<char*>(&g_z) + b * ZB, sb + SM_KVB, ZB);
      }
      bulk_commit(); bulk_wait0();
      fence_gpu();
      __syncwarp();
      if (lane == 0) { st_relaxed(g_ready + b, tag); TSTAMP(42); }
      int it = 0;
#pragma unroll 1
      for (int c = 0; c < 2; c++) {
        uint4 gv;
        do {
          asm volatile("ld.relaxed.gpu.global.v4.u32 {%0, %1, %2, %3}, [%4];" : "=r"(gv.x), "=r"(gv.y), "=r"(gv.z), "=r"(gv.w)
                       : "l"(g_gate + tg * 256 + c * 128 + lane * 4) : "memory");
          if (++it > (1 << 20)) __trap();
        } while (!__all_sync(0xffffffffu, (((gv.x ^ tag) | (gv.y ^ tag) | (gv.z ^ tag) | (gv.w ^ tag)) & 0xfffu) == 0));
        sts64(sb + SM_GATE + c * 256 + lane * 8, __uint_as_float(__byte_perm(gv.x, gv.y, 0x7632)), __uint_as_float(__byte_perm(gv.z, gv.w, 0x7632)));
      }
      const unsigned gsel = wait_tagged<200>(g_bcast + 128 + tg * 16, tag);
      if ((idx >> 8) == tg && lane == 0) asm volatile("st.shared.b16 [%0], %1;" :: "r"(sb + SM_GATE + (idx & 255) * 2), "h"((unsigned short)gsel) : "memory");
      __syncwarp();
      if (elect_one()) { mbar_arrive(BAR(B_RDY)); TSTAMP(43); }
    } else if (e < NMOE) {
      const int w = warp & 1;
      const CUtensorMap* tm = &maps.wg + rank;
      int c0 = (e >> 1) * 64, c1 = 0, c2 = 4 * w;
      uint32_t bar = BAR(B_MOE + w);
      mbar_wait(BAR(B_XRD), 0);
#pragma unroll 1
      for (int m = 0; m < 12; m++) {
        mbar_wait(bar + (B_MOEE - B_MOE) * 8, ((m >> 1) & 1) ^ 1);
        if (elect_one()) {
          mbar_expect_tx(bar, 8192);
          tma_load_3d(sb + SM_MOE + w * 8192 + (m & 1) * 16384, tm, c0, c1, c2, bar);
        }
        bar ^= 16;
        if (m < 7) c2 += 8; else c1 += 8;
        if (m == 7) { tm = &maps.wd; c0 = 0; c1 = e * 32 + w * 4; c2 = 0; }
      }
    }
    const int wi = warp - 8, st = tid - 256;
    bar_sync(5, 128);
    asm volatile("setmaxnreg.inc.sync.aligned.u32 " STR(REG_K) ";");
    {
      auto kv_half = [&](float (&d)[20], int h, int mb) {
#pragma unroll
        for (int i = 0; i < 8; i++)
          wgmma_ss_n40<1, 1, H128, H64>(d, dlo(SB0 + SM_PHIK + 32768, 16) - h * 2048 + (((i & 2) << 2) + (i & 4) + mb * 2 + (i & 1)) * 128,
                                        dlo(SB0 + SM_V, SM_ONES - SM_V) + (h * 16 + (i & 4) * 2 + mb * 4 + (i & 3)) * (64 - (64 << 16)), (mb | i) != 0);
      };
      auto kv_out = [&](float (&d)[20], int h) {
        fence_regs(d);
        float* dst = g_z.kv + (hp * 2 + h) * KVH + st * 2;
        const int q = lane & 3;
        uint32_t w[8];
#pragma unroll
        for (int i = 0; i < 8; i++) w[i] = pack_bf16(d[2 * i], d[2 * i + 1]);
#pragma unroll
        for (int c = 0; c < 4; c++)
          asm volatile("red.global.add.noftz.v2.bf16x2 [%0], {%1, %2};" :: "l"(dst + c * 256), "r"(w[2 * c]), "r"(q == c ? 0x3f80u : w[2 * c + 1]) : "memory");
        asm volatile("red.global.add.noftz.v2.bf16x2 [%0], {%1, %2};" :: "l"(dst + 1024), "r"((q & 2) ? ((q & 1) ? w[7] : w[5]) : ((q & 1) ? w[3] : w[1])),
                     "r"(q == 0 ? 0x3f80u : q == 1 ? pack_bf16(d[16], d[18]) : 0u) : "memory");
      };
#pragma unroll 1
      for (int h = 0; h < 2; h++) {
        float kv[20];
        mbar_wait_bounded(BAR(B_PHI + h), 0);
        if (st == 0) TSTAMP(23 + h);
        wgmma_fence();
        kv_half(kv, h, 0); kv_half(kv, h, 1);
        wgmma_commit();
        wgmma_wait<0>();
        if (st == 0) TSTAMP(21 + h);
        kv_out(kv, h);
        bar_sync(5, 128);
        if (XT_IN_A && h == XT_H && wi < 2 && elect_one()) load_xt(wi);
      }
      if (wi == 3 && elect_one()) mbar_arrive_cluster(BAR(B_PEER) ^ (1u << 24));
      if (st == 0) TSTAMP(13);
      const int f = wi * 16 + (lane & 15), sw = (f >> 1) & 3, chi = lane >> 4;
      uint2 v[10];
      const float* src = g_z.kv + hp * 2 * KVH + st * 2;
      const int q = lane & 3;
      { const unsigned c0 = clock32(); while (clock32() - c0 < KV_DELAY) {} }
      int it = 0;
      unsigned need = 0x3ff;
#pragma unroll
      for (int i = 0; i < 10; i++) v[i] = make_uint2(0, 0);
      do {
        if (++it > (1 << 20)) __trap();
        unsigned bad = 0;
        if (st == 0 && it == 1) TSTAMP(35);
#pragma unroll
        for (int i = 0; i < 10; i++)
          asm volatile("{\n.reg .pred p;\nsetp.ne.u32 p, %3, 0;\n@p ld.relaxed.gpu.global.v2.u32 {%0, %1}, [%2];\n}"
                       : "+r"(v[i].x), "+r"(v[i].y) : "l"(src + i * 256), "r"(need & (1u << i)) : "memory");
#pragma unroll
        for (int i = 0; i < 10; i++) bad |= (v[i].y != 0x4100u) << i;
        need = __reduce_or_sync(0xffffffffu, bad & ((0x21u << q) | (q ? 0u : 0x210u)));
        if (st == 0 && it == 1) TSTAMP(20);
      } while (need);
      uint32_t zz[2];
#pragma unroll
      for (int h = 0; h < 2; h++) {
        const uint2* w = v + h * 5;
        const uint32_t kb = sb + SM_KVB + h * 4096 + f * 64;
        zz[h] = __shfl_sync(0xffffffffu, w[4].y, (lane & 28) + 1);
        stsm4(kb + ((chi ^ sw) << 4), w[0].x, q == 0 ? w[4].x : w[0].y, w[1].x, q == 1 ? w[4].x : w[1].y);
        stsm4(kb + (((2 + chi) ^ sw) << 4), w[2].x, q == 2 ? w[4].x : w[2].y, w[3].x, q == 3 ? w[4].x : w[3].y);
      }
      stsm4(sb + SM_KVB + 8192 + f * 64 + ((chi ^ sw) << 4), zz[0], zz[0] >> 16, zz[1], zz[1] >> 16);
      fence_async_smem();
      __syncwarp();
      if (elect_one()) mbar_arrive(BAR(B_KVB));
    }
    {
      const int pm = wi >> 1;
      if (wi & 1) {
        const int hf = half ^ pm;
        mbar_wait(BAR(B_PEER), 0);
        mbar_wait_bounded(BAR(B_OP + hf * 2), 0);
        const unsigned c0 = clock32();
        while (clock32() - c0 < (unsigned)(pm ? LATE_DELAY + ct * LATE_STEP : (ct >> 2) * URG_STEP)) {}
        __syncwarp();
        auto to_partner = [&](int mb) {
          asm volatile("cp.async.bulk.shared::cluster.shared::cta.mbarrier::complete_tx::bytes [%0], [%1], 8192, [%2];"
                       :: "r"((sb ^ (1u << 24)) + SM_RA + mb * 8192), "r"(sb + SM_O + mb * 8192), "r"(BAR(B_F2 + mb * 16 + 1) ^ (1u << 24)) : "memory");
        };
        unsigned* hint = g_z.hint + (tg * 2 + hf) * 32 + hp;
        const int sz = pm ? LATE_SZ : 8192;
#pragma unroll 1
        for (int o = 0; o < 16384; o += sz) {
          const int mb = o >> 13;
          if (o == 8192) mbar_wait(BAR(B_OP + hf * 2 + 1), 0);
          if (elect_one()) bulk_store(reinterpret_cast<char*>(o_piece(hf, mb, hp)) + (o & 8191), sb + SM_O + pm * 16384 + o, sz);
          bulk_commit();
          if (pm == 0 && elect_one()) to_partner(mb);
          if (pm ? HINT_L == 0 : HINT_U == 0) bulk_wait0(); else if (pm ? HINT_L == 1 : HINT_U == 1) bulk_wait0_read();
          __syncwarp();
          if (((o + sz) & 8191) == 0 && lane == 0) { st_relaxed(hint + mb * 16, 1); TSTAMP((pm ? 37 : 15) + mb); }
        }
        bulk_wait0();
        __syncwarp();
        if (lane == 0) mbar_arrive(BAR(B_ST + pm));
        if (pm == 0) {
          if (lane < 2) mbar_arrive_cluster((lane << 24) + SB0 + SM_BAR + 8 * (B_GO + NA2));
          mbar_wait(BAR(B5_AFTER), 0);
#pragma unroll 1
          for (int i = XT_IN_A ? NB2 : 5; i < 16; i++) {
            mbar_wait(i < NB2 ? BAR(B_XTD) : BAR(B_DB + i - NB2), 0);
            if (elect_one()) load_b2(i);
          }
        } else {
          mbar_wait(BAR(B_ST), 0);
          fence_gpu();
          if (lane == 0) st_relaxed(g_z.done + b, 1);
        }
      } else if (pm) {
        const __nv_bfloat16* src = o_piece(half, rank, half * 8);
        uint32_t dst = sb + SM_RA + 16384 + rank * 8192;
        mbar_wait(BAR(B_PEER), 0);
#pragma unroll 1
        for (int i = 2; i < 16; i++) {
          if (i == (ct & 6) + 2) src += 2 * 4096;
          if (i == 8) src -= half * 16 * 4096;
          mbar_wait_bounded(BAR(B_GO + i), 0);
          if (elect_one()) {
            asm volatile("cp.async.bulk.shared::cluster.global.mbarrier::complete_tx::bytes.multicast::cluster [%0], [%1], 8192, [%2], %3;"
                         :: "r"(dst), "l"(src), "r"(BAR(B_F2 + rank * 16 + i)), "h"((uint16_t)3) : "memory");
            if (i == 2) TSTAMP(19);
          }
          src += 4096;
          dst += (i == 5 || i == 10) ? -4 * 16384 : 16384;
        }
      } else {
        const unsigned* flag = g_z.hint + (tg * 2 + half) * 32 + rank * 16 + slice_of(lane & 15);
        bool seen = lane < 2 || lane > 15;
        mbar_wait(BAR(B_OP + half * 2 + rank), 0);
        int it = 0;
        do {
          if (ld_relaxed(flag) != 0 && !seen) {
            mbar_arrive(BAR(B_GO) + lane * 8);
            seen = true;
          }
          if (++it > (1 << 20)) __trap();
        } while (!__all_sync(0xffffffffu, seen));
      }
    }
  } else {
    asm volatile("setmaxnreg.inc.sync.aligned.u32 224;");
    const int wg = warp >> 2, wi = warp & 3;
    cluster_wait();
    if (tid == 0) TSTAMP(59);
    float acc0[96], acc1[96];
    {
      int s = 0, ph = 0, sprev = 0;
#pragma unroll 1
      for (int kt = 0; kt < KT - STAGES; kt++) {
        mbar_wait(BAR(B_FULL + s), ph);
        if (kt == 0 && tid == 0) TSTAMP(1);
        if (tid == 0 && !(kt & 1)) TSTAMP(44 + kt / 2);
        const uint32_t da = dlo(SB0 + SM_RA, 16) + s * (A_BYTES >> 4) + wg * 512;
        const uint32_t db = dlo(SB0 + SM_RB, 4096) + s * (B_BYTES >> 4);
        wgmma_fence();
#pragma unroll
        for (int k = 0; k < 2; k++) {
          wgmma_ss_n192<0, 1, H64, H128>(acc0, da + k * 2, db + k * 128, (kt | k) != 0);
          wgmma_ss_n192<0, 1, H64, H128>(acc1, da + 256 + k * 2, db + k * 128, (kt | k) != 0);
        }
        wgmma_commit();
        wgmma_wait<1>();
        if (kt > 0 && wi < 2 && elect_one()) mbar_arrive_cluster((wi << 24) + SB0 + SM_BAR + 8 * (B_EMPTY + sprev));
        sprev = s;
        if (++s == STAGES) { s = 0; ph ^= 1; }
      }
#pragma unroll 1
      for (int kt = 0; kt < STAGES; kt++) {
        mbar_wait(BAR(B_FULL + s), ph);
        const uint32_t da = dlo(SB0 + SM_RA, 16) + s * (A_BYTES >> 4) + wg * 512;
        const uint32_t db = dlo(SB0 + SM_RB, 4096) + s * (B_BYTES >> 4);
        wgmma_fence();
        wgmma_ss_n192<0, 1, H64, H128>(acc0, da, db, 1);
        wgmma_ss_n192<0, 1, H64, H128>(acc0, da + 2, db + 128, 1);
        wgmma_commit();
        wgmma_wait<1>();
        if (kt == 0 && wi < 2 && elect_one()) mbar_arrive_cluster((wi << 24) + SB0 + SM_BAR + 8 * (B_EMPTY + 1));
        if (++s == STAGES) { s = 0; ph ^= 1; }
      }
      mbar_wait(BAR(B_RDY), 0);
    }
    const int trow = wg * 128 + wi * 16 + (lane & 15);
    const int chi = lane >> 4;
    uint32_t ak[16], aq[2][16];
    float p[4][16];
    auto catch_one = [&](int i) {
      const int s = (2 + (i >> 1)) % STAGES;
      wgmma_ss_n192<0, 1, H64, H128>(acc1, dlo(SB0 + SM_RA + s * A_BYTES + 4096 + (i & 1) * 32, 16) + wg * 512, dlo(SB0 + SM_RB + s * B_BYTES + (i & 1) * 2048, 4096), 1);
    };
    auto catch_up = [&](int s) { wgmma_fence(); catch_one(2 * s - 4); catch_one(2 * s - 3); wgmma_commit(); };
    auto store_v = [&](const float (&acc)[96], int mb) {
#pragma unroll
      for (int h = 0; h < 2; h++)
#pragma unroll
        for (int jj = 0; jj < 2; jj++) {
          const int o = 64 + h * 16 + jj * 8;
          stsm4(sb + SM_V + h * 16384 + (trow + mb * 64) * 64 + (((2 * jj + chi) ^ ((trow >> 1) & 3)) << 4),
                pack_bf16(acc[o], acc[o + 1]), pack_bf16(acc[o + 2], acc[o + 3]), pack_bf16(acc[o + 4], acc[o + 5]), pack_bf16(acc[o + 6], acc[o + 7]));
        }
    };
    const uint32_t pa = sb + SM_PHIK + (wi >> 1) * 16384 + wg * 8192 + (trow & 31) * 128 + ((chi ^ (trow & 7)) << 4);
    auto store_phi = [&](const uint32_t (&phi)[16], int h, int mb) { store_phi_k(phi, pa + (1 - h) * 32768 + mb * 4096); };
    auto hand_over = [&](int i, bool ok) { hand_over_smem(BAR(B_PHI + i), ok); };
    bool okk[3];
    {
      HState hs;
      uint32_t phi[16];
      float d0, d1;
      catch_up(2);
      wgmma_wait<1>();
      fence_regs(acc0);
      if (tid == 0) TSTAMP(2);
      store_v(acc0, 0);
      pack_frags<32>(acc0, ak);
      issue_feat(ak, p[0], p[1], SB0 + SM_WPHI);
      catch_up(3);
      pack_frags<0>(acc0, aq[0]);
      wgmma_wait<1>();
      fence_regs(p[0]); fence_regs(p[1]); keep_alive(ak);
      wgmma_fence();
#pragma unroll
      for (int i = 4; i < 4 + NFIRST; i++) catch_one(i);
      okk[0] = hedgehog_fast<true>(p[0], phi, d0, d1);
      store_phi(phi, 0, 0);
#pragma unroll
      for (int i = 4 + NFIRST; i < 12; i++) catch_one(i);
      wgmma_commit();
      okk[0] &= hedgehog_fast<true>(p[1], phi, d0, d1);
      store_phi(phi, 1, 0);
      if (tid == 0) TSTAMP(17);
      wgmma_wait<0>();
      fence_regs(acc1);
      if (tid == 0) TSTAMP(27);
      if (wi < 2 && elect_one()) mbar_arrive_cluster((wi << 24) + SB0 + SM_BAR + 8 * (B_EMPTY + 1));
      pack_frags<32>(acc1, ak);
      issue_feat(ak, p[2], p[3], SB0 + SM_WPHI);
      store_v(acc1, 1);
      pack_frags<0>(acc1, aq[1]);
      wgmma_wait<0>();
      fence_regs(p[2]); fence_regs(p[3]); keep_alive(ak);
      asm volatile("setmaxnreg.dec.sync.aligned.u32 " STR(REG_C) ";");
      if (tid == 0) TSTAMP(28);
      HState h2;
      hedgehog_fast1(p[2], hs);
      hedgehog_fast1(p[3], h2);
      okk[1] = __all_sync(0xffffffffu, okk[0] & hedgehog_fast2<true>(hs, phi, d0, d1));
      store_phi(phi, 0, 1);
      hand_over(0, okk[1]);
      h2.s[0] += lds_f32(sb + SM_INFO + 12);
      okk[2] = __all_sync(0xffffffffu, okk[0] & hedgehog_fast2<true>(h2, phi, d0, d1));
      store_phi(phi, 1, 1);
      hand_over(1, okk[2]);
    }
    if (__builtin_expect(!(okk[1] & okk[2]), 0)) {
      __align__(16) float buf[64];
#pragma unroll
      for (int i = 0; i < 64; i++) buf[i] = p[i >> 4][i & 15];
      redo_phi_k(buf, okk[1] * 5 + okk[2] * 10, pa, BAR(B_PHI));
    }
    if (wi == 0 && lane == 0) TSTAMP(wg ? 29 : 3);
    uint32_t pq[4][16];
    float sc[8];
    issue_feat(aq[0], p[0], p[1], SB0 + SM_WPHI);
    issue_feat(aq[1], p[2], p[3], SB0 + SM_WPHI);
    mbar_wait(BAR(Q_AFTER), 0);
    wgmma_wait<0>();
#pragma unroll
    for (int u = 0; u < 4; u++) fence_regs(p[u]);
    keep_alive(aq[0]); keep_alive(aq[1]);
    if (tid == 0) TSTAMP(4);
    {
      bool ok = true;
#pragma unroll
      for (int u = 0; u < 4; u++) ok &= hedgehog_fast<false>(p[u], pq[u], sc[2 * u], sc[2 * u + 1]);
      if (__builtin_expect(!__all_sync(0xffffffffu, ok), 0)) {
        __align__(16) float buf[64];
#pragma unroll
        for (int i = 0; i < 64; i++) buf[i] = p[i >> 4][i & 15];
        hedgehog_slow(buf, 4);
#pragma unroll
        for (int i = 0; i < 64; i++) pq[i >> 4][i & 15] = __float_as_uint(buf[i]);
#pragma unroll
        for (int i = 0; i < 8; i++) sc[i] = 1.0f;
      }
    }
    if (tid == 0) TSTAMP(5);
    float acc[64];
    const int wq = wg ^ half;
    const uint32_t xo = wq * 8192 + wi * 2048 + (lane & 15) * 128 + ((chi ^ (lane & 7)) << 4);
    const uint32_t ga = sb + SM_GATE + (half * 128 + wq * 64 + wi * 16) * 2;
    mbar_wait(BAR(B_XT + wq), 0);
    float gt[4];
#pragma unroll
    for (int i = 0; i < 4; i++) gt[i] = lds_bf16(sb + SM_GATE + (wg * 128 + (i >> 1) * 64 + wi * 16 + (i & 1) * 8 + (lane >> 2)) * 2);
    const float g0 = lds_bf16(ga + (lane >> 2) * 2), g1 = lds_bf16(ga + 16 + (lane >> 2) * 2);
    const unsigned routed = lds_u32(sb + SM_INFO + 4);
    const uint32_t par = lds_u32(sb + SM_INFO) & 1, tmask = (lane & 3) ? ~0u : ~1u, tbit = (lane & 3) ? 0u : par;
    mbar_wait(BAR(B_KVB), 0);
    if (tid == 0) TSTAMP(7);
    if (wg != half) mbar_wait(BAR(B_OP + half * 2 + O_YIELD - 1), 0);
    {
      float nd[4][20];
#pragma unroll
      for (int u = 0; u < 4; u++)
#pragma unroll
        for (int i = 0; i < 16; i++) asm volatile("" : "+r"(pq[u][i]) :: "memory");
      auto num = [&](int mb, int k0, int k1) {
#pragma unroll
        for (int kk = k0; kk < k1; kk++)
#pragma unroll
          for (int h = 0; h < 2; h++) {
            const int u = mb * 2 + h;
            wgmma_rs_n40<1, H64>(nd[u], pq[u][4 * kk], pq[u][4 * kk + 1], pq[u][4 * kk + 2], pq[u][4 * kk + 3],
                                 dlo(SB0 + SM_KVB + h * 4096 + kk * 1024, 8192 - h * 4096 + h * 16), kk != 0);
          }
        wgmma_commit();
      };
      wgmma_fence();
      num(0, 0, 4);
      if (O_OVL == 2) num(1, 0, 4);
#pragma unroll
      for (int mb = 0; mb < 2; mb++) {
        if (O_OVL == 2 && mb == 0) wgmma_wait<1>(); else wgmma_wait<0>();
        fence_regs(nd[2 * mb]); fence_regs(nd[2 * mb + 1]);
        if (O_OVL == 1 && mb == 0) { wgmma_fence(); num(1, 0, 4); }
        if (tid == 0 && mb == 0) TSTAMP(18);
#pragma unroll
        for (int h = 0; h < 2; h++) {
          const int u = mb * 2 + h;
          const float i0 = gt[2 * mb] * rcp(fmaf(sc[2 * u], 1e-6f, nd[u][16])), i1 = gt[2 * mb + 1] * rcp(fmaf(sc[2 * u + 1], 1e-6f, nd[u][18]));
#pragma unroll
          for (int jj = 0; jj < 2; jj++) {
            const int o = jj * 8;
            stsm4(sb + SM_O + (wg ^ half) * 16384 + ((trow & 63) + mb * 64) * 128 + (((h * 4 + 2 * jj + chi) ^ (trow & 7)) << 4),
                  (pack_bf16(nd[u][o] * i0, nd[u][o + 1] * i0) & tmask) | tbit, (pack_bf16(nd[u][o + 2] * i1, nd[u][o + 3] * i1) & tmask) | tbit,
                  pack_bf16(nd[u][o + 4] * i0, nd[u][o + 5] * i0), pack_bf16(nd[u][o + 6] * i1, nd[u][o + 7] * i1));
          }
        }
        fence_async_smem();
        __syncwarp();
        if (elect_one()) mbar_arrive(BAR(B_OP + wg * 2 + mb));
        if (!O_OVL && mb == 0) { wgmma_fence(); num(1, 0, 4); }
      }
#pragma unroll
      for (int u = 0; u < 4; u++)
#pragma unroll
        for (int i = 0; i < 16; i++) asm volatile("" :: "r"(pq[u][i]) : "memory");
    }
    if (tid == 0) TSTAMP(8);
    uint32_t stale = 0;
    {
      const uint32_t ca = sb - SB0 - (dlo(0, 16) << 4) + wi * 2048 + (lane >> 2) * 128 + ((((lane & 3) * 2) ^ (lane >> 2)) << 4);
      const uint32_t da_end = dlo(SB0 + SM_RA + NA2 * 16384, 16) + wq * 512, f_end = BAR(B_F2 + wq * 16 + 16);
      uint32_t da = da_end - 1024, db = dlo(SB0 + SM_RB + 4 * 16384, 8192), f = f_end - 128;
      uint32_t xs[32];
#pragma unroll
      for (int i = 0; i < 2; i++) {
        mbar_wait(f + i * 8, 0);
        wgmma_fence();
#pragma unroll
        for (int k = 0; k < 4; k++) wgmma_ss_n128<0, 1, H128, H128>(acc, da - i * 4096 + k * 2, db + i * 1024 + k * 128, (i | k) != 0);
        wgmma_commit();
        if (i == 0) {
          if ((routed >> 4) == tg * 16 + half * 8 + wq * 4 + wi) mbar_wait_bounded(BAR(B_Y), 0);
#pragma unroll
          for (int jj = 0; jj < 8; jj++)
            ldsm4(((sb + SM_XT + xo) ^ ((jj & 3) << 5)) + (jj >> 2) * 16384, xs[4 * jj], xs[4 * jj + 1], xs[4 * jj + 2], xs[4 * jj + 3]);
          fence_async_smem();
          __syncwarp();
          if (elect_one()) mbar_arrive_cluster(((XT_IN_A ? wq : rank) << 24) + SB0 + SM_BAR + 8 * (XT_IN_A ? B_GO + 3 : B_XTD));
        }
      }
      const float og0 = round_bf16(1.0f - g0), og1 = round_bf16(1.0f - g1);
      da -= 3072; db += 2048; f += 16;
      wgmma_wait<0>();
      fence_regs(acc);
      uint32_t dn = SB0 + SM_BAR + (wi ? (wq << 24) + 8 * (B_GO + NA2) : (rank << 24) + 8 * B_DB);
      if (wi < 2 && elect_one()) mbar_arrive_cluster(dn);
#pragma unroll
      for (int i = 0; i < 32; i++) { acc[2 * i] = fmaf((i & 1) ? og1 : og0, bf_lo(xs[i]), acc[2 * i]); acc[2 * i + 1] = fmaf((i & 1) ? og1 : og0, bf_hi(xs[i]), acc[2 * i + 1]); }
      fence_regs(acc);
      bool got = false;
#pragma unroll 1
      do {
        if (!got) mbar_wait(f, 0);
        wgmma_fence();
        wgmma_ss_n128<0, 1, H128, H128>(acc, da, db, 1);
        const uint32_t ta = ca + (da << 4), t0 = lds_u32(ta), t1 = lds_u32(ta + 1024);
        got = mbar_test(f + 8, 0);
#pragma unroll
        for (int k = 1; k < 4; k++) wgmma_ss_n128<0, 1, H128, H128>(acc, da + k * 2, db + k * 128, 1);
        wgmma_commit();
        da += 1024; if (da == da_end) da -= NA2 * 1024;
        db += 1024; if (db == dlo(SB0 + SM_RB + NB2 * 16384, 8192)) db -= NB2 * 1024;
        f += 8;
        stale |= (t0 ^ par) | (t1 ^ par);
        if (LEAD2 && wq == 0 && wi == 2 && f == f_end - 8 * LEAD_AT && elect_one()) mbar_arrive(BAR(B_F2 + 32 - LEAD2));
        wgmma_wait<1>();
        dn += 8;
        if (wi < 2 && f <= f_end - 32 && elect_one()) mbar_arrive_cluster(dn);
      } while (f != f_end);
      const uint32_t xa = sb + SM_RA + xo, xt = sb + SM_RA + wq * 8192 + wi * 2048;
      const int orow = tg * 256 + half * 128 + wq * 64 + wi * 16;
      const bool redo = __any_sync(0xffffffffu, stale & 1);
      wgmma_wait<0>();
      fence_regs(acc);
      if (wi == 0 && lane == 0) TSTAMP(wq ? 25 : 11);
      stage_out<0, 4>(acc, xa);
      fence_async_smem();
      __syncwarp();
      if (!redo && elect_one()) tma_store_2d(&maps.out, xt, ct * 128, orow);
      stage_out<4, 8>(acc, xa);
      if (__builtin_expect(redo, 0))
        redo_rows(o_piece(half, wq, 0), wo + ct * 128, g_z.done + tg * 16, x + (size_t)orow * D_ + ct * 128, xa, wi, ga, (int)routed - orow, sb + SM_UPD);
      fence_async_smem();
      __syncwarp();
      if (elect_one()) {
        tma_store_2d(&maps.out, xt + 16384, ct * 128 + 64, orow);
        if (redo) tma_store_2d(&maps.out, xt, ct * 128, orow);
      }
      bulk_commit();
      bulk_wait0_read();
    }
  }
}

typedef CUresult (*PFN_encodeTiled)(CUtensorMap*, CUtensorMapDataType, cuuint32_t, void*, const cuuint64_t*, const cuuint64_t*,
                                    const cuuint32_t*, const cuuint32_t*, CUtensorMapInterleave, CUtensorMapSwizzle,
                                    CUtensorMapL2promotion, CUtensorMapFloatOOBfill);
static void make_map(PFN_encodeTiled fn, CUtensorMap* m, const void* ptr, uint64_t rows, uint64_t cols, uint32_t brows, uint32_t bcols,
                     CUtensorMapSwizzle sw, CUtensorMapL2promotion prom) {
  cuuint64_t dims[2] = {cols, rows}; cuuint64_t strides[1] = {cols * 2}; cuuint32_t box[2] = {bcols, brows}; cuuint32_t es[2] = {1, 1};
  fn(m, CU_TENSOR_MAP_DATA_TYPE_BFLOAT16, 2, const_cast<void*>(ptr), dims, strides, box, es, CU_TENSOR_MAP_INTERLEAVE_NONE, sw, prom,
     CU_TENSOR_MAP_FLOAT_OOB_FILL_NONE);
}

extern "C" void kernel_launch(void* const* d_in, const int* in_sizes, int n_in, void* d_out, int out_size) {
  const __nv_bfloat16* x = (const __nv_bfloat16*)d_in[0];
  const __nv_bfloat16* wqkv = (const __nv_bfloat16*)d_in[1];
  const __nv_bfloat16* wphi = (const __nv_bfloat16*)d_in[2];
  const __nv_bfloat16* wo = (const __nv_bfloat16*)d_in[3];
  const __nv_bfloat16* w_r = (const __nv_bfloat16*)d_in[5];
  const __nv_bfloat16* w_gate = (const __nv_bfloat16*)d_in[6];
  const __nv_bfloat16* w_up = (const __nv_bfloat16*)d_in[7];
  const __nv_bfloat16* w_down = (const __nv_bfloat16*)d_in[8];
  const __nv_bfloat16* gate_w = (const __nv_bfloat16*)d_in[9];
  void* fp = nullptr; cudaDriverEntryPointQueryResult qr;
  cudaGetDriverEntryPoint("cuTensorMapEncodeTiled", &fp, cudaEnableDefault, &qr);
  PFN_encodeTiled fn = (PFN_encodeTiled)fp;
  Maps m;
  const CUtensorMapL2promotion P128 = CU_TENSOR_MAP_L2_PROMOTION_L2_128B;
  make_map(fn, &m.x, x, S_, D_, 128, 32, CU_TENSOR_MAP_SWIZZLE_64B, P128);
  {
    cuuint64_t dims[3] = {D_, D_, 3}; cuuint64_t strides[2] = {3 * D_ * 2, D_ * 2}; cuuint32_t box[3] = {64, 32, 3}; cuuint32_t es[3] = {1, 1, 1};
    fn(&m.w, CU_TENSOR_MAP_DATA_TYPE_BFLOAT16, 3, (void*)wqkv, dims, strides, box, es, CU_TENSOR_MAP_INTERLEAVE_NONE,
       CU_TENSOR_MAP_SWIZZLE_128B, P128, CU_TENSOR_MAP_FLOAT_OOB_FILL_NONE);
  }
  {
    cuuint64_t dims[3] = {64, D_, 16}; cuuint64_t strides[2] = {D_ * 2, 128}; cuuint32_t box[3] = {64, 64, 2}; cuuint32_t es[3] = {1, 1, 1};
    fn(&m.wo, CU_TENSOR_MAP_DATA_TYPE_BFLOAT16, 3, (void*)wo, dims, strides, box, es, CU_TENSOR_MAP_INTERLEAVE_NONE,
       CU_TENSOR_MAP_SWIZZLE_128B, P128, CU_TENSOR_MAP_FLOAT_OOB_FILL_NONE);
  }
  make_map(fn, &m.wphi, wphi, 1024, 32, 64, 32, CU_TENSOR_MAP_SWIZZLE_64B, P128);
  for (int i = 0; i < 3; i++) {
    cuuint64_t dims[3] = {i < 2 ? (cuuint64_t)F_ : 64, i < 2 ? (cuuint64_t)16 : F_, i < 2 ? (cuuint64_t)64 : 16};
    cuuint64_t strides[2] = {i < 2 ? (cuuint64_t)F_ * 2 : D_ * 2, i < 2 ? (cuuint64_t)F_ * 32 : 128};
    cuuint32_t box[3] = {64, i < 2 ? 16u : 4u, i < 2 ? 4u : 16u}; cuuint32_t es[3] = {1, 1, 1};
    fn(&m.wg + i, CU_TENSOR_MAP_DATA_TYPE_BFLOAT16, 3, (void*)(i == 0 ? w_gate : i == 1 ? w_up : w_down), dims, strides, box, es,
       CU_TENSOR_MAP_INTERLEAVE_NONE, CU_TENSOR_MAP_SWIZZLE_NONE, P128, CU_TENSOR_MAP_FLOAT_OOB_FILL_NONE);
  }
  make_map(fn, &m.xt, x, S_, D_, 64, 64, CU_TENSOR_MAP_SWIZZLE_128B, P128);
  make_map(fn, &m.out, d_out, S_, D_, 16, 64, CU_TENSOR_MAP_SWIZZLE_128B, P128);
  make_map(fn, &m.xr, x, S_, D_, 16, 128, CU_TENSOR_MAP_SWIZZLE_NONE, P128);
  make_map(fn, &m.tg, w_gate, D_, F_, 64, 64, CU_TENSOR_MAP_SWIZZLE_NONE, P128);
  make_map(fn, &m.tu, w_up, D_, F_, 64, 64, CU_TENSOR_MAP_SWIZZLE_NONE, P128);
  make_map(fn, &m.td, w_down, F_ * 16, 64, 64, 64, CU_TENSOR_MAP_SWIZZLE_NONE, P128);
  make_map(fn, &m.to, wo, D_ * 16, 64, 64, 64, CU_TENSOR_MAP_SWIZZLE_NONE, P128);
  for (int cl = 0; cl < NCTA / 2; cl++) {
    const int col = cl < 4 ? 7 : cl < 36 ? ((cl - 4) & 3) + ((cl - 4) & 4) * 2 : (cl - 36) % 7 + ((cl - 36) % 7 < 3 ? 4 : 9);
    const int pos = cl < 4 ? cl : cl < 36 ? (cl - 4) >> 3 : (cl - 36) / 7;
    m.tile[cl] = ((col & 7) * 16 + (col >> 3) * 8 + pos * 2) | (EVEN_FFN ? cl * 2 : (col & 7) * 16 + (col >> 3) * 8 + pos * 2) << 8;
  }
  m.tile[NCTA / 2] = NCTA;
  cudaFuncSetAttribute(fused_kernel, cudaFuncAttributeMaxDynamicSharedMemorySize, SM_TOTAL);
  fused_kernel<<<NCTA + 2, 512, SM_TOTAL>>>(m, x, wo, w_r, gate_w);
}
```

```cpp
#include <cuda_runtime.h>
#include <cuda_bf16.h>
#include <cuda.h>
#include <stdint.h>

__device__ __forceinline__ uint32_t smem_u32(const void* p) { return (uint32_t)__cvta_generic_to_shared(p); }
__device__ __forceinline__ void mbar_init(uint32_t bar, uint32_t cnt) { asm volatile("mbarrier.init.shared::cta.b64 [%0], %1;" :: "r"(bar), "r"(cnt) : "memory"); }
__device__ __forceinline__ void mbar_expect_tx(uint32_t bar, uint32_t bytes) { asm volatile("mbarrier.arrive.expect_tx.shared::cta.b64 _, [%0], %1;" :: "r"(bar), "r"(bytes) : "memory"); }
__device__ __forceinline__ void mbar_arrive(uint32_t bar) { asm volatile("mbarrier.arrive.shared::cta.b64 _, [%0];" :: "r"(bar) : "memory"); }
__device__ __forceinline__ bool mbar_try_wait(uint32_t bar, uint32_t parity) {
  uint32_t ok;
  asm volatile("{\n.reg .pred p;\nmbarrier.try_wait.parity.shared::cta.b64 p, [%1], %2;\nselp.u32 %0, 1, 0, p;\n}" : "=r"(ok) : "r"(bar), "r"(parity) : "memory");
  return ok;
}
__device__ __forceinline__ bool mbar_test(uint32_t bar, uint32_t parity) {
  uint32_t ok;
  asm volatile("{\n.reg .pred p;\nmbarrier.test_wait.parity.shared::cta.b64 p, [%1], %2;\nselp.u32 %0, 1, 0, p;\n}" : "=r"(ok) : "r"(bar), "r"(parity) : "memory");
  return ok;
}
__device__ __forceinline__ void mbar_wait(uint32_t bar, uint32_t parity) {
  asm volatile("{\n.reg .pred p;\nWAIT: mbarrier.try_wait.parity.shared::cta.b64 p, [%0], %1;\n@!p bra.uni WAIT;\n}" :: "r"(bar), "r"(parity) : "memory");
}
__device__ __forceinline__ void mbar_wait_bounded(uint32_t bar, uint32_t parity) {
#pragma unroll 1
  for (int it = 0; it < (1 << 22); it++) { if (mbar_try_wait(bar, parity)) return; }
  __trap();
}
__device__ __forceinline__ void tma_load_2d(uint32_t dst, const CUtensorMap* tm, int c0, int c1, uint32_t bar) {
  asm volatile("cp.async.bulk.tensor.2d.shared::cluster.global.mbarrier::complete_tx::bytes [%0], [%1, {%3, %4}], [%2];"
    :: "r"(dst), "l"(tm), "r"(bar), "r"(c0), "r"(c1) : "memory");
}
__device__ __forceinline__ void tma_load_2d_mc(uint32_t dst, const CUtensorMap* tm, int c0, int c1, uint32_t bar) {
  asm volatile("cp.async.bulk.tensor.2d.shared::cluster.global.mbarrier::complete_tx::bytes.multicast::cluster [%0], [%1, {%3, %4}], [%2], %5;"
    :: "r"(dst), "l"(tm), "r"(bar), "r"(c0), "r"(c1), "h"((uint16_t)3) : "memory");
}
__device__ __forceinline__ void mbar_arrive_cluster(uint32_t bar) { asm volatile("mbarrier.arrive.shared::cluster.b64 _, [%0];" :: "r"(bar) : "memory"); }
__device__ __forceinline__ void wgmma_fence() { asm volatile("wgmma.fence.sync.aligned;" ::: "memory"); }
__device__ __forceinline__ void wgmma_commit() { asm volatile("wgmma.commit_group.sync.aligned;" ::: "memory"); }
template <int N> __device__ __forceinline__ void wgmma_wait() { asm volatile("wgmma.wait_group.sync.aligned %0;" :: "n"(N) : "memory"); }
template <int N> __device__ __forceinline__ void fence_regs(float (&d)[N]) {
#pragma unroll
  for (int i = 0; i < N; i++) asm volatile("" : "+f"(d[i]) :: "memory");
}
__host__ __device__ constexpr uint32_t dlo(uint32_t addr, uint32_t lbo) { return (addr >> 4) | ((lbo >> 4) << 16); }
constexpr uint32_t H128 = (1024 >> 4) | (1u << 30);
constexpr uint32_t H64 = (512 >> 4) | (2u << 30);

template <int TA, int TB, uint32_t HA, uint32_t HB>
__device__ __forceinline__ void wgmma_ss_n192(float (&d)[96], uint32_t da, uint32_t db, int scale_d) {
  asm volatile("{\n.reg .pred p;\n.reg .b64 da, db;\nsetp.ne.b32 p, %98, 0;\nmov.b64 da, {%96, %101};\nmov.b64 db, {%97, %102};\n"
    "wgmma.mma_async.sync.aligned.m64n192k16.f32.bf16.bf16 {%0, %1, %2, %3, %4, %5, %6, %7, %8, %9, %10, %11, %12, %13, %14, %15, %16, %17, %18, %19, %20, %21, %22, %23, %24, %25, %26, %27, %28, %29, %30, %31, %32, %33, %34, %35, %36, %37, %38, %39, %40, %41, %42, %43, %44, %45, %46, %47, %48, %49, %50, %51, %52, %53, %54, %55, %56, %57, %58, %59, %60, %61, %62, %63, %64, %65, %66, %67, %68, %69, %70, %71, %72, %73, %74, %75, %76, %77, %78, %79, %80, %81, %82, %83, %84, %85, %86, %87, %88, %89, %90, %91, %92, %93, %94, %95}, da, db, p, 1, 1, %99, %100;\n}\n"
    : "+f"(d[0]), "+f"(d[1]), "+f"(d[2]), "+f"(d[3]), "+f"(d[4]), "+f"(d[5]), "+f"(d[6]), "+f"(d[7]), "+f"(d[8]), "+f"(d[9]), "+f"(d[10]), "+f"(d[11]), "+f"(d[12]), "+f"(d[13]), "+f"(d[14]), "+f"(d[15]), "+f"(d[16]), "+f"(d[17]), "+f"(d[18]), "+f"(d[19]), "+f"(d[20]), "+f"(d[21]), "+f"(d[22]), "+f"(d[23]), "+f"(d[24]), "+f"(d[25]), "+f"(d[26]), "+f"(d[27]), "+f"(d[28]), "+f"(d[29]), "+f"(d[30]), "+f"(d[31]), "+f"(d[32]), "+f"(d[33]), "+f"(d[34]), "+f"(d[35]), "+f"(d[36]), "+f"(d[37]), "+f"(d[38]), "+f"(d[39]), "+f"(d[40]), "+f"(d[41]), "+f"(d[42]), "+f"(d[43]), "+f"(d[44]), "+f"(d[45]), "+f"(d[46]), "+f"(d[47]), "+f"(d[48]), "+f"(d[49]), "+f"(d[50]), "+f"(d[51]), "+f"(d[52]), "+f"(d[53]), "+f"(d[54]), "+f"(d[55]), "+f"(d[56]), "+f"(d[57]), "+f"(d[58]), "+f"(d[59]), "+f"(d[60]), "+f"(d[61]), "+f"(d[62]), "+f"(d[63]), "+f"(d[64]), "+f"(d[65]), "+f"(d[66]), "+f"(d[67]), "+f"(d[68]), "+f"(d[69]), "+f"(d[70]), "+f"(d[71]), "+f"(d[72]), "+f"(d[73]), "+f"(d[74]), "+f"(d[75]), "+f"(d[76]), "+f"(d[77]), "+f"(d[78]), "+f"(d[79]), "+f"(d[80]), "+f"(d[81]), "+f"(d[82]), "+f"(d[83]), "+f"(d[84]), "+f"(d[85]), "+f"(d[86]), "+f"(d[87]), "+f"(d[88]), "+f"(d[89]), "+f"(d[90]), "+f"(d[91]), "+f"(d[92]), "+f"(d[93]), "+f"(d[94]), "+f"(d[95])
    : "r"(da), "r"(db), "r"(scale_d), "n"(TA), "n"(TB), "n"(HA), "n"(HB));
}

template <int TA, int TB, uint32_t HA, uint32_t HB>
__device__ __forceinline__ void wgmma_ss_n128(float (&d)[64], uint32_t da, uint32_t db, int scale_d) {
  asm volatile("{\n.reg .pred p;\n.reg .b64 da, db;\nsetp.ne.b32 p, %66, 0;\nmov.b64 da, {%64, %69};\nmov.b64 db, {%65, %70};\n"
    "wgmma.mma_async.sync.aligned.m64n128k16.f32.bf16.bf16 {%0, %1, %2, %3, %4, %5, %6, %7, %8, %9, %10, %11, %12, %13, %14, %15, %16, %17, %18, %19, %20, %21, %22, %23, %24, %25, %26, %27, %28, %29, %30, %31, %32, %33, %34, %35, %36, %37, %38, %39, %40, %41, %42, %43, %44, %45, %46, %47, %48, %49, %50, %51, %52, %53, %54, %55, %56, %57, %58, %59, %60, %61, %62, %63}, da, db, p, 1, 1, %67, %68;\n}\n"
    : "+f"(d[0]), "+f"(d[1]), "+f"(d[2]), "+f"(d[3]), "+f"(d[4]), "+f"(d[5]), "+f"(d[6]), "+f"(d[7]), "+f"(d[8]), "+f"(d[9]), "+f"(d[10]), "+f"(d[11]), "+f"(d[12]), "+f"(d[13]), "+f"(d[14]), "+f"(d[15]), "+f"(d[16]), "+f"(d[17]), "+f"(d[18]), "+f"(d[19]), "+f"(d[20]), "+f"(d[21]), "+f"(d[22]), "+f"(d[23]), "+f"(d[24]), "+f"(d[25]), "+f"(d[26]), "+f"(d[27]), "+f"(d[28]), "+f"(d[29]), "+f"(d[30]), "+f"(d[31]), "+f"(d[32]), "+f"(d[33]), "+f"(d[34]), "+f"(d[35]), "+f"(d[36]), "+f"(d[37]), "+f"(d[38]), "+f"(d[39]), "+f"(d[40]), "+f"(d[41]), "+f"(d[42]), "+f"(d[43]), "+f"(d[44]), "+f"(d[45]), "+f"(d[46]), "+f"(d[47]), "+f"(d[48]), "+f"(d[49]), "+f"(d[50]), "+f"(d[51]), "+f"(d[52]), "+f"(d[53]), "+f"(d[54]), "+f"(d[55]), "+f"(d[56]), "+f"(d[57]), "+f"(d[58]), "+f"(d[59]), "+f"(d[60]), "+f"(d[61]), "+f"(d[62]), "+f"(d[63])
    : "r"(da), "r"(db), "r"(scale_d), "n"(TA), "n"(TB), "n"(HA), "n"(HB));
}

template <int TA, int TB, uint32_t HA, uint32_t HB>
__device__ __forceinline__ void wgmma_ss_n40(float (&d)[20], uint32_t da, uint32_t db, int scale_d) {
  asm volatile("{\n.reg .pred p;\n.reg .b64 da, db;\nsetp.ne.b32 p, %22, 0;\nmov.b64 da, {%20, %25};\nmov.b64 db, {%21, %26};\n"
    "wgmma.mma_async.sync.aligned.m64n40k16.f32.bf16.bf16 {%0, %1, %2, %3, %4, %5, %6, %7, %8, %9, %10, %11, %12, %13, %14, %15, %16, %17, %18, %19}, da, db, p, 1, 1, %23, %24;\n}\n"
    : "+f"(d[0]), "+f"(d[1]), "+f"(d[2]), "+f"(d[3]), "+f"(d[4]), "+f"(d[5]), "+f"(d[6]), "+f"(d[7]), "+f"(d[8]), "+f"(d[9]), "+f"(d[10]), "+f"(d[11]), "+f"(d[12]), "+f"(d[13]), "+f"(d[14]), "+f"(d[15]), "+f"(d[16]), "+f"(d[17]), "+f"(d[18]), "+f"(d[19])
    : "r"(da), "r"(db), "r"(scale_d), "n"(TA), "n"(TB), "n"(HA), "n"(HB));
}

template <int TB, uint32_t HB>
__device__ __forceinline__ void wgmma_rs_n32(float (&d)[16], uint32_t a0, uint32_t a1, uint32_t a2, uint32_t a3, uint32_t db, int scale_d) {
  asm volatile("{\n.reg .pred p;\n.reg .b64 db;\nsetp.ne.b32 p, %21, 0;\nmov.b64 db, {%20, %23};\n"
    "wgmma.mma_async.sync.aligned.m64n32k16.f32.bf16.bf16 {%0, %1, %2, %3, %4, %5, %6, %7, %8, %9, %10, %11, %12, %13, %14, %15}, {%16, %17, %18, %19}, db, p, 1, 1, %22;\n}\n"
    : "+f"(d[0]), "+f"(d[1]), "+f"(d[2]), "+f"(d[3]), "+f"(d[4]), "+f"(d[5]), "+f"(d[6]), "+f"(d[7]), "+f"(d[8]), "+f"(d[9]), "+f"(d[10]), "+f"(d[11]), "+f"(d[12]), "+f"(d[13]), "+f"(d[14]), "+f"(d[15])
    : "r"(a0), "r"(a1), "r"(a2), "r"(a3), "r"(db), "r"(scale_d), "n"(TB), "n"(HB));
}

template <int TB, uint32_t HB>
__device__ __forceinline__ void wgmma_rs_n40(float (&d)[20], uint32_t a0, uint32_t a1, uint32_t a2, uint32_t a3, uint32_t db, int scale_d) {
  asm volatile("{\n.reg .pred p;\n.reg .b64 db;\nsetp.ne.b32 p, %25, 0;\nmov.b64 db, {%24, %27};\n"
    "wgmma.mma_async.sync.aligned.m64n40k16.f32.bf16.bf16 {%0, %1, %2, %3, %4, %5, %6, %7, %8, %9, %10, %11, %12, %13, %14, %15, %16, %17, %18, %19}, {%20, %21, %22, %23}, db, p, 1, 1, %26;\n}\n"
    : "+f"(d[0]), "+f"(d[1]), "+f"(d[2]), "+f"(d[3]), "+f"(d[4]), "+f"(d[5]), "+f"(d[6]), "+f"(d[7]), "+f"(d[8]), "+f"(d[9]), "+f"(d[10]), "+f"(d[11]), "+f"(d[12]), "+f"(d[13]), "+f"(d[14]), "+f"(d[15]), "+f"(d[16]), "+f"(d[17]), "+f"(d[18]), "+f"(d[19])
    : "r"(a0), "r"(a1), "r"(a2), "r"(a3), "r"(db), "r"(scale_d), "n"(TB), "n"(HB));
}

template <int TB, uint32_t HB>
__device__ __forceinline__ void wgmma_rs_n128(float (&d)[64], uint32_t a0, uint32_t a1, uint32_t a2, uint32_t a3, uint32_t db, int scale_d) {
  asm volatile("{\n.reg .pred p;\n.reg .b64 db;\nsetp.ne.b32 p, %69, 0;\nmov.b64 db, {%68, %71};\n"
    "wgmma.mma_async.sync.aligned.m64n128k16.f32.bf16.bf16 {%0, %1, %2, %3, %4, %5, %6, %7, %8, %9, %10, %11, %12, %13, %14, %15, %16, %17, %18, %19, %20, %21, %22, %23, %24, %25, %26, %27, %28, %29, %30, %31, %32, %33, %34, %35, %36, %37, %38, %39, %40, %41, %42, %43, %44, %45, %46, %47, %48, %49, %50, %51, %52, %53, %54, %55, %56, %57, %58, %59, %60, %61, %62, %63}, {%64, %65, %66, %67}, db, p, 1, 1, %70;\n}\n"
    : "+f"(d[0]), "+f"(d[1]), "+f"(d[2]), "+f"(d[3]), "+f"(d[4]), "+f"(d[5]), "+f"(d[6]), "+f"(d[7]), "+f"(d[8]), "+f"(d[9]), "+f"(d[10]), "+f"(d[11]), "+f"(d[12]), "+f"(d[13]), "+f"(d[14]), "+f"(d[15]), "+f"(d[16]), "+f"(d[17]), "+f"(d[18]), "+f"(d[19]), "+f"(d[20]), "+f"(d[21]), "+f"(d[22]), "+f"(d[23]), "+f"(d[24]), "+f"(d[25]), "+f"(d[26]), "+f"(d[27]), "+f"(d[28]), "+f"(d[29]), "+f"(d[30]), "+f"(d[31]), "+f"(d[32]), "+f"(d[33]), "+f"(d[34]), "+f"(d[35]), "+f"(d[36]), "+f"(d[37]), "+f"(d[38]), "+f"(d[39]), "+f"(d[40]), "+f"(d[41]), "+f"(d[42]), "+f"(d[43]), "+f"(d[44]), "+f"(d[45]), "+f"(d[46]), "+f"(d[47]), "+f"(d[48]), "+f"(d[49]), "+f"(d[50]), "+f"(d[51]), "+f"(d[52]), "+f"(d[53]), "+f"(d[54]), "+f"(d[55]), "+f"(d[56]), "+f"(d[57]), "+f"(d[58]), "+f"(d[59]), "+f"(d[60]), "+f"(d[61]), "+f"(d[62]), "+f"(d[63])
    : "r"(a0), "r"(a1), "r"(a2), "r"(a3), "r"(db), "r"(scale_d), "n"(TB), "n"(HB));
}

constexpr int S_ = 2048, D_ = 1024, F_ = 3584;
constexpr int NCTA = 128;
#define NMOE_ 112
constexpr int NMOE = NMOE_;
#define KV16 1
constexpr int KVH = 5 * 128 * 2;

#define NY 8
struct Zeroed {
  float kv[32 * KVH];
  float y[NY * 2 * D_];
  unsigned hint[512];
  unsigned done[128];
  unsigned pad[384];
};
constexpr int ZB = KVH + 32 + NY * 64;
static_assert(sizeof(Zeroed) == NCTA * ZB, "zeroed block");
__device__ __align__(128) Zeroed g_z;
__device__ __align__(128) unsigned g_key[2 * NCTA];
__device__ __align__(128) uint2 g_bcast[2 * 8 * 16];
__device__ __align__(128) unsigned g_gate[S_];
__device__ __align__(1024) __nv_bfloat16 g_o[S_ * D_];
#define TSTAMP(i)
#define GSTAMP(i)

constexpr int STAGES = 6, KT = 32;
constexpr int A_BYTES = 256 * 64, B_BYTES = 192 * 64, STAGE_BYTES = A_BYTES + B_BYTES;
constexpr int SM_RA = 0;
constexpr int SM_RB = STAGES * A_BYTES;
constexpr int SM_PHIK = 0;
constexpr int SM_V = 65536;
constexpr int SM_O = SM_V;
constexpr int NA2 = 5, NB2 = 7;
#define XT_IN_A 1
constexpr int SM_XT = (XT_IN_A ? SM_RA : SM_RB) + 2 * 16384;
constexpr int SM_XR = STAGES * STAGE_BYTES;
constexpr int SM_MOE = SM_XR;
constexpr int SM_XSEL = SM_XR + 36864;
constexpr int SM_RED = SM_XSEL + 2048;
constexpr int SM_WPHI = 212992;
constexpr int SM_KVB = SM_WPHI + 4096;
constexpr int SM_ONES = SM_KVB + 12288;
constexpr int SM_BAR = SM_ONES + 1024;
constexpr int SM_INFO = SM_BAR + 1008;
constexpr int SM_GATE = SM_BAR + 1024;
constexpr int SM_UPD = SM_WPHI;
constexpr int SM_KEYS = SM_GATE + 512;
constexpr int SM_TS = SM_KEYS + 16;
constexpr int SM_TOTAL = SM_TS + 256;
static_assert(SM_TOTAL <= 232448 && ZB <= 4608, "smem");
static_assert(SM_WPHI % 1024 == 0 && SM_KVB % 1024 == 0 && SM_ONES % 1024 == 0, "align");
static_assert(SM_MOE + 40960 <= SM_WPHI && SM_RB + NB2 * 16384 <= SM_WPHI, "map");
#define QUAD 1
#define Q_UNROLL 1
#define HINT_U 0
#define HINT_L 0
#define COLMAP 0xefdb9ca875316420ull
#define INIT_FENCE 0
#define KV_BAR 0
#define KV_LOOP 0
#define GATE_EXACT 1
#define FFN_LOOP 0
#define QUAD_Q 1
#define EXPT 0
#define PF_START 0
#define PF_OFF 0
#define KV_DELAY 400
#define O_YIELD 1
#define TAILV -1
#define NFIRST 5
#define Q_AFTER B_PHI + 1
#define LEAD2 4
#define KEY_SLEEP 0
#define B5_AFTER B_F2 + 2
#define REG_C 192
#define REG_K 88
#define STR2(x) #x
#define STR(x) STR2(x)
#define XT_H 0
#define EARLY_MAP 1
#define NPRE 1
#define O_OVL 1
#define LATE_SZ 8192
#define LATE_SLEEP 0
#define URG_STEP 0
#define LEAD_AT 1
#define XR_AFTER 3
#define LATE_DELAY 300
#define LATE_STEP 400

constexpr int B_FULL = 0, B_XR = 6, B_WPHI = 10;
constexpr int B_EMPTY = 11, B_XRD = 17;
constexpr int B_INIT = 123;
constexpr int B_ST = 18, B_MOE = 20, B_XSEL = 24, B_H = 25, B_RDY = 26, B_Y = 27, B_XT = 28, B_PEER = 30;
constexpr int B_FB2 = 31, B_F2 = 47;
constexpr int B_DB = 79;
constexpr int B_GO = 95;
constexpr int B_KVB = 111, B_OP = 112, B_MOEE = 116;
constexpr int B_PHI = 120, B_XTD = 122;
constexpr int NBAR = 123;
__host__ __device__ constexpr int bar_count(int i) {
  return i < B_DB ? 1 : i < B_GO ? 2 : i < B_KVB ? (int)(0x3333333333519111ull >> (4 * (i - B_GO))) & 15 : i < B_PHI ? 4 : 8;
}

struct Maps { CUtensorMap x, w, wo, wphi, wg, wu, wd, tg, tu, td, to, xr, xt, out; };

__device__ __forceinline__ uint32_t pack_bf16(float lo, float hi) {
  uint32_t r; asm("cvt.rn.bf16x2.f32 %0, %1, %2;" : "=r"(r) : "f"(hi), "f"(lo)); return r;
}
__device__ __forceinline__ float bf_lo(uint32_t v) { return __uint_as_float(v << 16); }
__device__ __forceinline__ float bf_hi(uint32_t v) { return __uint_as_float(v & 0xffff0000u); }
__device__ __forceinline__ float round_bf16(float v) { return __bfloat162float(__float2bfloat16_rn(v)); }
__device__ __forceinline__ float ex2(float v) { float r; asm("ex2.approx.ftz.f32 %0, %1;" : "=f"(r) : "f"(v)); return r; }
__device__ __forceinline__ float rcp(float v) { float r; asm("rcp.approx.ftz.f32 %0, %1;" : "=f"(r) : "f"(v)); return r; }
__device__ __forceinline__ void stsm4(uint32_t addr, uint32_t r0, uint32_t r1, uint32_t r2, uint32_t r3) {
  asm volatile("stmatrix.sync.aligned.m8n8.x4.shared.b16 [%0], {%1, %2, %3, %4};" :: "r"(addr), "r"(r0), "r"(r1), "r"(r2), "r"(r3) : "memory");
}
__device__ __forceinline__ void stsm2(uint32_t addr, uint32_t r0, uint32_t r1) {
  asm volatile("stmatrix.sync.aligned.m8n8.x2.shared.b16 [%0], {%1, %2};" :: "r"(addr), "r"(r0), "r"(r1) : "memory");
}
__device__ __forceinline__ uint2 lds64(uint32_t addr) {
  uint2 v; asm volatile("ld.shared.v2.u32 {%0, %1}, [%2];" : "=r"(v.x), "=r"(v.y) : "r"(addr) : "memory"); return v;
}
__device__ __forceinline__ void lds128x4(uint32_t addr, uint4& a, uint4& b, uint4& c, uint4& d) {
  asm volatile("ld.shared.v4.u32 {%0, %1, %2, %3}, [%16];\nld.shared.v4.u32 {%4, %5, %6, %7}, [%16 + 128];\n"
               "ld.shared.v4.u32 {%8, %9, %10, %11}, [%16 + 256];\nld.shared.v4.u32 {%12, %13, %14, %15}, [%16 + 384];"
    : "=r"(a.x), "=r"(a.y), "=r"(a.z), "=r"(a.w), "=r"(b.x), "=r"(b.y), "=r"(b.z), "=r"(b.w),
      "=r"(c.x), "=r"(c.y), "=r"(c.z), "=r"(c.w), "=r"(d.x), "=r"(d.y), "=r"(d.z), "=r"(d.w) : "r"(addr) : "memory");
}
__device__ __forceinline__ void ldsm4(uint32_t addr, uint32_t& r0, uint32_t& r1, uint32_t& r2, uint32_t& r3) {
  asm volatile("ldmatrix.sync.aligned.m8n8.x4.shared.b16 {%0, %1, %2, %3}, [%4];" : "=r"(r0), "=r"(r1), "=r"(r2), "=r"(r3) : "r"(addr) : "memory");
}
__device__ __forceinline__ uint4 lds128(uint32_t addr) {
  uint4 v; asm volatile("ld.shared.v4.u32 {%0, %1, %2, %3}, [%4];" : "=r"(v.x), "=r"(v.y), "=r"(v.z), "=r"(v.w) : "r"(addr) : "memory"); return v;
}
__device__ __forceinline__ void sts128(uint32_t addr, uint4 v) {
  asm volatile("st.shared.v4.u32 [%0], {%1, %2, %3, %4};" :: "r"(addr), "r"(v.x), "r"(v.y), "r"(v.z), "r"(v.w) : "memory");
}
__device__ __forceinline__ float lds_f32(uint32_t addr) { float v; asm volatile("ld.shared.f32 %0, [%1];" : "=f"(v) : "r"(addr) : "memory"); return v; }
__device__ __forceinline__ void sts_f32(uint32_t addr, float v) { asm volatile("st.shared.f32 [%0], %1;" :: "r"(addr), "f"(v) : "memory"); }
__device__ __forceinline__ uint32_t lds_u32(uint32_t addr) { uint32_t v; asm volatile("ld.shared.u32 %0, [%1];" : "=r"(v) : "r"(addr) : "memory"); return v; }
__device__ __forceinline__ void sts_u32(uint32_t addr, uint32_t v) { asm volatile("st.shared.u32 [%0], %1;" :: "r"(addr), "r"(v) : "memory"); }
__device__ __forceinline__ unsigned clock32() { unsigned c; asm volatile("mov.u32 %0, %%clock;" : "=r"(c)); return c; }
__device__ __forceinline__ bool elect_one() {
  uint32_t p; asm volatile("{\n.reg .pred q;\nelect.sync _|q, 0xffffffff;\nselp.u32 %0, 1, 0, q;\n}" : "=r"(p)); return p;
}
__device__ __forceinline__ void bar_sync(int id, int n) { asm volatile("bar.sync %0, %1;" :: "r"(id), "r"(n) : "memory"); }
__device__ __forceinline__ void fence_async_smem() { asm volatile("fence.proxy.async.shared::cta;" ::: "memory"); }
__device__ __forceinline__ void fence_async_all() { asm volatile("fence.proxy.async;" ::: "memory"); }
__device__ __forceinline__ void fence_gpu() { asm volatile("fence.acq_rel.gpu;" ::: "memory"); }
__device__ __forceinline__ unsigned ld_acquire(const unsigned* p) { unsigned v; asm volatile("ld.acquire.gpu.global.u32 %0, [%1];" : "=r"(v) : "l"(p) : "memory"); return v; }
__device__ __forceinline__ void red_release(unsigned* p, unsigned v) { asm volatile("red.release.gpu.global.add.u32 [%0], %1;" :: "l"(p), "r"(v) : "memory"); }
__device__ __forceinline__ void st_release(unsigned* p, unsigned v) { asm volatile("st.release.gpu.global.u32 [%0], %1;" :: "l"(p), "r"(v) : "memory"); }
__device__ __forceinline__ unsigned ld_relaxed(const unsigned* p) { unsigned v; asm volatile("ld.relaxed.gpu.global.u32 %0, [%1];" : "=r"(v) : "l"(p) : "memory"); return v; }
__device__ __forceinline__ void red_relaxed(unsigned* p, unsigned v) { asm volatile("red.relaxed.gpu.global.add.u32 [%0], %1;" :: "l"(p), "r"(v) : "memory"); }
__device__ __forceinline__ void st_relaxed(unsigned* p, unsigned v) { asm volatile("st.relaxed.gpu.global.u32 [%0], %1;" :: "l"(p), "r"(v) : "memory"); }
__device__ __forceinline__ void st_relaxed2(uint2* p, unsigned a, unsigned b) { asm volatile("st.relaxed.gpu.global.v2.u32 [%0], {%1, %2};" :: "l"(p), "r"(a), "r"(b) : "memory"); }
template <int SLEEP>
__device__ __forceinline__ unsigned wait_tagged(const uint2* p, unsigned tag) {
  uint2 v;
  int it = 0;
  do {
    if (SLEEP && it > 0) __nanosleep(SLEEP);
    asm volatile("ld.relaxed.gpu.global.v2.u32 {%0, %1}, [%2];" : "=r"(v.x), "=r"(v.y) : "l"(p) : "memory");
    if (++it > (1 << 20)) __trap();
  } while (!__all_sync(0xffffffffu, v.y == tag));
  return v.x;
}
__device__ __forceinline__ void wait_counter(const unsigned* p, unsigned target) {
#pragma unroll 1
  for (int it = 0; it < (1 << 20); it++) { if ((int)(ld_relaxed(p) - target) >= 0) return; }
  __trap();
}
__device__ __forceinline__ float4 ldg_l2(const float* p) {
  float4 v; asm volatile("ld.relaxed.gpu.global.v4.f32 {%0, %1, %2, %3}, [%4];" : "=f"(v.x), "=f"(v.y), "=f"(v.z), "=f"(v.w) : "l"(p) : "memory"); return v;
}
__device__ __forceinline__ float ldg_l2_f(const float* p) { float v; asm volatile("ld.relaxed.gpu.global.f32 %0, [%1];" : "=f"(v) : "l"(p) : "memory"); return v; }
__device__ __forceinline__ void sts64(uint32_t addr, float a, float b) { asm volatile("st.shared.v2.f32 [%0], {%1, %2};" :: "r"(addr), "f"(a), "f"(b) : "memory"); }
__device__ __forceinline__ void bulk_load(uint32_t dst, const void* src, uint32_t bytes, uint32_t bar) {
  asm volatile("cp.async.bulk.shared::cluster.global.mbarrier::complete_tx::bytes [%0], [%1], %2, [%3];" :: "r"(dst), "l"(src), "r"(bytes), "r"(bar) : "memory");
}
__device__ __forceinline__ void bulk_prefetch(const void* src, uint32_t bytes) {
  asm volatile("cp.async.bulk.prefetch.L2.global [%0], %1;" :: "l"(src), "r"(bytes) : "memory");
}
__device__ __forceinline__ void tma_store_2d(const CUtensorMap* tm, uint32_t src, int c0, int c1) {
  asm volatile("cp.async.bulk.tensor.2d.global.shared::cta.bulk_group [%0, {%2, %3}], [%1];" :: "l"(tm), "r"(src), "r"(c0), "r"(c1) : "memory");
}
__device__ __forceinline__ void bulk_store(void* dst, uint32_t src, uint32_t bytes) {
  asm volatile("cp.async.bulk.global.shared::cta.bulk_group [%0], [%1], %2;" :: "l"(dst), "r"(src), "r"(bytes) : "memory");
}
__device__ __forceinline__ void bulk_reduce_f32(void* dst, uint32_t src, uint32_t bytes) {
  asm volatile("cp.reduce.async.bulk.global.shared::cta.bulk_group.add.f32 [%0], [%1], %2;" :: "l"(dst), "r"(src), "r"(bytes) : "memory");
}
__device__ __forceinline__ void tma_load_3d(uint32_t dst, const CUtensorMap* tm, int c0, int c1, int c2, uint32_t bar) {
  asm volatile("cp.async.bulk.tensor.3d.shared::cluster.global.mbarrier::complete_tx::bytes [%0], [%1, {%3, %4, %5}], [%2];"
    :: "r"(dst), "l"(tm), "r"(bar), "r"(c0), "r"(c1), "r"(c2) : "memory");
}
__device__ __forceinline__ void cp_async16(uint32_t dst, const void* src) { asm volatile("cp.async.cg.shared.global [%0], [%1], 16;" :: "r"(dst), "l"(src) : "memory"); }
__device__ __forceinline__ void cp_async_commit() { asm volatile("cp.async.commit_group;" ::: "memory"); }
template <int N> __device__ __forceinline__ void cp_async_wait() { asm volatile("cp.async.wait_group %0;" :: "n"(N) : "memory"); }
__device__ __forceinline__ void prefetch_map(const CUtensorMap* tm) { asm volatile("prefetch.tensormap [%0];" :: "l"(tm) : "memory"); }
__device__ __forceinline__ void bulk_commit() { asm volatile("cp.async.bulk.commit_group;" ::: "memory"); }
__device__ __forceinline__ void bulk_wait0() { asm volatile("cp.async.bulk.wait_group 0;" ::: "memory"); }
__device__ __forceinline__ void bulk_wait0_read() { asm volatile("cp.async.bulk.wait_group.read 0;" ::: "memory"); }
__device__ __forceinline__ void mma16816(float& d0, float& d1, float& d2, float& d3, uint32_t a0, uint32_t a1, uint32_t a2, uint32_t a3, uint32_t b0, uint32_t b1) {
  asm volatile("mma.sync.aligned.m16n8k16.row.col.f32.bf16.bf16.f32 {%0, %1, %2, %3}, {%4, %5, %6, %7}, {%8, %9}, {%0, %1, %2, %3};"
    : "+f"(d0), "+f"(d1), "+f"(d2), "+f"(d3) : "r"(a0), "r"(a1), "r"(a2), "r"(a3), "r"(b0), "r"(b1));
}
__device__ __forceinline__ uint32_t hmul2(uint32_t a, uint32_t b) { uint32_t r; asm("mul.rn.bf16x2 %0, %1, %2;" : "=r"(r) : "r"(a), "r"(b)); return r; }
__device__ __forceinline__ uint32_t hfma2(uint32_t a, uint32_t b, uint32_t c) { uint32_t r; asm("fma.rn.bf16x2 %0, %1, %2, %3;" : "=r"(r) : "r"(a), "r"(b), "r"(c)); return r; }
__device__ __forceinline__ uint32_t hadd2(uint32_t a, uint32_t b) { uint32_t r; asm("add.rn.bf16x2 %0, %1, %2;" : "=r"(r) : "r"(a), "r"(b)); return r; }
__device__ __forceinline__ float sigmoidf_(float v) { return rcp(1.0f + ex2(v * -1.4426950408889634f)); }

__device__ __forceinline__ void hedgehog(const float (&p)[16], uint32_t (&phi)[16]) {
  float mx0 = p[0], mn0 = p[0], mx1 = p[2], mn1 = p[2];
#pragma unroll
  for (int j = 0; j < 4; j++) {
    mx0 = fmaxf(mx0, fmaxf(p[4 * j], p[4 * j + 1])); mn0 = fminf(mn0, fminf(p[4 * j], p[4 * j + 1]));
    mx1 = fmaxf(mx1, fmaxf(p[4 * j + 2], p[4 * j + 3])); mn1 = fminf(mn1, fminf(p[4 * j + 2], p[4 * j + 3]));
  }
#pragma unroll
  for (int o = 1; o <= 2; o <<= 1) {
    mx0 = fmaxf(mx0, __shfl_xor_sync(0xffffffffu, mx0, o)); mn0 = fminf(mn0, __shfl_xor_sync(0xffffffffu, mn0, o));
    mx1 = fmaxf(mx1, __shfl_xor_sync(0xffffffffu, mx1, o)); mn1 = fminf(mn1, __shfl_xor_sync(0xffffffffu, mn1, o));
  }
  float ep[16], en[16];
  float sp0 = 0.f, sn0 = 0.f, sp1 = 0.f, sn1 = 0.f;
#pragma unroll
  for (int j = 0; j < 4; j++) {
#pragma unroll
    for (int c = 0; c < 2; c++) {
      ep[4 * j + c] = ex2(p[4 * j + c] - mx0); en[4 * j + c] = ex2(mn0 - p[4 * j + c]);
      ep[4 * j + 2 + c] = ex2(p[4 * j + 2 + c] - mx1); en[4 * j + 2 + c] = ex2(mn1 - p[4 * j + 2 + c]);
      sp0 += ep[4 * j + c]; sn0 += en[4 * j + c]; sp1 += ep[4 * j + 2 + c]; sn1 += en[4 * j + 2 + c];
    }
  }
#pragma unroll
  for (int o = 1; o <= 2; o <<= 1) {
    sp0 += __shfl_xor_sync(0xffffffffu, sp0, o); sn0 += __shfl_xor_sync(0xffffffffu, sn0, o);
    sp1 += __shfl_xor_sync(0xffffffffu, sp1, o); sn1 += __shfl_xor_sync(0xffffffffu, sn1, o);
  }
  sp0 = rcp(sp0); sn0 = rcp(sn0); sp1 = rcp(sp1); sn1 = rcp(sn1);
#pragma unroll
  for (int j = 0; j < 4; j++) {
    phi[2 * j] = pack_bf16(ep[4 * j] * sp0, ep[4 * j + 1] * sp0);
    phi[2 * j + 1] = pack_bf16(ep[4 * j + 2] * sp1, ep[4 * j + 3] * sp1);
    phi[8 + 2 * j] = pack_bf16(en[4 * j + 1] * sn0, en[4 * j] * sn0);
    phi[8 + 2 * j + 1] = pack_bf16(en[4 * j + 3] * sn1, en[4 * j + 2] * sn1);
  }
}

__device__ __noinline__ void hedgehog_slow(float* buf, int n) {
#pragma unroll 1
  for (int u = 0; u < n; u++) {
    float p[16]; uint32_t phi[16];
#pragma unroll
    for (int i = 0; i < 16; i++) p[i] = buf[u * 16 + i];
    hedgehog(p, phi);
#pragma unroll
    for (int i = 0; i < 16; i++) buf[u * 16 + i] = __uint_as_float(phi[i]);
  }
}

__device__ __forceinline__ void store_phi_k(const uint32_t (&phi)[16], uint32_t a) {
#pragma unroll
  for (int jj = 0; jj < 4; jj++) stsm4(a ^ (jj << 5), phi[4 * jj], phi[4 * jj + 1], phi[4 * jj + 2], phi[4 * jj + 3]);
}
__device__ __forceinline__ void hand_over_smem(uint32_t bar, bool ok) {
  fence_async_smem();
  __syncwarp();
  if (elect_one() & ok) mbar_arrive(bar);
}
__device__ __noinline__ void redo_phi_k(float* buf, unsigned done, uint32_t pa, uint32_t bar) {
  hedgehog_slow(buf, 4);
#pragma unroll 1
  for (int u = 0; u < 4; u++) {
    if ((done >> u) & 1) continue;
    uint32_t phi[16];
#pragma unroll
    for (int i = 0; i < 16; i++) phi[i] = __float_as_uint(buf[u * 16 + i]);
    store_phi_k(phi, pa + (~u & 1) * 32768 + (u >> 1) * 4096);
    if (u >= 2) hand_over_smem(bar + (u - 2) * 8, true);
  }
}

__device__ __forceinline__ uint32_t dup_lo(uint32_t v) { uint32_t r; asm("{\n.reg .b16 l, h;\nmov.b32 {l, h}, %1;\nmov.b32 %0, {l, l};\n}" : "=r"(r) : "r"(v)); return r; }
__device__ __forceinline__ uint32_t dup_hi(uint32_t v) { uint32_t r; asm("{\n.reg .b16 l, h;\nmov.b32 {l, h}, %1;\nmov.b32 %0, {h, h};\n}" : "=r"(r) : "r"(v)); return r; }
struct HState { uint32_t a[16]; float s[5]; };
template <bool QD>
__device__ __forceinline__ void hedgehog_fast1(const float (&p)[16], HState& a) {
  float sm[8], m[8], r[8];
#pragma unroll
  for (int i = 0; i < 8; i++) {
    const float t0 = ex2(p[2 * i]), t1 = ex2(p[2 * i + 1]);
    a.a[i] = pack_bf16(t0, t1); sm[i] = t0 + t1; m[i] = t0 * t1;
  }
  if (QD) {
    float mq[4];
#pragma unroll
    for (int i = 0; i < 4; i++) {
      mq[i] = m[2 * i] * m[2 * i + 1];
      const float R = rcp(mq[i]);
      r[2 * i] = R * m[2 * i + 1]; r[2 * i + 1] = R * m[2 * i];
    }
    a.s[4] = (mq[0] + mq[1]) + (mq[2] + mq[3]);
  } else {
#pragma unroll
    for (int i = 0; i < 8; i++) r[i] = rcp(m[i]);
    a.s[4] = 0.f;
  }
#pragma unroll
  for (int i = 0; i < 4; i++) {
    const uint32_t rr = pack_bf16(r[2 * i], r[2 * i + 1]);
    a.a[8 + 2 * i] = hmul2(a.a[2 * i], dup_lo(rr)); a.a[9 + 2 * i] = hmul2(a.a[2 * i + 1], dup_hi(rr));
  }
#pragma unroll
  for (int c = 0; c < 2; c++) {
    a.s[2 * c] = (sm[c] + sm[2 + c]) + (sm[4 + c] + sm[6 + c]);
    a.s[2 * c + 1] = fmaf(r[6 + c], sm[6 + c], fmaf(r[4 + c], sm[4 + c], fmaf(r[2 + c], sm[2 + c], r[c] * sm[c])));
  }
}
template <bool NORM>
__device__ __forceinline__ bool hedgehog_fast2(const HState& a, uint32_t (&phi)[16], float& s0, float& s1) {
  float s[4] = {a.s[0], a.s[1], a.s[2], a.s[3]};
#pragma unroll
  for (int o = 1; o <= 2; o <<= 1)
#pragma unroll
    for (int i = 0; i < 4; i++) s[i] += __shfl_xor_sync(0xffffffffu, s[i], o);
  const bool ok = ((s[0] + s[1]) + (s[2] + s[3]) <= 7.2e16f) & (a.s[4] <= 1.3e36f);
  if (NORM) {
    const float R0 = rcp(s[0] * s[1]), R1 = rcp(s[2] * s[3]);
    const uint32_t n0 = pack_bf16(R0 * s[1], R0 * s[0]), n1 = pack_bf16(R1 * s[3], R1 * s[2]);
#pragma unroll
    for (int i = 0; i < 8; i++) { phi[i] = hmul2(a.a[i], dup_lo((i & 1) ? n1 : n0)); phi[8 + i] = hmul2(a.a[8 + i], dup_hi((i & 1) ? n1 : n0)); }
  } else {
    const uint32_t n = pack_bf16(s[0] * rcp(s[1]), s[2] * rcp(s[3]));
    s0 = s[0]; s1 = s[2];
#pragma unroll
    for (int i = 0; i < 8; i++) { phi[i] = a.a[i]; phi[8 + i] = hmul2(a.a[8 + i], (i & 1) ? dup_hi(n) : dup_lo(n)); }
  }
  return ok;
}
template <bool NORM>
__device__ __forceinline__ bool hedgehog_fast(const float (&p)[16], uint32_t (&phi)[16], float& s0, float& s1) {
  HState a;
  hedgehog_fast1<NORM ? QUAD : QUAD_Q>(p, a);
  return hedgehog_fast2<NORM>(a, phi, s0, s1);
}

template <int OFF>
__device__ __forceinline__ void pack_frags(const float (&acc)[96], uint32_t (&a)[16]) {
#pragma unroll
  for (int i = 0; i < 16; i++) a[i] = pack_bf16(acc[OFF + 2 * i], acc[OFF + 2 * i + 1]);
#pragma unroll
  for (int i = 0; i < 16; i++) asm volatile("" : "+r"(a[i]) :: "memory");
}
__device__ __forceinline__ void issue_feat(const uint32_t (&a)[16], float (&p0)[16], float (&p1)[16], uint32_t wphi) {
  wgmma_fence();
#pragma unroll
  for (int kk = 0; kk < 2; kk++) {
    wgmma_rs_n32<1, H64>(p0, a[4 * kk], a[4 * kk + 1], a[4 * kk + 2], a[4 * kk + 3], dlo(wphi + kk * 1024, 16), kk);
    wgmma_rs_n32<1, H64>(p1, a[8 + 4 * kk], a[8 + 4 * kk + 1], a[8 + 4 * kk + 2], a[8 + 4 * kk + 3], dlo(wphi + 2048 + kk * 1024, 16), kk);
  }
  wgmma_commit();
}
__device__ __forceinline__ void keep_alive(const uint32_t (&a)[16]) {
#pragma unroll
  for (int i = 0; i < 16; i++) asm volatile("" :: "r"(a[i]) : "memory");
}

__device__ __forceinline__ void fma8(float (&a)[8], float xv, const uint4& w) {
  a[0] = fmaf(xv, bf_lo(w.x), a[0]); a[1] = fmaf(xv, bf_hi(w.x), a[1]);
  a[2] = fmaf(xv, bf_lo(w.y), a[2]); a[3] = fmaf(xv, bf_hi(w.y), a[3]);
  a[4] = fmaf(xv, bf_lo(w.z), a[4]); a[5] = fmaf(xv, bf_hi(w.z), a[5]);
  a[6] = fmaf(xv, bf_lo(w.w), a[6]); a[7] = fmaf(xv, bf_hi(w.w), a[7]);
}

template <int J0, int J1>
__device__ __forceinline__ void stage_out(const float (&acc)[64], uint32_t xa) {
#pragma unroll
  for (int jj = J0; jj < J1; jj++)
    stsm4((xa ^ ((jj & 3) << 5)) + (jj >> 2) * 16384, pack_bf16(acc[8 * jj], acc[8 * jj + 1]), pack_bf16(acc[8 * jj + 2], acc[8 * jj + 3]),
          pack_bf16(acc[8 * jj + 4], acc[8 * jj + 5]), pack_bf16(acc[8 * jj + 6], acc[8 * jj + 7]));
}
__device__ __forceinline__ float lds_bf16(uint32_t addr) {
  unsigned short v; asm volatile("ld.shared.u16 %0, [%1];" : "=h"(v) : "r"(addr) : "memory"); return __uint_as_float((uint32_t)v << 16);
}
__device__ __noinline__ void redo_rows(const __nv_bfloat16* x, const __nv_bfloat16* wo, uint32_t sb, int b, int wq, uint32_t xa) {
  const int lane = threadIdx.x & 31, wi = (threadIdx.x >> 5) & 3, blk = (b >> 3) * 2 + wq, row0 = blk * 64 + wi * 16;
  const __nv_bfloat16 *pieces = g_o + (size_t)blk * 16 * 4096, *wo_cols = wo + (b & 7) * 128, *xrows = x + (size_t)row0 * D_ + (b & 7) * 128;
  const unsigned* done = g_z.done + (b & ~15);
  const uint32_t gate = sb + SM_GATE + (row0 & 255) * 2, upd = sb + SM_UPD;
  const int routed = (int)lds_u32(sb + SM_INFO + 4) - row0;
  int it = 0;
  while (!__all_sync(0xffffffffu, ld_acquire(done + (lane & 15)) != 0)) { if (++it > (1 << 20)) __trap(); }
  float acc[64];
  const int g = lane >> 2, q = lane & 3, r0 = wi * 16 + g;
#pragma unroll
  for (int i = 0; i < 32; i++) {
    const int r = g + (i & 1) * 8, c = (i >> 1) * 8 + q * 2;
    const uint32_t v = *reinterpret_cast<const uint32_t*>(xrows + (size_t)r * D_ + c);
    const float og = round_bf16(1.0f - lds_bf16(gate + r * 2));
    acc[2 * i] = og * bf_lo(v); acc[2 * i + 1] = og * bf_hi(v);
    if (r == routed) {
      const uint32_t u = lds_u32(upd + (c >> 6) * 2048 + (c & 63) * 2);
      acc[2 * i] += bf_lo(u); acc[2 * i + 1] += bf_hi(u);
    }
  }
#pragma unroll 1
  for (int ks = 0; ks < 64; ks++) {
    const unsigned* pc = reinterpret_cast<const unsigned*>(pieces + (ks >> 2) * 4096) + r0 * 32 + q;
    const int c0 = ((2 * (ks & 3)) ^ (r0 & 7)) * 4, c1 = ((2 * (ks & 3) + 1) ^ (r0 & 7)) * 4;
    const uint32_t a0 = ld_relaxed(pc + c0), a1 = ld_relaxed(pc + 256 + c0), a2 = ld_relaxed(pc + c1), a3 = ld_relaxed(pc + 256 + c1);
    const unsigned short* wp = reinterpret_cast<const unsigned short*>(wo_cols) + (size_t)(ks * 16 + 2 * q) * D_ + g;
#pragma unroll
    for (int nb = 0; nb < 16; nb++) {
      const uint32_t b0 = wp[nb * 8] | ((uint32_t)wp[nb * 8 + D_] << 16), b1 = wp[nb * 8 + 8 * D_] | ((uint32_t)wp[nb * 8 + 9 * D_] << 16);
      mma16816(acc[4 * nb], acc[4 * nb + 1], acc[4 * nb + 2], acc[4 * nb + 3], a0, a1, a2, a3, b0, b1);
    }
  }
  __syncwarp();
  stage_out<0, 8>(acc, xa);
}

__global__ void __cluster_dims__(2, 1, 1) __launch_bounds__(512, 1)
fused_kernel(const __grid_constant__ Maps maps, const __nv_bfloat16* __restrict__ x,
             const __nv_bfloat16* __restrict__ wo, const __nv_bfloat16* __restrict__ w_r, const __nv_bfloat16* __restrict__ gate_w) {
  extern __shared__ __align__(1024) uint8_t smem_raw[];
  if (threadIdx.x == 0) { prefetch_map(&maps.w); prefetch_map(&maps.x); }
  const int tid = threadIdx.x, warp = __shfl_sync(0xffffffffu, tid >> 5, 0), lane = tid & 31;
  const int rank = blockIdx.x & 1;
  const unsigned cl = blockIdx.x >> 1, hi = (cl - 36) * 37 >> 8, lo7 = cl - 36 - hi * 7;
  const bool r8 = cl < 36;
  const unsigned c4 = cl - 4, col = cl < 4 ? 15 : r8 ? c4 & 7 : 8 + lo7, pos = cl < 4 ? cl : r8 ? c4 >> 3 : hi;
  const int b = ((unsigned)(COLMAP >> (4 * col)) & 15) * 8 + pos * 2 + rank;
  const int e = EXPT == 12 ? 200 : blockIdx.x;
  const int tg = b >> 4, hp = b & 15;
  const int half = hp >> 3, ct = hp & 7;
  constexpr uint32_t SB0 = 1024;
  const uint32_t sb = SB0 + ((uint32_t)rank << 24);
  auto BAR = [&](int i) { return sb + SM_BAR + 8 * i; };
  auto load_stage = [&](int kt, int s, bool mc) {
    const uint32_t a = sb + SM_RA + s * A_BYTES, full = BAR(B_FULL + s);
    mbar_expect_tx(full, STAGE_BYTES);
    tma_load_3d(sb + SM_RB + s * B_BYTES, &maps.w, hp * 64, kt * 32, 0, full);
    if (mc) tma_load_2d_mc(a + rank * 8192, &maps.x, kt * 32, tg * 256 + rank * 128, full);
    else { tma_load_2d(a, &maps.x, kt * 32, tg * 256, full); tma_load_2d(a + 8192, &maps.x, kt * 32, tg * 256 + 128, full); }
  };
  auto slice_of = [&](int i) { const int t = i - 2 * ((unsigned)(i - 2) < (unsigned)(ct & 6)); return ((i >> 1) ? t : t ^ ct) ^ (half * 8); };
  auto load_b2 = [&](int i) {
    const int j = slice_of(i), sl = i + 4 - (i >= 3) * NB2 - (i >= 10) * NB2;
    mbar_expect_tx(BAR(B_FB2 + i), 16384);
    tma_load_3d(sb + SM_RB + sl * 16384, &maps.wo, 0, j * 64, ct * 2, BAR(B_FB2 + i));
  };
  auto load_xt = [&](int w) {
    mbar_expect_tx(BAR(B_XT + w), 16384);
    tma_load_2d(sb + SM_XT + w * 8192, &maps.xt, ct * 128, tg * 256 + half * 128 + w * 64, BAR(B_XT + w));
    tma_load_2d(sb + SM_XT + w * 8192 + 16384, &maps.xt, ct * 128 + 64, tg * 256 + half * 128 + w * 64, BAR(B_XT + w));
  };
  auto o_piece = [&](int hf, int mb, int j) { return g_o + (size_t)((((tg * 2 + hf) * 2 + mb) * 16 + j) * 4096); };

  if (blockIdx.x >= NCTA) {
    if (warp == 0 && blockIdx.x == NCTA) {
      if (smem_u32(smem_raw) != sb) __trap();
      const unsigned tag = (ld_relaxed(&g_bcast[0].y) + 1) & 0xfffu;
#pragma unroll 1
      for (int round = 0; round < 2; round++) {
        bool all;
        int it = 0;
        do {
          uint4 k;
          asm volatile("ld.relaxed.gpu.global.v4.u32 {%0, %1, %2, %3}, [%4];" : "=r"(k.x), "=r"(k.y), "=r"(k.z), "=r"(k.w) : "l"(g_key + round * NCTA + lane * 4) : "memory");
          all = __all_sync(0xffffffffu, (((k.x ^ tag) | (k.y ^ tag) | (k.z ^ tag) | (k.w ^ tag)) & 0xfffu) == 0);
          auto full = [&](unsigned m, int c) { return (m & 0xffff0000u) | ((127u - (lane * 4 + c)) << 4) | ((m >> 12) & 15u); };
          const unsigned val = __reduce_max_sync(0xffffffffu, max(max(full(k.x, 0), full(k.y, 1)), max(full(k.z, 2), full(k.w, 3))));
          asm volatile("{\n.reg .pred p;\nsetp.ne.u32 p, %3, 0;\n@p st.relaxed.gpu.global.v2.u32 [%0], {%1, %2};\n}"
                       :: "l"(g_bcast + round * 128 + (lane & 7) * 16), "r"(val), "r"(tag), "r"((uint32_t)(all && lane < 8)) : "memory");
          if (++it > (1 << 20)) __trap();
        } while (!all);
      }
    }
    return;
  }
  if (warp == 8) {
    if (elect_one()) {
      mbar_init(BAR(0), 1);
      if (NPRE > 1) { mbar_init(BAR(1), 1); mbar_init(BAR(2), 1); }
      if (NPRE > 0 && INIT_FENCE) fence_async_smem();
      TSTAMP(40);
      if (NPRE > 0) load_stage(0, 0, false);
      if (NPRE > 1) load_stage(1, 1, false);
      if (NPRE > 2) load_stage(2, 2, false);
      TSTAMP(41);
    }
  } else if (elect_one()) {
    const int i = 3 + warp - (warp > 8);
    mbar_init(BAR(i), i < B_EMPTY ? 1 : 4);
    if (NPRE < 2 && warp >= 14) mbar_init(BAR(warp - 13), 1);
    if (warp == 13) mbar_init(BAR(B_INIT), 3);
  }
  asm volatile("fence.mbarrier_init.release.cluster;" ::: "memory");
  __syncwarp();
  asm volatile("barrier.cluster.arrive.relaxed.aligned;" ::: "memory");
  auto cluster_wait = [&]() { asm volatile("barrier.cluster.wait.aligned;" ::: "memory"); };

  if (warp >= 12) {
    asm volatile("setmaxnreg.dec.sync.aligned.u32 40;");
    const int aw = warp - 12;
    cluster_wait();
    const unsigned old_gate = ld_relaxed(g_gate + b * 16 + aw * 4);
    const uint32_t zero = smem_u32(smem_raw) ^ sb;
    {
      float r[4], l[4];
#pragma unroll
      for (int t = 0; t < 4; t++) { r[t] = 0.f; l[t] = 0.f; }
      uint32_t xa = sb + SM_XR + aw * 1024 + lane * 8, wa = sb + SM_XR + 32768 + lane * 8;
#pragma unroll 1
      for (int i = 0; i < 8; i++) {
        if (!(i & 1)) mbar_wait(BAR(B_XR) + i * 4, 0);
        if (tid == 384 && i == 6) TSTAMP(30);
        uint2 wr = lds64(wa);
        const uint2 gw = lds64(wa + 2048);
        uint2 xv[4];
#pragma unroll
        for (int t = 0; t < 4; t++) xv[t] = lds64(xa + t * 256);
        xa += 4096; wa += 256;
        wr.x |= (xv[1].x | xv[2].x | xv[3].x) & zero;
        const float w0 = bf_lo(wr.x), w1 = bf_hi(wr.x), w2 = bf_lo(wr.y), w3 = bf_hi(wr.y);
#pragma unroll
        for (int t = 0; t < 4; t++) {
          const uint32_t p0 = hmul2(xv[t].x, gw.x), p1 = hmul2(xv[t].y, gw.y);
          r[t] = fmaf(bf_hi(xv[t].y), w3, fmaf(bf_lo(xv[t].y), w2, fmaf(bf_hi(xv[t].x), w1, fmaf(bf_lo(xv[t].x), w0, r[t]))));
          if (GATE_EXACT) l[t] += (bf_lo(p0) + bf_hi(p0)) + (bf_lo(p1) + bf_hi(p1));
          else l[t] = fmaf(bf_hi(xv[t].y), bf_hi(gw.y), fmaf(bf_lo(xv[t].y), bf_lo(gw.y), fmaf(bf_hi(xv[t].x), bf_hi(gw.x), fmaf(bf_lo(xv[t].x), bf_lo(gw.x), l[t]))));
        }
      }
      float u[4];
#pragma unroll
      for (int t = 0; t < 4; t++) u[t] = ((lane & 4) ? l[t] : r[t]) + __shfl_xor_sync(0xffffffffu, (lane & 4) ? r[t] : l[t], 4);
      const float v0 = ((lane & 1) ? u[1] : u[0]) + __shfl_xor_sync(0xffffffffu, (lane & 1) ? u[0] : u[1], 1);
      const float v1 = ((lane & 1) ? u[3] : u[2]) + __shfl_xor_sync(0xffffffffu, (lane & 1) ? u[2] : u[3], 1);
      float v = ((lane & 2) ? v1 : v0) + __shfl_xor_sync(0xffffffffu, (lane & 2) ? v0 : v1, 2);
      v += __shfl_xor_sync(0xffffffffu, v, 8);
      v += __shfl_xor_sync(0xffffffffu, v, 16);
      v = round_bf16(v);
      unsigned k = __float_as_uint(v) >> 16;
      k = (k & 0x8000u) ? (~k & 0xffffu) : (k | 0x8000u);
      k = __reduce_max_sync(0xffffffffu, lane < 4 ? (k << 4) | (15u - (aw * 4 + lane)) : 0u);
      if (lane == 0) sts_u32(sb + SM_KEYS + aw * 4, k);
      if ((lane >> 2) == 1) st_relaxed(g_gate + b * 16 + aw * 4 + (lane & 3), __float_as_uint(round_bf16(sigmoidf_(v))) | ((old_gate + 1) & 0xfffu));
      mbar_wait(BAR(B_INIT), 0);
    }
    if (tid == 384) { TSTAMP(31); GSTAMP(60); }
    fence_async_smem();
    __syncwarp();
    if (elect_one()) mbar_arrive(BAR(B_XRD));
    mbar_wait_bounded(BAR(B_XSEL), 0);
    if (tid == 384) TSTAMP(36);
    float ag[8];
#pragma unroll
    for (int i = 0; i < 8; i++) ag[i] = 0.f;
    if (e < NMOE) {
      const uint32_t lw = sb + SM_MOE + aw * 2048 + (lane >> 3) * 512 + (lane & 7) * 16;
      uint32_t lx = sb + SM_XSEL + aw * 32 + (lane >> 3) * 8, fb = BAR(B_MOE), wa = lw;
      bool got = false;
#pragma unroll 1
      for (int m = 0; m < 12; m++) {
#pragma unroll
        for (int c = 0; c < 2; c++) {
          if (!got) mbar_wait(fb + c * 8, (m >> 1) & 1);
          uint4 w0, w1, w2, w3;
          lds128x4(wa + c * 8192, w0, w1, w2, w3);
          uint2 xv = lds64(lx + c * 128);
          got = mbar_test(c ? fb ^ 16 : fb + 8, ((m + c) >> 1) & 1);
          const uint32_t dep = ((w0.x | w1.x | w2.x) | w3.x) & zero;
          xv.x |= dep;
          if (elect_one()) mbar_arrive(fb + dep + (B_MOEE - B_MOE + c) * 8);
          fma8(ag, bf_lo(xv.x), w0); fma8(ag, bf_hi(xv.x), w1); fma8(ag, bf_lo(xv.y), w2); fma8(ag, bf_hi(xv.y), w3);
        }
        fb ^= 16; wa = 2 * lw + 16384 - wa; lx += 256;
        if (m == (FFN_LOOP ? 15 : 7)) {
          int ln;
          asm volatile("mov.u32 %0, %%laneid;" : "=r"(ln));
#pragma unroll
          for (int i = 0; i < 4; i++) ag[i] = ((ln & 16) ? ag[4 + i] : ag[i]) + __shfl_xor_sync(0xffffffffu, (ln & 16) ? ag[i] : ag[4 + i], 16);
          const float v0 = ((ln & 8) ? ag[2] : ag[0]) + __shfl_xor_sync(0xffffffffu, (ln & 8) ? ag[0] : ag[2], 8);
          const float v1 = ((ln & 8) ? ag[3] : ag[1]) + __shfl_xor_sync(0xffffffffu, (ln & 8) ? ag[1] : ag[3], 8);
          const uint32_t own = (uint32_t)(ln & 4) << 22;
          asm volatile("st.async.shared::cluster.mbarrier::complete_tx::bytes.v2.f32 [%0], {%1, %2}, [%3];"
                       :: "r"(own + SB0 + SM_RED + rank * 512 + aw * 128 + (ln & 3) * 32 + (ln >> 3) * 8), "f"(v0), "f"(v1), "r"(own + SB0 + SM_BAR + 8 * B_H) : "memory");
          mbar_wait_bounded(BAR(B_H), 0);
          const uint32_t ra = sb + SM_RED + ln * 4;
          float gv = round_bf16((lds_f32(ra) + lds_f32(ra + 128)) + (lds_f32(ra + 256) + lds_f32(ra + 384)));
          const float uv = round_bf16((lds_f32(ra + 512) + lds_f32(ra + 640)) + (lds_f32(ra + 768) + lds_f32(ra + 896)));
          gv = round_bf16(gv * sigmoidf_(gv));
          lx = sb + SM_XSEL + aw * 32;
          asm volatile("st.shared.b16 [%0], %1;" :: "r"(lx + (ln >> 2) * 128 + (ln & 3) * 2), "h"(__bfloat16_as_ushort(__float2bfloat16_rn(gv * uv))) : "memory");
          __syncwarp();
#pragma unroll
          for (int i = 0; i < 8; i++) ag[i] = 0.f;
          if (tid == 384) TSTAMP(33);
        }
      }
      mbar_wait(BAR(B_RDY), 0);
#pragma unroll
      for (int j = 0; j < 3; j++)
        asm volatile("red.global.add.v4.f32 [%0], {%1, %2, %3, %4};" :: "l"(g_z.y + (e & (NY - 1)) * 2 * D_ + (j * 128 + aw * 32 + lane) * 4),
                     "f"(ag[3 * j]), "f"(ag[3 * j + 1]), "f"(j < 2 ? ag[3 * j + 2] : 0.f), "f"(1.0f) : "memory");
    }
    fence_async_smem();
    if (tid == 384) TSTAMP(34);
    bar_sync(4, 128);
    if (aw == 3) {
      const uint4 info = lds128(sb + SM_INFO);
      int it = 0;
      if ((info.y >> 7) == tg * 2 + half && EXPT != 12) {
        mbar_wait(BAR(B_RDY), 0);
        const float rs = round_bf16(sigmoidf_(__uint_as_float(info.z)));
        float y[9];
        do {
          __nanosleep(100);
#pragma unroll
          for (int i = 0; i < 9; i++) y[i] = 0.f;
#pragma unroll 1
          for (int c = lane >> 4; c < NY; c += 2) {
            const float* yp = g_z.y + c * 2 * D_ + (ct * 16 + (lane & 15)) * 4;
            const float4 a0 = ldg_l2(yp), a1 = ldg_l2(yp + 512), a2 = ldg_l2(yp + 1024);
            y[0] += a0.x; y[1] += a0.y; y[2] += a0.z; y[3] += a1.x; y[4] += a1.y; y[5] += a1.z; y[6] += a2.x; y[7] += a2.y;
            y[8] += a0.w + a1.w + a2.w;
          }
#pragma unroll
          for (int i = 0; i < 9; i++) y[i] += __shfl_xor_sync(0xffffffffu, y[i], 16);
          if (++it > (1 << 20)) __trap();
        } while (!__all_sync(0xffffffffu, y[8] == 3.f * NMOE));
        const int hw = lane >> 4;
        const uint2 xv = __ldg(reinterpret_cast<const uint2*>(x + (size_t)info.y * D_ + ct * 128) + (lane & 15) * 2 + hw);
        const float og = round_bf16(1.0f - lds_bf16(sb + SM_GATE + (info.y & 255) * 2));
        const uint32_t rs2 = pack_bf16(rs, rs);
        const uint32_t t0 = hadd2(xv.x, hmul2(pack_bf16(hw ? y[4] : y[0], hw ? y[5] : y[1]), rs2));
        const uint32_t t1 = hadd2(xv.y, hmul2(pack_bf16(hw ? y[6] : y[2], hw ? y[7] : y[3]), rs2));
        mbar_wait(BAR(B_OP), 0); mbar_wait(BAR(B_OP + 2), 0);
        sts64(sb + SM_UPD + (lane & 8) * 256 + (lane & 7) * 16 + hw * 8,
              __uint_as_float(pack_bf16(og * (bf_lo(t0) - bf_lo(xv.x)), og * (bf_hi(t0) - bf_hi(xv.x)))),
              __uint_as_float(pack_bf16(og * (bf_lo(t1) - bf_lo(xv.y)), og * (bf_hi(t1) - bf_hi(xv.y)))));
        fence_async_smem();
        __syncwarp();
        if (elect_one()) { mbar_arrive(BAR(B_Y)); TSTAMP(39); }
      }
    } else {
      if (aw == 0) mbar_wait(BAR(B_PHI), 0);
      if (elect_one()) load_b2(aw);
      if (aw) {
#pragma unroll 1
        for (int i = 0; i < 16; i++) {
          mbar_wait_bounded(BAR(B_FB2 + i), 0);
          if (i == 0) mbar_wait(BAR(B_OP + half * 2 + aw - 1), 0);
          if (elect_one()) mbar_expect_tx(BAR(B_F2 + (aw - 1) * 16 + i), i ? 8192 : 0);
        }
      }
    }
  } else if (warp >= 8) {
    asm volatile("setmaxnreg.dec.sync.aligned.u32 24;");
    cluster_wait();
    if (tid == 256) TSTAMP(58);
    if (warp != 8) {
      if (elect_one()) {
#pragma unroll 1
        for (int i = B_ST + warp - 9; i < NBAR; i += 3) mbar_init(BAR(i), bar_count(i) + (LEAD2 && i == B_F2 + 32 - LEAD2));
        asm volatile("fence.mbarrier_init.release.cluster;" ::: "memory");
      }
#pragma unroll
      for (int i = 0; i < (ZB + 1535) / 1536; i++) sts128(sb + SM_KVB + (i * 96 + tid - 288) * 16, make_uint4(0, 0, 0, 0));
      if (warp < 11) sts128(sb + SM_ONES + (tid - 288) * 16, make_uint4(0x3f803f80u, 0x3f803f80u, 0x3f803f80u, 0x3f803f80u));
      hand_over_smem(BAR(B_INIT), true);
      if (tid == 288) TSTAMP(57);
    }
    if (warp == 8) {
      int s = NPRE, ph = 1;
#pragma unroll 1
      for (int kt = NPRE; kt < KT; kt++) {
        mbar_wait_bounded(BAR(B_EMPTY + s), ph);
        if (elect_one()) {
          load_stage(kt, s, true);
          const unsigned xc = kt - XR_AFTER;
          if (xc < 4) {
            mbar_expect_tx(BAR(B_XR + xc), xc ? 8192 : 12288);
            tma_load_2d(sb + SM_XR + xc * 8192, &maps.xr, xc * 256, b * 16, BAR(B_XR + xc));
            tma_load_2d(sb + SM_XR + xc * 8192 + 4096, &maps.xr, xc * 256 + 128, b * 16, BAR(B_XR + xc));
            if (xc == 0) { bulk_load(sb + SM_XR + 32768, w_r, 2048, BAR(B_XR)); bulk_load(sb + SM_XR + 34816, gate_w, 2048, BAR(B_XR)); }
          }
          const int pg = kt - STAGES - PF_START + PF_OFF;
          if (pg >= (e < NMOE ? PF_OFF : 24) && pg < 26 && (EXPT != 3 || pg >= 24)) {
            const CUtensorMap* tm = &maps.tg + (pg < 16 ? (b & 1) : pg < 24 ? 2 : 3);
            const int c0 = pg < 16 ? (e >> 1) * 64 : 0, c1 = (pg < 16 ? pg : pg < 24 ? e * 8 + pg - 16 : b * 2 + pg - 24) * 64;
            asm volatile("cp.async.bulk.prefetch.tensor.2d.L2.global [%0, {%1, %2}];" :: "l"(tm), "r"(c0), "r"(c1) : "memory");
          }
        }
        if (++s == STAGES) { s = 0; ph ^= 1; }
      }
      mbar_wait(BAR(B_EMPTY + 1), 1);
#pragma unroll 1
      for (int i = 3; i < (XT_IN_A ? NB2 : 5); i++)
        if (elect_one()) { if (!XT_IN_A) load_xt(i - 3); load_b2(i); }
    } else if (warp == 9) {
      const unsigned tag = (ld_relaxed(g_key + b) + 1) & 0xfffu;
      if (elect_one()) {
        mbar_expect_tx(BAR(B_WPHI), 4096);
        tma_load_2d(sb + SM_WPHI, &maps.wphi, 0, hp * 64, BAR(B_WPHI));
      }
      mbar_wait(BAR(B_WPHI), 0);
#pragma unroll 1
      for (uint32_t ad = sb + SM_WPHI + lane * 16; ad < sb + SM_WPHI + 4096; ad += 512) {
        constexpr float L = 1.4426950408889634f;
        const uint4 w = lds128(ad);
        sts128(ad, make_uint4(pack_bf16(bf_lo(w.x) * L, bf_hi(w.x) * L), pack_bf16(bf_lo(w.y) * L, bf_hi(w.y) * L),
                              pack_bf16(bf_lo(w.z) * L, bf_hi(w.z) * L), pack_bf16(bf_lo(w.w) * L, bf_hi(w.w) * L)));
      }
      fence_async_smem();
      mbar_wait(BAR(B_XRD), 0);
      {
        const uint4 k = lds128(sb + SM_KEYS);
        if (lane == 0) st_relaxed(g_key + b, (max(max(k.x, k.y), max(k.z, k.w)) << 12) | tag);
      }
      const unsigned best = __shfl_sync(0xffffffffu, wait_tagged<KEY_SLEEP>(g_bcast + tg * 16, tag), 0);
      const unsigned idx = 2047u - (best & 0x7ffu);
      unsigned u = best >> 16;
      u = (u & 0x8000u) ? (u & 0x7fffu) : (~u & 0xffffu);
      if (elect_one()) {
        sts128(sb + SM_INFO, make_uint4(tag, idx, u << 16, 0));
        mbar_expect_tx(BAR(B_H), 1024);
        mbar_expect_tx(BAR(B_XSEL), 2048);
        bulk_load(sb + SM_XSEL, x + (size_t)idx * D_, 2048, BAR(B_XSEL));
        TSTAMP(32); GSTAMP(61);
        bulk_store(reinterpret_cast<char*>(&g_z) + b * ZB, sb + SM_KVB, ZB);
      }
      bulk_commit(); bulk_wait0();
      fence_gpu();
      __syncwarp();
      if (lane == 0) { st_relaxed(g_key + NCTA + b, tag); TSTAMP(42); }
      int it = 0;
#pragma unroll 1
      for (int c = 0; c < 2; c++) {
        uint4 gv;
        do {
          asm volatile("ld.relaxed.gpu.global.v4.u32 {%0, %1, %2, %3}, [%4];" : "=r"(gv.x), "=r"(gv.y), "=r"(gv.z), "=r"(gv.w)
                       : "l"(g_gate + tg * 256 + c * 128 + lane * 4) : "memory");
          if (++it > (1 << 20)) __trap();
        } while (!__all_sync(0xffffffffu, (((gv.x ^ tag) | (gv.y ^ tag) | (gv.z ^ tag) | (gv.w ^ tag)) & 0xfffu) == 0));
        sts64(sb + SM_GATE + c * 256 + lane * 8, __uint_as_float(__byte_perm(gv.x, gv.y, 0x7632)), __uint_as_float(__byte_perm(gv.z, gv.w, 0x7632)));
      }
      wait_tagged<200>(g_bcast + 128 + tg * 16, tag);
      __syncwarp();
      if (elect_one()) { mbar_arrive(BAR(B_RDY)); TSTAMP(43); }
    } else if (e < NMOE) {
      const int w = warp & 1;
      const CUtensorMap* tm = &maps.wg + rank;
      int c0 = (e >> 1) * 64, c1 = 0, c2 = 4 * w;
      uint32_t bar = BAR(B_MOE + w);
      mbar_wait(BAR(B_XRD), 0);
#pragma unroll 1
      for (int m = 0; m < 12; m++) {
        mbar_wait(bar + (B_MOEE - B_MOE) * 8, ((m >> 1) & 1) ^ 1);
        if (elect_one()) {
          mbar_expect_tx(bar, 8192);
          tma_load_3d(sb + SM_MOE + w * 8192 + (m & 1) * 16384, tm, c0, c1, c2, bar);
        }
        bar ^= 16;
        if (m < 7) c2 += 8; else c1 += 8;
        if (m == 7) { tm = &maps.wd; c0 = 0; c1 = e * 32 + w * 4; c2 = 0; }
      }
    }
    const int wi = warp - 8, st = tid - 256;
    bar_sync(5, 128);
    asm volatile("setmaxnreg.inc.sync.aligned.u32 " STR(REG_K) ";");
    {
      auto kv_half = [&](float (&d)[20], int h, int mb) {
#pragma unroll
        for (int i = 0; i < 8; i++)
          wgmma_ss_n40<1, 1, H128, H64>(d, dlo(SB0 + SM_PHIK + 32768, 16) - h * 2048 + (((i & 2) << 2) + (i & 4) + mb * 2 + (i & 1)) * 128,
                                        dlo(SB0 + SM_V, SM_ONES - SM_V) + (h * 16 + (i & 4) * 2 + mb * 4 + (i & 3)) * (64 - (64 << 16)), (mb | i) != 0);
      };
      auto kv_out = [&](float (&d)[20], int h) {
        fence_regs(d);
        float* dst = g_z.kv + (hp * 2 + h) * KVH + st * 2;
        const int q = lane & 3;
        uint32_t w[8];
#pragma unroll
        for (int i = 0; i < 8; i++) w[i] = pack_bf16(d[2 * i], d[2 * i + 1]);
#pragma unroll
        for (int c = 0; c < 4; c++)
          asm volatile("red.global.add.noftz.v2.bf16x2 [%0], {%1, %2};" :: "l"(dst + c * 256), "r"(w[2 * c]), "r"(q == c ? 0x3f80u : w[2 * c + 1]) : "memory");
        asm volatile("red.global.add.noftz.v2.bf16x2 [%0], {%1, %2};" :: "l"(dst + 1024), "r"((q & 2) ? ((q & 1) ? w[7] : w[5]) : ((q & 1) ? w[3] : w[1])),
                     "r"(q == 0 ? 0x3f80u : q == 1 ? pack_bf16(d[16], d[18]) : 0u) : "memory");
      };
#pragma unroll 1
      for (int h = 0; h < 2; h++) {
        float kv[20];
        mbar_wait_bounded(BAR(B_PHI + h), 0);
        if (st == 0) TSTAMP(23 + h);
        wgmma_fence();
        kv_half(kv, h, 0); kv_half(kv, h, 1);
        wgmma_commit();
        if (KV_BAR && h && wi < 2 && elect_one()) load_xt(wi);
        wgmma_wait<0>();
        if (st == 0) TSTAMP(21 + h);
        kv_out(kv, h);
        if (!KV_BAR) {
          bar_sync(5, 128);
          if (XT_IN_A && h == XT_H && wi < 2 && elect_one()) load_xt(wi);
        }
      }
      if (wi == 3 && elect_one()) mbar_arrive_cluster(BAR(B_PEER) ^ (1u << 24));
      if (st == 0) TSTAMP(13);
      const int f = wi * 16 + (lane & 15), sw = (f >> 1) & 3, chi = lane >> 4;
      uint2 v[10];
      const float* src = g_z.kv + hp * 2 * KVH + st * 2;
      const int q = lane & 3;
      { const unsigned c0 = clock32(); while (clock32() - c0 < KV_DELAY) {} }
      int it = 0;
      unsigned need = 0x3ff;
#pragma unroll
      for (int i = 0; i < 10; i++) v[i] = make_uint2(0, 0);
      do {
        if (++it > (1 << 20)) __trap();
        unsigned bad = 0;
        if (st == 0 && it == 1) TSTAMP(35);
#pragma unroll
        for (int i = 0; i < 10; i++)
          asm volatile("{\n.reg .pred p;\nsetp.ne.u32 p, %3, 0;\n@p ld.relaxed.gpu.global.v2.u32 {%0, %1}, [%2];\n}"
                       : "+r"(v[i].x), "+r"(v[i].y) : "l"(src + i * 256), "r"(need & (1u << i)) : "memory");
#pragma unroll
        for (int i = 0; i < 10; i++) bad |= (v[i].y != 0x4100u) << i;
        need = __reduce_or_sync(0xffffffffu, bad & ((0x21u << q) | (q ? 0u : 0x210u)));
        if (st == 0 && it == 1) TSTAMP(20);
      } while (need);
      uint32_t zz[2];
#pragma unroll
      for (int h = 0; h < 2; h++) {
        const uint2* w = v + h * 5;
        const uint32_t kb = sb + SM_KVB + h * 4096 + f * 64;
        zz[h] = __shfl_sync(0xffffffffu, w[4].y, (lane & 28) + 1);
        stsm4(kb + ((chi ^ sw) << 4), w[0].x, q == 0 ? w[4].x : w[0].y, w[1].x, q == 1 ? w[4].x : w[1].y);
        stsm4(kb + (((2 + chi) ^ sw) << 4), w[2].x, q == 2 ? w[4].x : w[2].y, w[3].x, q == 3 ? w[4].x : w[3].y);
      }
      stsm4(sb + SM_KVB + 8192 + f * 64 + ((chi ^ sw) << 4), zz[0], zz[0] >> 16, zz[1], zz[1] >> 16);
      fence_async_smem();
      __syncwarp();
      if (elect_one()) mbar_arrive(BAR(B_KVB));
    }
    {
      const int pm = wi >> 1;
      if (wi & 1) {
        const int hf = half ^ pm;
        mbar_wait(BAR(B_PEER), 0);
        mbar_wait_bounded(BAR(B_OP + hf * 2), 0);
        const unsigned c0 = clock32();
        while (clock32() - c0 < (unsigned)(pm ? LATE_DELAY + ct * LATE_STEP : (ct >> 2) * URG_STEP)) {}
        __syncwarp();
        auto to_partner = [&](int mb) {
          asm volatile("cp.async.bulk.shared::cluster.shared::cta.mbarrier::complete_tx::bytes [%0], [%1], 8192, [%2];"
                       :: "r"((sb ^ (1u << 24)) + SM_RA + mb * 8192), "r"(sb + SM_O + mb * 8192), "r"(BAR(B_F2 + mb * 16 + 1) ^ (1u << 24)) : "memory");
        };
        unsigned* hint = g_z.hint + (tg * 2 + hf) * 32 + hp;
        const int sz = pm ? LATE_SZ : 8192;
#pragma unroll 1
        for (int o = 0; o < 16384; o += sz) {
          const int mb = o >> 13;
          if (o == 8192) mbar_wait(BAR(B_OP + hf * 2 + 1), 0);
          if (elect_one()) bulk_store(reinterpret_cast<char*>(o_piece(hf, mb, hp)) + (o & 8191), sb + SM_O + pm * 16384 + o, sz);
          bulk_commit();
          if (pm == 0 && elect_one()) to_partner(mb);
          if (pm ? HINT_L == 0 : HINT_U == 0) bulk_wait0(); else if (pm ? HINT_L == 1 : HINT_U == 1) bulk_wait0_read();
          __syncwarp();
          if (((o + sz) & 8191) == 0 && lane == 0) { st_relaxed(hint + mb * 16, 1); TSTAMP((pm ? 37 : 15) + mb); }
        }
        bulk_wait0();
        __syncwarp();
        if (lane == 0) mbar_arrive(BAR(B_ST + pm));
        if (pm == 0) {
          if (lane < 2) mbar_arrive_cluster((lane << 24) + SB0 + SM_BAR + 8 * (B_GO + NA2));
          mbar_wait(BAR(B5_AFTER), 0);
#pragma unroll 1
          for (int i = XT_IN_A ? NB2 : 5; i < 16; i++) {
            mbar_wait(i < NB2 ? BAR(B_XTD) : BAR(B_DB + i - NB2), 0);
            if (elect_one()) load_b2(i);
          }
        } else {
          mbar_wait(BAR(B_ST), 0);
          fence_gpu();
          if (lane == 0) st_relaxed(g_z.done + b, 1);
        }
      } else if (pm) {
        const __nv_bfloat16* src = o_piece(half, rank, half * 8);
        uint32_t dst = sb + SM_RA + 16384 + rank * 8192;
        mbar_wait(BAR(B_PEER), 0);
#pragma unroll 1
        for (int i = 2; i < 16; i++) {
          if (i == (ct & 6) + 2) src += 2 * 4096;
          if (i == 8) src -= half * 16 * 4096;
          mbar_wait_bounded(BAR(B_GO + i), 0);
          if (elect_one()) {
            asm volatile("cp.async.bulk.shared::cluster.global.mbarrier::complete_tx::bytes.multicast::cluster [%0], [%1], 8192, [%2], %3;"
                         :: "r"(dst), "l"(src), "r"(BAR(B_F2 + rank * 16 + i)), "h"((uint16_t)3) : "memory");
            if (i == 2) TSTAMP(19);
          }
          src += 4096;
          dst += (i == 5 || i == 10) ? -4 * 16384 : 16384;
        }
      } else {
        const unsigned* flag = g_z.hint + (tg * 2 + half) * 32 + rank * 16 + slice_of(lane & 15);
        bool seen = lane < 2 || lane > 15;
        mbar_wait(BAR(B_OP + half * 2 + rank), 0);
        int it = 0;
        do {
          if (ld_relaxed(flag) != 0 && !seen) {
            mbar_arrive(BAR(B_GO) + lane * 8);
            seen = true;
          }
          if (++it > (1 << 20)) __trap();
        } while (!__all_sync(0xffffffffu, seen));
      }
    }
  } else {
    asm volatile("setmaxnreg.inc.sync.aligned.u32 224;");
    const int wg = warp >> 2, wi = warp & 3;
    cluster_wait();
    if (tid == 0) TSTAMP(59);
    float acc0[96], acc1[96];
    {
      int s = 0, ph = 0, sprev = 0;
#pragma unroll 1
      for (int kt = 0; kt < KT - STAGES; kt++) {
        mbar_wait(BAR(B_FULL + s), ph);
        if (kt == 0 && tid == 0) TSTAMP(1);
        if (tid == 0 && !(kt & 1)) TSTAMP(44 + kt / 2);
        const uint32_t da = dlo(SB0 + SM_RA, 16) + s * (A_BYTES >> 4) + wg * 512;
        const uint32_t db = dlo(SB0 + SM_RB, 4096) + s * (B_BYTES >> 4);
        wgmma_fence();
#pragma unroll
        for (int k = 0; k < 2; k++) {
          wgmma_ss_n192<0, 1, H64, H128>(acc0, da + k * 2, db + k * 128, (kt | k) != 0);
          wgmma_ss_n192<0, 1, H64, H128>(acc1, da + 256 + k * 2, db + k * 128, (kt | k) != 0);
        }
        wgmma_commit();
        wgmma_wait<1>();
        if (kt > 0 && wi < 2 && elect_one()) mbar_arrive_cluster((wi << 24) + SB0 + SM_BAR + 8 * (B_EMPTY + sprev));
        sprev = s;
        if (++s == STAGES) { s = 0; ph ^= 1; }
      }
#pragma unroll 1
      for (int kt = 0; kt < STAGES; kt++) {
        mbar_wait(BAR(B_FULL + s), ph);
        const uint32_t da = dlo(SB0 + SM_RA, 16) + s * (A_BYTES >> 4) + wg * 512;
        const uint32_t db = dlo(SB0 + SM_RB, 4096) + s * (B_BYTES >> 4);
        wgmma_fence();
        wgmma_ss_n192<0, 1, H64, H128>(acc0, da, db, 1);
        wgmma_ss_n192<0, 1, H64, H128>(acc0, da + 2, db + 128, 1);
        wgmma_commit();
        wgmma_wait<1>();
        if (kt == 0 && wi < 2 && elect_one()) mbar_arrive_cluster((wi << 24) + SB0 + SM_BAR + 8 * (B_EMPTY + 1));
        if (++s == STAGES) { s = 0; ph ^= 1; }
      }
      mbar_wait(BAR(B_RDY), 0);
    }
    const int trow = wg * 128 + wi * 16 + (lane & 15);
    const int chi = lane >> 4;
    uint32_t ak[16], aq[2][16];
    float p[4][16];
    auto catch_one = [&](int i) {
      const int s = (2 + (i >> 1)) % STAGES;
      wgmma_ss_n192<0, 1, H64, H128>(acc1, dlo(SB0 + SM_RA + s * A_BYTES + 4096 + (i & 1) * 32, 16) + wg * 512, dlo(SB0 + SM_RB + s * B_BYTES + (i & 1) * 2048, 4096), 1);
    };
    auto catch_up = [&](int s) { wgmma_fence(); catch_one(2 * s - 4); catch_one(2 * s - 3); wgmma_commit(); };
    auto store_v = [&](const float (&acc)[96], int mb) {
#pragma unroll
      for (int h = 0; h < 2; h++)
#pragma unroll
        for (int jj = 0; jj < 2; jj++) {
          const int o = 64 + h * 16 + jj * 8;
          stsm4(sb + SM_V + h * 16384 + (trow + mb * 64) * 64 + (((2 * jj + chi) ^ ((trow >> 1) & 3)) << 4),
                pack_bf16(acc[o], acc[o + 1]), pack_bf16(acc[o + 2], acc[o + 3]), pack_bf16(acc[o + 4], acc[o + 5]), pack_bf16(acc[o + 6], acc[o + 7]));
        }
    };
    const uint32_t pa = sb + SM_PHIK + (wi >> 1) * 16384 + wg * 8192 + (trow & 31) * 128 + ((chi ^ (trow & 7)) << 4);
    auto store_phi = [&](const uint32_t (&phi)[16], int h, int mb) { store_phi_k(phi, pa + (1 - h) * 32768 + mb * 4096); };
    auto hand_over = [&](int i, bool ok) { hand_over_smem(BAR(B_PHI + i), ok); };
    bool okk[3];
    {
      HState hs;
      uint32_t phi[16];
      float d0, d1;
      catch_up(2);
      wgmma_wait<1>();
      fence_regs(acc0);
      if (tid == 0) TSTAMP(2);
      store_v(acc0, 0);
      pack_frags<32>(acc0, ak);
      issue_feat(ak, p[0], p[1], SB0 + SM_WPHI);
      catch_up(3);
      pack_frags<0>(acc0, aq[0]);
      wgmma_wait<1>();
      fence_regs(p[0]); fence_regs(p[1]); keep_alive(ak);
      wgmma_fence();
#pragma unroll
      for (int i = 4; i < 4 + NFIRST; i++) catch_one(i);
      okk[0] = hedgehog_fast<true>(p[0], phi, d0, d1);
      store_phi(phi, 0, 0);
#pragma unroll
      for (int i = 4 + NFIRST; i < 12; i++) catch_one(i);
      wgmma_commit();
      okk[0] &= hedgehog_fast<true>(p[1], phi, d0, d1);
      store_phi(phi, 1, 0);
      if (tid == 0) TSTAMP(17);
      wgmma_wait<0>();
      fence_regs(acc1);
      if (tid == 0) TSTAMP(27);
      if (wi < 2 && elect_one()) mbar_arrive_cluster((wi << 24) + SB0 + SM_BAR + 8 * (B_EMPTY + 1));
      pack_frags<32>(acc1, ak);
      issue_feat(ak, p[2], p[3], SB0 + SM_WPHI);
      store_v(acc1, 1);
      pack_frags<0>(acc1, aq[1]);
      wgmma_wait<0>();
      fence_regs(p[2]); fence_regs(p[3]); keep_alive(ak);
      asm volatile("setmaxnreg.dec.sync.aligned.u32 " STR(REG_C) ";");
      if (tid == 0) TSTAMP(28);
      HState h2;
      hedgehog_fast1<QUAD>(p[2], hs);
      hedgehog_fast1<QUAD>(p[3], h2);
      okk[1] = __all_sync(0xffffffffu, okk[0] & hedgehog_fast2<true>(hs, phi, d0, d1));
      store_phi(phi, 0, 1);
      hand_over(0, okk[1]);
      h2.s[0] += lds_f32(sb + SM_INFO + 12);
      okk[2] = __all_sync(0xffffffffu, okk[0] & hedgehog_fast2<true>(h2, phi, d0, d1));
      store_phi(phi, 1, 1);
      hand_over(1, okk[2]);
    }
    if (__builtin_expect(!(okk[1] & okk[2]), 0)) {
      __align__(16) float buf[64];
#pragma unroll
      for (int i = 0; i < 64; i++) buf[i] = p[i >> 4][i & 15];
      redo_phi_k(buf, okk[1] * 5 + okk[2] * 10, pa, BAR(B_PHI));
    }
    if (wi == 0 && lane == 0) TSTAMP(wg ? 29 : 3);
    uint32_t pq[4][16];
    float sc[8];
    issue_feat(aq[0], p[0], p[1], SB0 + SM_WPHI);
    issue_feat(aq[1], p[2], p[3], SB0 + SM_WPHI);
    mbar_wait(BAR(Q_AFTER), 0);
    wgmma_wait<0>();
#pragma unroll
    for (int u = 0; u < 4; u++) fence_regs(p[u]);
    keep_alive(aq[0]); keep_alive(aq[1]);
    if (tid == 0) TSTAMP(4);
    {
      bool ok = true;
#pragma unroll
      for (int u = 0; u < 4; u++) ok &= hedgehog_fast<false>(p[u], pq[u], sc[2 * u], sc[2 * u + 1]);
      if (__builtin_expect(!__all_sync(0xffffffffu, ok), 0)) {
        __align__(16) float buf[64];
#pragma unroll
        for (int i = 0; i < 64; i++) buf[i] = p[i >> 4][i & 15];
        hedgehog_slow(buf, 4);
#pragma unroll
        for (int i = 0; i < 64; i++) pq[i >> 4][i & 15] = __float_as_uint(buf[i]);
#pragma unroll
        for (int i = 0; i < 8; i++) sc[i] = 1.0f;
      }
    }
    if (tid == 0) TSTAMP(5);
    float acc[64];
    const int wq = wg ^ half;
    const uint32_t xo = wq * 8192 + wi * 2048 + (lane & 15) * 128 + ((chi ^ (lane & 7)) << 4);
    const uint32_t ga = sb + SM_GATE + (half * 128 + wq * 64 + wi * 16) * 2 + (lane >> 2) * 2;
    mbar_wait(BAR(B_XT + wq), 0);
    float gt[4];
#pragma unroll
    for (int i = 0; i < 4; i++) gt[i] = lds_bf16(sb + SM_GATE + (wg * 128 + (i >> 1) * 64 + wi * 16 + (i & 1) * 8 + (lane >> 2)) * 2);
    const float g0 = lds_bf16(ga), g1 = lds_bf16(ga + 16);
    const unsigned routed = lds_u32(sb + SM_INFO + 4);
    const uint32_t par = lds_u32(sb + SM_INFO) & 1, tmask = (lane & 3) ? ~0u : ~1u, tbit = (lane & 3) ? 0u : par;
    mbar_wait(BAR(B_KVB), 0);
    if (tid == 0) TSTAMP(7);
    if (wg != half) mbar_wait(BAR(B_OP + half * 2 + O_YIELD - 1), 0);
    {
      float nd[4][20];
#pragma unroll
      for (int u = 0; u < 4; u++)
#pragma unroll
        for (int i = 0; i < 16; i++) asm volatile("" : "+r"(pq[u][i]) :: "memory");
      auto num = [&](int mb, int k0, int k1) {
#pragma unroll
        for (int kk = k0; kk < k1; kk++)
#pragma unroll
          for (int h = 0; h < 2; h++) {
            const int u = mb * 2 + h;
            wgmma_rs_n40<1, H64>(nd[u], pq[u][4 * kk], pq[u][4 * kk + 1], pq[u][4 * kk + 2], pq[u][4 * kk + 3],
                                 dlo(SB0 + SM_KVB + h * 4096 + kk * 1024, 8192 - h * 4096 + h * 16), kk != 0);
          }
        wgmma_commit();
      };
      wgmma_fence();
      num(0, 0, 4);
      if (O_OVL == 2) num(1, 0, 4);
#pragma unroll
      for (int mb = 0; mb < 2; mb++) {
        if (O_OVL == 2 && mb == 0) wgmma_wait<1>(); else wgmma_wait<0>();
        fence_regs(nd[2 * mb]); fence_regs(nd[2 * mb + 1]);
        if (O_OVL == 1 && mb == 0) { wgmma_fence(); num(1, 0, 4); }
        if (tid == 0 && mb == 0) TSTAMP(18);
#pragma unroll
        for (int h = 0; h < 2; h++) {
          const int u = mb * 2 + h;
          const float i0 = gt[2 * mb] * rcp(fmaf(sc[2 * u], 1e-6f, nd[u][16])), i1 = gt[2 * mb + 1] * rcp(fmaf(sc[2 * u + 1], 1e-6f, nd[u][18]));
#pragma unroll
          for (int jj = 0; jj < 2; jj++) {
            const int o = jj * 8;
            stsm4(sb + SM_O + (wg ^ half) * 16384 + ((trow & 63) + mb * 64) * 128 + (((h * 4 + 2 * jj + chi) ^ (trow & 7)) << 4),
                  (pack_bf16(nd[u][o] * i0, nd[u][o + 1] * i0) & tmask) | tbit, (pack_bf16(nd[u][o + 2] * i1, nd[u][o + 3] * i1) & tmask) | tbit,
                  pack_bf16(nd[u][o + 4] * i0, nd[u][o + 5] * i0), pack_bf16(nd[u][o + 6] * i1, nd[u][o + 7] * i1));
          }
        }
        fence_async_smem();
        __syncwarp();
        if (elect_one()) mbar_arrive(BAR(B_OP + wg * 2 + mb));
        if (!O_OVL && mb == 0) { wgmma_fence(); num(1, 0, 4); }
      }
#pragma unroll
      for (int u = 0; u < 4; u++)
#pragma unroll
        for (int i = 0; i < 16; i++) asm volatile("" :: "r"(pq[u][i]) : "memory");
    }
    if (tid == 0) TSTAMP(8);
    uint32_t stale = 0;
    {
      const uint32_t ca = sb - SB0 - (dlo(0, 16) << 4) + wi * 2048 + (lane >> 2) * 128 + ((((lane & 3) * 2) ^ (lane >> 2)) << 4);
      const uint32_t da_end = dlo(SB0 + SM_RA + NA2 * 16384, 16) + wq * 512, f_end = BAR(B_F2 + wq * 16 + 16);
      uint32_t da = da_end - 1024, db = dlo(SB0 + SM_RB + 4 * 16384, 8192), f = f_end - 128;
      uint32_t xs[32];
#pragma unroll
      for (int i = 0; i < 2; i++) {
        mbar_wait(f + i * 8, 0);
        wgmma_fence();
#pragma unroll
        for (int k = 0; k < 4; k++) wgmma_ss_n128<0, 1, H128, H128>(acc, da - i * 4096 + k * 2, db + i * 1024 + k * 128, (i | k) != 0);
        wgmma_commit();
        if (i == 0) {
#pragma unroll
          for (int jj = 0; jj < 8; jj++)
            ldsm4(((sb + SM_XT + xo) ^ ((jj & 3) << 5)) + (jj >> 2) * 16384, xs[4 * jj], xs[4 * jj + 1], xs[4 * jj + 2], xs[4 * jj + 3]);
          fence_async_smem();
          __syncwarp();
          if (elect_one()) mbar_arrive_cluster(((XT_IN_A ? wq : rank) << 24) + SB0 + SM_BAR + 8 * (XT_IN_A ? B_GO + 3 : B_XTD));
        }
      }
      const float og0 = round_bf16(1.0f - g0), og1 = round_bf16(1.0f - g1);
      da -= 3072; db += 2048; f += 16;
      wgmma_wait<0>();
      fence_regs(acc);
      uint32_t dn = SB0 + SM_BAR + (wi ? (wq << 24) + 8 * (B_GO + NA2) : (rank << 24) + 8 * B_DB);
      if (wi < 2 && elect_one()) mbar_arrive_cluster(dn);
#pragma unroll
      for (int i = 0; i < 32; i++) { acc[2 * i] = fmaf((i & 1) ? og1 : og0, bf_lo(xs[i]), acc[2 * i]); acc[2 * i + 1] = fmaf((i & 1) ? og1 : og0, bf_hi(xs[i]), acc[2 * i + 1]); }
      fence_regs(acc);
      bool got = false;
#pragma unroll 1
      do {
        if (!got) mbar_wait(f, 0);
        wgmma_fence();
        wgmma_ss_n128<0, 1, H128, H128>(acc, da, db, 1);
        const uint32_t ta = ca + (da << 4), t0 = lds_u32(ta), t1 = lds_u32(ta + 1024);
        got = mbar_test(f + 8, 0);
#pragma unroll
        for (int k = 1; k < 4; k++) wgmma_ss_n128<0, 1, H128, H128>(acc, da + k * 2, db + k * 128, 1);
        wgmma_commit();
        da += 1024; if (da == da_end) da -= NA2 * 1024;
        db += 1024; if (db == dlo(SB0 + SM_RB + NB2 * 16384, 8192)) db -= NB2 * 1024;
        f += 8;
        stale |= (t0 ^ par) | (t1 ^ par);
        if (LEAD2 && wq == 0 && wi == 2 && f == f_end - 8 * LEAD_AT && elect_one()) mbar_arrive(BAR(B_F2 + 32 - LEAD2));
        wgmma_wait<1>();
        dn += 8;
        if (wi < 2 && f <= f_end - 32 && elect_one()) mbar_arrive_cluster(dn);
      } while (f != f_end);
      if (__builtin_expect((routed >> 6) == tg * 4 + half * 2 + wq && EXPT != 12, 0)) {
        const unsigned r = (routed & 63) - wi * 16 - (lane >> 2);
        const uint32_t one = (lane & 3) ? 0u : 0x3f80u;
        mbar_wait_bounded(BAR(B_Y), 0);
        wgmma_fence();
        wgmma_rs_n128<1, H128>(acc, r == 0 ? one : 0u, r == 8 ? one : 0u, 0, 0, dlo(SB0 + SM_UPD, 2048), 1);
        wgmma_commit();
      }
      const uint32_t xa = sb + SM_RA + xo, xt = sb + SM_RA + wq * 8192 + wi * 2048;
      const int orow = tg * 256 + half * 128 + wq * 64 + wi * 16;
      const bool redo = __any_sync(0xffffffffu, stale & 1);
      wgmma_wait<0>();
      fence_regs(acc);
      if (wi == 0 && lane == 0) TSTAMP(wq ? 25 : 11);
      stage_out<0, 4>(acc, xa);
      fence_async_smem();
      __syncwarp();
      if (!redo && elect_one()) tma_store_2d(&maps.out, xt, ct * 128, orow);
      stage_out<4, 8>(acc, xa);
      if (__builtin_expect(redo, 0))
        redo_rows(x, wo, sb, b, wq, xa);
      fence_async_smem();
      __syncwarp();
      if (elect_one()) {
        tma_store_2d(&maps.out, xt + 16384, ct * 128 + 64, orow);
        if (redo) tma_store_2d(&maps.out, xt, ct * 128, orow);
      }
      bulk_commit();
      bulk_wait0_read();
    }
  }
}

typedef CUresult (*PFN_encodeTiled)(CUtensorMap*, CUtensorMapDataType, cuuint32_t, void*, const cuuint64_t*, const cuuint64_t*,
                                    const cuuint32_t*, const cuuint32_t*, CUtensorMapInterleave, CUtensorMapSwizzle,
                                    CUtensorMapL2promotion, CUtensorMapFloatOOBfill);
static void make_map(PFN_encodeTiled fn, CUtensorMap* m, const void* ptr, uint64_t rows, uint64_t cols, uint32_t brows, uint32_t bcols,
                     CUtensorMapSwizzle sw, CUtensorMapL2promotion prom) {
  cuuint64_t dims[2] = {cols, rows}; cuuint64_t strides[1] = {cols * 2}; cuuint32_t box[2] = {bcols, brows}; cuuint32_t es[2] = {1, 1};
  fn(m, CU_TENSOR_MAP_DATA_TYPE_BFLOAT16, 2, const_cast<void*>(ptr), dims, strides, box, es, CU_TENSOR_MAP_INTERLEAVE_NONE, sw, prom,
     CU_TENSOR_MAP_FLOAT_OOB_FILL_NONE);
}

extern "C" void kernel_launch(void* const* d_in, const int* in_sizes, int n_in, void* d_out, int out_size) {
  const __nv_bfloat16* x = (const __nv_bfloat16*)d_in[0];
  const __nv_bfloat16* wqkv = (const __nv_bfloat16*)d_in[1];
  const __nv_bfloat16* wphi = (const __nv_bfloat16*)d_in[2];
  const __nv_bfloat16* wo = (const __nv_bfloat16*)d_in[3];
  const __nv_bfloat16* w_r = (const __nv_bfloat16*)d_in[5];
  const __nv_bfloat16* w_gate = (const __nv_bfloat16*)d_in[6];
  const __nv_bfloat16* w_up = (const __nv_bfloat16*)d_in[7];
  const __nv_bfloat16* w_down = (const __nv_bfloat16*)d_in[8];
  const __nv_bfloat16* gate_w = (const __nv_bfloat16*)d_in[9];
  void* fp = nullptr; cudaDriverEntryPointQueryResult qr;
  cudaGetDriverEntryPoint("cuTensorMapEncodeTiled", &fp, cudaEnableDefault, &qr);
  PFN_encodeTiled fn = (PFN_encodeTiled)fp;
  Maps m;
  const CUtensorMapL2promotion P128 = CU_TENSOR_MAP_L2_PROMOTION_L2_128B;
  make_map(fn, &m.x, x, S_, D_, 128, 32, CU_TENSOR_MAP_SWIZZLE_64B, P128);
  {
    cuuint64_t dims[3] = {D_, D_, 3}; cuuint64_t strides[2] = {3 * D_ * 2, D_ * 2}; cuuint32_t box[3] = {64, 32, 3}; cuuint32_t es[3] = {1, 1, 1};
    fn(&m.w, CU_TENSOR_MAP_DATA_TYPE_BFLOAT16, 3, (void*)wqkv, dims, strides, box, es, CU_TENSOR_MAP_INTERLEAVE_NONE,
       CU_TENSOR_MAP_SWIZZLE_128B, P128, CU_TENSOR_MAP_FLOAT_OOB_FILL_NONE);
  }
  {
    cuuint64_t dims[3] = {64, D_, 16}; cuuint64_t strides[2] = {D_ * 2, 128}; cuuint32_t box[3] = {64, 64, 2}; cuuint32_t es[3] = {1, 1, 1};
    fn(&m.wo, CU_TENSOR_MAP_DATA_TYPE_BFLOAT16, 3, (void*)wo, dims, strides, box, es, CU_TENSOR_MAP_INTERLEAVE_NONE,
       CU_TENSOR_MAP_SWIZZLE_128B, P128, CU_TENSOR_MAP_FLOAT_OOB_FILL_NONE);
  }
  make_map(fn, &m.wphi, wphi, 1024, 32, 64, 32, CU_TENSOR_MAP_SWIZZLE_64B, P128);
  for (int i = 0; i < 3; i++) {
    cuuint64_t dims[3] = {i < 2 ? (cuuint64_t)F_ : 64, i < 2 ? (cuuint64_t)16 : F_, i < 2 ? (cuuint64_t)64 : 16};
    cuuint64_t strides[2] = {i < 2 ? (cuuint64_t)F_ * 2 : D_ * 2, i < 2 ? (cuuint64_t)F_ * 32 : 128};
    cuuint32_t box[3] = {64, i < 2 ? 16u : 4u, i < 2 ? 4u : 16u}; cuuint32_t es[3] = {1, 1, 1};
    fn(&m.wg + i, CU_TENSOR_MAP_DATA_TYPE_BFLOAT16, 3, (void*)(i == 0 ? w_gate : i == 1 ? w_up : w_down), dims, strides, box, es,
       CU_TENSOR_MAP_INTERLEAVE_NONE, CU_TENSOR_MAP_SWIZZLE_NONE, P128, CU_TENSOR_MAP_FLOAT_OOB_FILL_NONE);
  }
  make_map(fn, &m.xt, x, S_, D_, 64, 64, CU_TENSOR_MAP_SWIZZLE_128B, P128);
  make_map(fn, &m.out, d_out, S_, D_, 16, 64, CU_TENSOR_MAP_SWIZZLE_128B, P128);
  make_map(fn, &m.xr, x, S_, D_, 16, 128, CU_TENSOR_MAP_SWIZZLE_NONE, P128);
  make_map(fn, &m.tg, w_gate, D_, F_, 64, 64, CU_TENSOR_MAP_SWIZZLE_NONE, P128);
  make_map(fn, &m.tu, w_up, D_, F_, 64, 64, CU_TENSOR_MAP_SWIZZLE_NONE, P128);
  make_map(fn, &m.td, w_down, F_ * 16, 64, 64, 64, CU_TENSOR_MAP_SWIZZLE_NONE, P128);
  make_map(fn, &m.to, wo, D_ * 16, 64, 64, 64, CU_TENSOR_MAP_SWIZZLE_NONE, P128);
  cudaFuncSetAttribute(fused_kernel, cudaFuncAttributeMaxDynamicSharedMemorySize, SM_TOTAL);
  fused_kernel<<<NCTA + 2, 512, SM_TOTAL>>>(m, x, wo, w_r, gate_w);
}
```

```cpp
#include <cuda_runtime.h>
#include <cuda_bf16.h>
#include <cuda.h>
#include <stdint.h>

__device__ __forceinline__ uint32_t smem_u32(const void* p) { return (uint32_t)__cvta_generic_to_shared(p); }
__device__ __forceinline__ void mbar_init(uint32_t bar, uint32_t cnt) { asm volatile("mbarrier.init.shared::cta.b64 [%0], %1;" :: "r"(bar), "r"(cnt) : "memory"); }
__device__ __forceinline__ void mbar_expect_tx(uint32_t bar, uint32_t bytes) { asm volatile("mbarrier.arrive.expect_tx.shared::cta.b64 _, [%0], %1;" :: "r"(bar), "r"(bytes) : "memory"); }
__device__ __forceinline__ void mbar_arrive(uint32_t bar) { asm volatile("mbarrier.arrive.shared::cta.b64 _, [%0];" :: "r"(bar) : "memory"); }
__device__ __forceinline__ bool mbar_try_wait(uint32_t bar, uint32_t parity) {
  uint32_t ok;
  asm volatile("{\n.reg .pred p;\nmbarrier.try_wait.parity.shared::cta.b64 p, [%1], %2;\nselp.u32 %0, 1, 0, p;\n}" : "=r"(ok) : "r"(bar), "r"(parity) : "memory");
  return ok;
}
__device__ __forceinline__ bool mbar_test(uint32_t bar, uint32_t parity) {
  uint32_t ok;
  asm volatile("{\n.reg .pred p;\nmbarrier.test_wait.parity.shared::cta.b64 p, [%1], %2;\nselp.u32 %0, 1, 0, p;\n}" : "=r"(ok) : "r"(bar), "r"(parity) : "memory");
  return ok;
}
__device__ __forceinline__ void mbar_wait(uint32_t bar, uint32_t parity) {
  asm volatile("{\n.reg .pred p;\nWAIT: mbarrier.try_wait.parity.shared::cta.b64 p, [%0], %1;\n@!p bra.uni WAIT;\n}" :: "r"(bar), "r"(parity) : "memory");
}
__device__ __forceinline__ void mbar_wait_bounded(uint32_t bar, uint32_t parity) {
#pragma unroll 1
  for (int it = 0; it < (1 << 22); it++) { if (mbar_try_wait(bar, parity)) return; }
  __trap();
}
__device__ __forceinline__ void tma_load_2d(uint32_t dst, const CUtensorMap* tm, int c0, int c1, uint32_t bar) {
  asm volatile("cp.async.bulk.tensor.2d.shared::cluster.global.mbarrier::complete_tx::bytes [%0], [%1, {%3, %4}], [%2];"
    :: "r"(dst), "l"(tm), "r"(bar), "r"(c0), "r"(c1) : "memory");
}
__device__ __forceinline__ void tma_load_2d_mc(uint32_t dst, const CUtensorMap* tm, int c0, int c1, uint32_t bar) {
  asm volatile("cp.async.bulk.tensor.2d.shared::cluster.global.mbarrier::complete_tx::bytes.multicast::cluster [%0], [%1, {%3, %4}], [%2], %5;"
    :: "r"(dst), "l"(tm), "r"(bar), "r"(c0), "r"(c1), "h"((uint16_t)3) : "memory");
}
__device__ __forceinline__ void mbar_arrive_cluster(uint32_t bar) { asm volatile("mbarrier.arrive.shared::cluster.b64 _, [%0];" :: "r"(bar) : "memory"); }
__device__ __forceinline__ void wgmma_fence() { asm volatile("wgmma.fence.sync.aligned;" ::: "memory"); }
__device__ __forceinline__ void wgmma_commit() { asm volatile("wgmma.commit_group.sync.aligned;" ::: "memory"); }
template <int N> __device__ __forceinline__ void wgmma_wait() { asm volatile("wgmma.wait_group.sync.aligned %0;" :: "n"(N) : "memory"); }
template <int N> __device__ __forceinline__ void fence_regs(float (&d)[N]) {
#pragma unroll
  for (int i = 0; i < N; i++) asm volatile("" : "+f"(d[i]) :: "memory");
}
__host__ __device__ constexpr uint32_t dlo(uint32_t addr, uint32_t lbo) { return (addr >> 4) | ((lbo >> 4) << 16); }
constexpr uint32_t H128 = (1024 >> 4) | (1u << 30);
constexpr uint32_t H64 = (512 >> 4) | (2u << 30);

template <int TA, int TB, uint32_t HA, uint32_t HB>
__device__ __forceinline__ void wgmma_ss_n192(float (&d)[96], uint32_t da, uint32_t db, int scale_d) {
  asm volatile("{\n.reg .pred p;\n.reg .b64 da, db;\nsetp.ne.b32 p, %98, 0;\nmov.b64 da, {%96, %101};\nmov.b64 db, {%97, %102};\n"
    "wgmma.mma_async.sync.aligned.m64n192k16.f32.bf16.bf16 {%0, %1, %2, %3, %4, %5, %6, %7, %8, %9, %10, %11, %12, %13, %14, %15, %16, %17, %18, %19, %20, %21, %22, %23, %24, %25, %26, %27, %28, %29, %30, %31, %32, %33, %34, %35, %36, %37, %38, %39, %40, %41, %42, %43, %44, %45, %46, %47, %48, %49, %50, %51, %52, %53, %54, %55, %56, %57, %58, %59, %60, %61, %62, %63, %64, %65, %66, %67, %68, %69, %70, %71, %72, %73, %74, %75, %76, %77, %78, %79, %80, %81, %82, %83, %84, %85, %86, %87, %88, %89, %90, %91, %92, %93, %94, %95}, da, db, p, 1, 1, %99, %100;\n}\n"
    : "+f"(d[0]), "+f"(d[1]), "+f"(d[2]), "+f"(d[3]), "+f"(d[4]), "+f"(d[5]), "+f"(d[6]), "+f"(d[7]), "+f"(d[8]), "+f"(d[9]), "+f"(d[10]), "+f"(d[11]), "+f"(d[12]), "+f"(d[13]), "+f"(d[14]), "+f"(d[15]), "+f"(d[16]), "+f"(d[17]), "+f"(d[18]), "+f"(d[19]), "+f"(d[20]), "+f"(d[21]), "+f"(d[22]), "+f"(d[23]), "+f"(d[24]), "+f"(d[25]), "+f"(d[26]), "+f"(d[27]), "+f"(d[28]), "+f"(d[29]), "+f"(d[30]), "+f"(d[31]), "+f"(d[32]), "+f"(d[33]), "+f"(d[34]), "+f"(d[35]), "+f"(d[36]), "+f"(d[37]), "+f"(d[38]), "+f"(d[39]), "+f"(d[40]), "+f"(d[41]), "+f"(d[42]), "+f"(d[43]), "+f"(d[44]), "+f"(d[45]), "+f"(d[46]), "+f"(d[47]), "+f"(d[48]), "+f"(d[49]), "+f"(d[50]), "+f"(d[51]), "+f"(d[52]), "+f"(d[53]), "+f"(d[54]), "+f"(d[55]), "+f"(d[56]), "+f"(d[57]), "+f"(d[58]), "+f"(d[59]), "+f"(d[60]), "+f"(d[61]), "+f"(d[62]), "+f"(d[63]), "+f"(d[64]), "+f"(d[65]), "+f"(d[66]), "+f"(d[67]), "+f"(d[68]), "+f"(d[69]), "+f"(d[70]), "+f"(d[71]), "+f"(d[72]), "+f"(d[73]), "+f"(d[74]), "+f"(d[75]), "+f"(d[76]), "+f"(d[77]), "+f"(d[78]), "+f"(d[79]), "+f"(d[80]), "+f"(d[81]), "+f"(d[82]), "+f"(d[83]), "+f"(d[84]), "+f"(d[85]), "+f"(d[86]), "+f"(d[87]), "+f"(d[88]), "+f"(d[89]), "+f"(d[90]), "+f"(d[91]), "+f"(d[92]), "+f"(d[93]), "+f"(d[94]), "+f"(d[95])
    : "r"(da), "r"(db), "r"(scale_d), "n"(TA), "n"(TB), "n"(HA), "n"(HB));
}

template <int TA, int TB, uint32_t HA, uint32_t HB>
__device__ __forceinline__ void wgmma_ss_n128(float (&d)[64], uint32_t da, uint32_t db, int scale_d) {
  asm volatile("{\n.reg .pred p;\n.reg .b64 da, db;\nsetp.ne.b32 p, %66, 0;\nmov.b64 da, {%64, %69};\nmov.b64 db, {%65, %70};\n"
    "wgmma.mma_async.sync.aligned.m64n128k16.f32.bf16.bf16 {%0, %1, %2, %3, %4, %5, %6, %7, %8, %9, %10, %11, %12, %13, %14, %15, %16, %17, %18, %19, %20, %21, %22, %23, %24, %25, %26, %27, %28, %29, %30, %31, %32, %33, %34, %35, %36, %37, %38, %39, %40, %41, %42, %43, %44, %45, %46, %47, %48, %49, %50, %51, %52, %53, %54, %55, %56, %57, %58, %59, %60, %61, %62, %63}, da, db, p, 1, 1, %67, %68;\n}\n"
    : "+f"(d[0]), "+f"(d[1]), "+f"(d[2]), "+f"(d[3]), "+f"(d[4]), "+f"(d[5]), "+f"(d[6]), "+f"(d[7]), "+f"(d[8]), "+f"(d[9]), "+f"(d[10]), "+f"(d[11]), "+f"(d[12]), "+f"(d[13]), "+f"(d[14]), "+f"(d[15]), "+f"(d[16]), "+f"(d[17]), "+f"(d[18]), "+f"(d[19]), "+f"(d[20]), "+f"(d[21]), "+f"(d[22]), "+f"(d[23]), "+f"(d[24]), "+f"(d[25]), "+f"(d[26]), "+f"(d[27]), "+f"(d[28]), "+f"(d[29]), "+f"(d[30]), "+f"(d[31]), "+f"(d[32]), "+f"(d[33]), "+f"(d[34]), "+f"(d[35]), "+f"(d[36]), "+f"(d[37]), "+f"(d[38]), "+f"(d[39]), "+f"(d[40]), "+f"(d[41]), "+f"(d[42]), "+f"(d[43]), "+f"(d[44]), "+f"(d[45]), "+f"(d[46]), "+f"(d[47]), "+f"(d[48]), "+f"(d[49]), "+f"(d[50]), "+f"(d[51]), "+f"(d[52]), "+f"(d[53]), "+f"(d[54]), "+f"(d[55]), "+f"(d[56]), "+f"(d[57]), "+f"(d[58]), "+f"(d[59]), "+f"(d[60]), "+f"(d[61]), "+f"(d[62]), "+f"(d[63])
    : "r"(da), "r"(db), "r"(scale_d), "n"(TA), "n"(TB), "n"(HA), "n"(HB));
}

template <int TA, int TB, uint32_t HA, uint32_t HB>
__device__ __forceinline__ void wgmma_ss_n40(float (&d)[20], uint32_t da, uint32_t db, int scale_d) {
  asm volatile("{\n.reg .pred p;\n.reg .b64 da, db;\nsetp.ne.b32 p, %22, 0;\nmov.b64 da, {%20, %25};\nmov.b64 db, {%21, %26};\n"
    "wgmma.mma_async.sync.aligned.m64n40k16.f32.bf16.bf16 {%0, %1, %2, %3, %4, %5, %6, %7, %8, %9, %10, %11, %12, %13, %14, %15, %16, %17, %18, %19}, da, db, p, 1, 1, %23, %24;\n}\n"
    : "+f"(d[0]), "+f"(d[1]), "+f"(d[2]), "+f"(d[3]), "+f"(d[4]), "+f"(d[5]), "+f"(d[6]), "+f"(d[7]), "+f"(d[8]), "+f"(d[9]), "+f"(d[10]), "+f"(d[11]), "+f"(d[12]), "+f"(d[13]), "+f"(d[14]), "+f"(d[15]), "+f"(d[16]), "+f"(d[17]), "+f"(d[18]), "+f"(d[19])
    : "r"(da), "r"(db), "r"(scale_d), "n"(TA), "n"(TB), "n"(HA), "n"(HB));
}

template <int TB, uint32_t HB>
__device__ __forceinline__ void wgmma_rs_n32(float (&d)[16], uint32_t a0, uint32_t a1, uint32_t a2, uint32_t a3, uint32_t db, int scale_d) {
  asm volatile("{\n.reg .pred p;\n.reg .b64 db;\nsetp.ne.b32 p, %21, 0;\nmov.b64 db, {%20, %23};\n"
    "wgmma.mma_async.sync.aligned.m64n32k16.f32.bf16.bf16 {%0, %1, %2, %3, %4, %5, %6, %7, %8, %9, %10, %11, %12, %13, %14, %15}, {%16, %17, %18, %19}, db, p, 1, 1, %22;\n}\n"
    : "+f"(d[0]), "+f"(d[1]), "+f"(d[2]), "+f"(d[3]), "+f"(d[4]), "+f"(d[5]), "+f"(d[6]), "+f"(d[7]), "+f"(d[8]), "+f"(d[9]), "+f"(d[10]), "+f"(d[11]), "+f"(d[12]), "+f"(d[13]), "+f"(d[14]), "+f"(d[15])
    : "r"(a0), "r"(a1), "r"(a2), "r"(a3), "r"(db), "r"(scale_d), "n"(TB), "n"(HB));
}

template <int TB, uint32_t HB>
__device__ __forceinline__ void wgmma_rs_n40(float (&d)[20], uint32_t a0, uint32_t a1, uint32_t a2, uint32_t a3, uint32_t db, int scale_d) {
  asm volatile("{\n.reg .pred p;\n.reg .b64 db;\nsetp.ne.b32 p, %25, 0;\nmov.b64 db, {%24, %27};\n"
    "wgmma.mma_async.sync.aligned.m64n40k16.f32.bf16.bf16 {%0, %1, %2, %3, %4, %5, %6, %7, %8, %9, %10, %11, %12, %13, %14, %15, %16, %17, %18, %19}, {%20, %21, %22, %23}, db, p, 1, 1, %26;\n}\n"
    : "+f"(d[0]), "+f"(d[1]), "+f"(d[2]), "+f"(d[3]), "+f"(d[4]), "+f"(d[5]), "+f"(d[6]), "+f"(d[7]), "+f"(d[8]), "+f"(d[9]), "+f"(d[10]), "+f"(d[11]), "+f"(d[12]), "+f"(d[13]), "+f"(d[14]), "+f"(d[15]), "+f"(d[16]), "+f"(d[17]), "+f"(d[18]), "+f"(d[19])
    : "r"(a0), "r"(a1), "r"(a2), "r"(a3), "r"(db), "r"(scale_d), "n"(TB), "n"(HB));
}

template <int TB, uint32_t HB>
__device__ __forceinline__ void wgmma_rs_n128(float (&d)[64], uint32_t a0, uint32_t a1, uint32_t a2, uint32_t a3, uint32_t db, int scale_d) {
  asm volatile("{\n.reg .pred p;\n.reg .b64 db;\nsetp.ne.b32 p, %69, 0;\nmov.b64 db, {%68, %71};\n"
    "wgmma.mma_async.sync.aligned.m64n128k16.f32.bf16.bf16 {%0, %1, %2, %3, %4, %5, %6, %7, %8, %9, %10, %11, %12, %13, %14, %15, %16, %17, %18, %19, %20, %21, %22, %23, %24, %25, %26, %27, %28, %29, %30, %31, %32, %33, %34, %35, %36, %37, %38, %39, %40, %41, %42, %43, %44, %45, %46, %47, %48, %49, %50, %51, %52, %53, %54, %55, %56, %57, %58, %59, %60, %61, %62, %63}, {%64, %65, %66, %67}, db, p, 1, 1, %70;\n}\n"
    : "+f"(d[0]), "+f"(d[1]), "+f"(d[2]), "+f"(d[3]), "+f"(d[4]), "+f"(d[5]), "+f"(d[6]), "+f"(d[7]), "+f"(d[8]), "+f"(d[9]), "+f"(d[10]), "+f"(d[11]), "+f"(d[12]), "+f"(d[13]), "+f"(d[14]), "+f"(d[15]), "+f"(d[16]), "+f"(d[17]), "+f"(d[18]), "+f"(d[19]), "+f"(d[20]), "+f"(d[21]), "+f"(d[22]), "+f"(d[23]), "+f"(d[24]), "+f"(d[25]), "+f"(d[26]), "+f"(d[27]), "+f"(d[28]), "+f"(d[29]), "+f"(d[30]), "+f"(d[31]), "+f"(d[32]), "+f"(d[33]), "+f"(d[34]), "+f"(d[35]), "+f"(d[36]), "+f"(d[37]), "+f"(d[38]), "+f"(d[39]), "+f"(d[40]), "+f"(d[41]), "+f"(d[42]), "+f"(d[43]), "+f"(d[44]), "+f"(d[45]), "+f"(d[46]), "+f"(d[47]), "+f"(d[48]), "+f"(d[49]), "+f"(d[50]), "+f"(d[51]), "+f"(d[52]), "+f"(d[53]), "+f"(d[54]), "+f"(d[55]), "+f"(d[56]), "+f"(d[57]), "+f"(d[58]), "+f"(d[59]), "+f"(d[60]), "+f"(d[61]), "+f"(d[62]), "+f"(d[63])
    : "r"(a0), "r"(a1), "r"(a2), "r"(a3), "r"(db), "r"(scale_d), "n"(TB), "n"(HB));
}

constexpr int S_ = 2048, D_ = 1024, F_ = 3584;
constexpr int NCTA = 128;
#define NMOE_ 112
constexpr int NMOE = NMOE_;
#define KV16 1
constexpr int KVH = 5 * 128 * 2;

#define NY 8
struct Zeroed {
  float kv[32 * KVH];
  float y[NY * 2 * D_];
  uint4 hint[512];
  unsigned done[128];
  unsigned pad[1920];
};
constexpr int ZB = KVH + 128 + NY * 64;
static_assert(sizeof(Zeroed) == NCTA * ZB, "zeroed block");
__device__ __align__(128) Zeroed g_z;
__device__ __align__(128) unsigned g_key[2 * NCTA];
__device__ __align__(128) uint2 g_bcast[2 * 8 * 16];
__device__ __align__(128) unsigned g_gate[S_];
__device__ __align__(1024) __nv_bfloat16 g_o[S_ * D_];
#define TSTAMP(i)
#define GSTAMP(i)

constexpr int STAGES = 6, KT = 32;
constexpr int A_BYTES = 256 * 64, B_BYTES = 192 * 64, STAGE_BYTES = A_BYTES + B_BYTES;
constexpr int SM_RA = 0;
constexpr int SM_RB = STAGES * A_BYTES;
constexpr int SM_PHIK = 0;
constexpr int SM_V = 65536;
constexpr int SM_O = SM_V;
constexpr int NA2 = 5, NB2 = 7;
#define XT_IN_A 1
constexpr int SM_XT = (XT_IN_A ? SM_RA : SM_RB) + 2 * 16384;
constexpr int SM_XR = STAGES * STAGE_BYTES;
constexpr int SM_MOE = SM_XR;
constexpr int SM_XSEL = SM_XR + 36864;
constexpr int SM_RED = SM_XSEL + 2048;
constexpr int SM_WPHI = 212992;
constexpr int SM_KVB = SM_WPHI + 4096;
constexpr int SM_ONES = SM_KVB + 12288;
constexpr int SM_BAR = SM_ONES + 1024;
constexpr int SM_INFO = SM_BAR + 1008;
constexpr int SM_GATE = SM_BAR + 1024;
constexpr int SM_UPD = SM_WPHI;
constexpr int SM_KEYS = SM_GATE + 512;
constexpr int SM_TS = SM_KEYS + 16;
constexpr int SM_TOTAL = SM_TS + 256;
static_assert(SM_TOTAL <= 232448 && ZB <= 4608, "smem");
static_assert(SM_WPHI % 1024 == 0 && SM_KVB % 1024 == 0 && SM_ONES % 1024 == 0, "align");
static_assert(SM_MOE + 40960 <= SM_WPHI && SM_RB + NB2 * 16384 <= SM_WPHI, "map");
#define QUAD 1
#define Q_UNROLL 1
#define COLMAP 0xefdb9ca875316420ull
#define INIT_FENCE 0
#define KV_BAR 0
#define KV_LOOP 0
#define GATE_EXACT 1
#define FFN_LOOP 0
#define QUAD_Q 1
#define HINT_BULK 1
#define EXPT 0
#define PF_START 0
#define PF_OFF 0
#define KV_DELAY 400
#define O_YIELD 1
#define TAILV -1
#define NFIRST 5
#define Q_AFTER B_PHI + 1
#define LEAD2 4
#define KEY_SLEEP 0
#define B5_AFTER B_F2 + 2
#define REG_C 192
#define REG_K 88
#define STR2(x) #x
#define STR(x) STR2(x)
#define XT_H 0
#define EARLY_MAP 1
#define NPRE 1
#define O_OVL 1
#define LATE_SLEEP 0
#define URG_STEP 0
#define LEAD_AT 1
#define XR_AFTER 3
#define LATE_DELAY 300
#define LATE_STEP 400

constexpr int B_FULL = 0, B_XR = 6, B_WPHI = 10;
constexpr int B_EMPTY = 11, B_XRD = 17;
constexpr int B_INIT = 123;
constexpr int B_ST = 18, B_MOE = 20, B_XSEL = 24, B_H = 25, B_RDY = 26, B_Y = 27, B_XT = 28, B_PEER = 30;
constexpr int B_FB2 = 31, B_F2 = 47;
constexpr int B_DB = 79;
constexpr int B_GO = 95;
constexpr int B_KVB = 111, B_OP = 112, B_MOEE = 116;
constexpr int B_PHI = 120, B_XTD = 122;
constexpr int NBAR = 123;
__host__ __device__ constexpr int bar_count(int i) {
  return i < B_DB ? 1 : i < B_GO ? 2 : i < B_KVB ? (int)(0x3333333333519111ull >> (4 * (i - B_GO))) & 15 : i < B_PHI ? 4 : 8;
}

struct Maps { CUtensorMap x, w, wo, wphi, wg, wu, wd, tg, tu, td, to, xr, xt, out; };

__device__ __forceinline__ uint32_t pack_bf16(float lo, float hi) {
  uint32_t r; asm("cvt.rn.bf16x2.f32 %0, %1, %2;" : "=r"(r) : "f"(hi), "f"(lo)); return r;
}
__device__ __forceinline__ float bf_lo(uint32_t v) { return __uint_as_float(v << 16); }
__device__ __forceinline__ float bf_hi(uint32_t v) { return __uint_as_float(v & 0xffff0000u); }
__device__ __forceinline__ float round_bf16(float v) { return __bfloat162float(__float2bfloat16_rn(v)); }
__device__ __forceinline__ float ex2(float v) { float r; asm("ex2.approx.ftz.f32 %0, %1;" : "=f"(r) : "f"(v)); return r; }
__device__ __forceinline__ float rcp(float v) { float r; asm("rcp.approx.ftz.f32 %0, %1;" : "=f"(r) : "f"(v)); return r; }
__device__ __forceinline__ void stsm4(uint32_t addr, uint32_t r0, uint32_t r1, uint32_t r2, uint32_t r3) {
  asm volatile("stmatrix.sync.aligned.m8n8.x4.shared.b16 [%0], {%1, %2, %3, %4};" :: "r"(addr), "r"(r0), "r"(r1), "r"(r2), "r"(r3) : "memory");
}
__device__ __forceinline__ void stsm2(uint32_t addr, uint32_t r0, uint32_t r1) {
  asm volatile("stmatrix.sync.aligned.m8n8.x2.shared.b16 [%0], {%1, %2};" :: "r"(addr), "r"(r0), "r"(r1) : "memory");
}
__device__ __forceinline__ uint2 lds64(uint32_t addr) {
  uint2 v; asm volatile("ld.shared.v2.u32 {%0, %1}, [%2];" : "=r"(v.x), "=r"(v.y) : "r"(addr) : "memory"); return v;
}
__device__ __forceinline__ void lds128x4(uint32_t addr, uint4& a, uint4& b, uint4& c, uint4& d) {
  asm volatile("ld.shared.v4.u32 {%0, %1, %2, %3}, [%16];\nld.shared.v4.u32 {%4, %5, %6, %7}, [%16 + 128];\n"
               "ld.shared.v4.u32 {%8, %9, %10, %11}, [%16 + 256];\nld.shared.v4.u32 {%12, %13, %14, %15}, [%16 + 384];"
    : "=r"(a.x), "=r"(a.y), "=r"(a.z), "=r"(a.w), "=r"(b.x), "=r"(b.y), "=r"(b.z), "=r"(b.w),
      "=r"(c.x), "=r"(c.y), "=r"(c.z), "=r"(c.w), "=r"(d.x), "=r"(d.y), "=r"(d.z), "=r"(d.w) : "r"(addr) : "memory");
}
__device__ __forceinline__ void ldsm4(uint32_t addr, uint32_t& r0, uint32_t& r1, uint32_t& r2, uint32_t& r3) {
  asm volatile("ldmatrix.sync.aligned.m8n8.x4.shared.b16 {%0, %1, %2, %3}, [%4];" : "=r"(r0), "=r"(r1), "=r"(r2), "=r"(r3) : "r"(addr) : "memory");
}
__device__ __forceinline__ uint4 lds128(uint32_t addr) {
  uint4 v; asm volatile("ld.shared.v4.u32 {%0, %1, %2, %3}, [%4];" : "=r"(v.x), "=r"(v.y), "=r"(v.z), "=r"(v.w) : "r"(addr) : "memory"); return v;
}
__device__ __forceinline__ void sts128(uint32_t addr, uint4 v) {
  asm volatile("st.shared.v4.u32 [%0], {%1, %2, %3, %4};" :: "r"(addr), "r"(v.x), "r"(v.y), "r"(v.z), "r"(v.w) : "memory");
}
__device__ __forceinline__ float lds_f32(uint32_t addr) { float v; asm volatile("ld.shared.f32 %0, [%1];" : "=f"(v) : "r"(addr) : "memory"); return v; }
__device__ __forceinline__ void sts_f32(uint32_t addr, float v) { asm volatile("st.shared.f32 [%0], %1;" :: "r"(addr), "f"(v) : "memory"); }
__device__ __forceinline__ uint32_t lds_u32(uint32_t addr) { uint32_t v; asm volatile("ld.shared.u32 %0, [%1];" : "=r"(v) : "r"(addr) : "memory"); return v; }
__device__ __forceinline__ void sts_u32(uint32_t addr, uint32_t v) { asm volatile("st.shared.u32 [%0], %1;" :: "r"(addr), "r"(v) : "memory"); }
__device__ __forceinline__ unsigned clock32() { unsigned c; asm volatile("mov.u32 %0, %%clock;" : "=r"(c)); return c; }
__device__ __forceinline__ bool elect_one() {
  uint32_t p; asm volatile("{\n.reg .pred q;\nelect.sync _|q, 0xffffffff;\nselp.u32 %0, 1, 0, q;\n}" : "=r"(p)); return p;
}
__device__ __forceinline__ void bar_sync(int id, int n) { asm volatile("bar.sync %0, %1;" :: "r"(id), "r"(n) : "memory"); }
__device__ __forceinline__ void fence_async_smem() { asm volatile("fence.proxy.async.shared::cta;" ::: "memory"); }
__device__ __forceinline__ void fence_async_all() { asm volatile("fence.proxy.async;" ::: "memory"); }
__device__ __forceinline__ void fence_gpu() { asm volatile("fence.acq_rel.gpu;" ::: "memory"); }
__device__ __forceinline__ unsigned ld_acquire(const unsigned* p) { unsigned v; asm volatile("ld.acquire.gpu.global.u32 %0, [%1];" : "=r"(v) : "l"(p) : "memory"); return v; }
__device__ __forceinline__ void red_release(unsigned* p, unsigned v) { asm volatile("red.release.gpu.global.add.u32 [%0], %1;" :: "l"(p), "r"(v) : "memory"); }
__device__ __forceinline__ void st_release(unsigned* p, unsigned v) { asm volatile("st.release.gpu.global.u32 [%0], %1;" :: "l"(p), "r"(v) : "memory"); }
__device__ __forceinline__ unsigned ld_relaxed(const unsigned* p) { unsigned v; asm volatile("ld.relaxed.gpu.global.u32 %0, [%1];" : "=r"(v) : "l"(p) : "memory"); return v; }
__device__ __forceinline__ void red_relaxed(unsigned* p, unsigned v) { asm volatile("red.relaxed.gpu.global.add.u32 [%0], %1;" :: "l"(p), "r"(v) : "memory"); }
__device__ __forceinline__ void st_relaxed(unsigned* p, unsigned v) { asm volatile("st.relaxed.gpu.global.u32 [%0], %1;" :: "l"(p), "r"(v) : "memory"); }
__device__ __forceinline__ void st_relaxed2(uint2* p, unsigned a, unsigned b) { asm volatile("st.relaxed.gpu.global.v2.u32 [%0], {%1, %2};" :: "l"(p), "r"(a), "r"(b) : "memory"); }
template <int SLEEP>
__device__ __forceinline__ unsigned wait_tagged(const uint2* p, unsigned tag) {
  uint2 v;
  int it = 0;
  do {
    if (SLEEP && it > 0) __nanosleep(SLEEP);
    asm volatile("ld.relaxed.gpu.global.v2.u32 {%0, %1}, [%2];" : "=r"(v.x), "=r"(v.y) : "l"(p) : "memory");
    if (++it > (1 << 20)) __trap();
  } while (!__all_sync(0xffffffffu, v.y == tag));
  return v.x;
}
__device__ __forceinline__ void wait_counter(const unsigned* p, unsigned target) {
#pragma unroll 1
  for (int it = 0; it < (1 << 20); it++) { if ((int)(ld_relaxed(p) - target) >= 0) return; }
  __trap();
}
__device__ __forceinline__ float4 ldg_l2(const float* p) {
  float4 v; asm volatile("ld.relaxed.gpu.global.v4.f32 {%0, %1, %2, %3}, [%4];" : "=f"(v.x), "=f"(v.y), "=f"(v.z), "=f"(v.w) : "l"(p) : "memory"); return v;
}
__device__ __forceinline__ float ldg_l2_f(const float* p) { float v; asm volatile("ld.relaxed.gpu.global.f32 %0, [%1];" : "=f"(v) : "l"(p) : "memory"); return v; }
__device__ __forceinline__ void sts64(uint32_t addr, float a, float b) { asm volatile("st.shared.v2.f32 [%0], {%1, %2};" :: "r"(addr), "f"(a), "f"(b) : "memory"); }
__device__ __forceinline__ void bulk_load(uint32_t dst, const void* src, uint32_t bytes, uint32_t bar) {
  asm volatile("cp.async.bulk.shared::cluster.global.mbarrier::complete_tx::bytes [%0], [%1], %2, [%3];" :: "r"(dst), "l"(src), "r"(bytes), "r"(bar) : "memory");
}
__device__ __forceinline__ void bulk_prefetch(const void* src, uint32_t bytes) {
  asm volatile("cp.async.bulk.prefetch.L2.global [%0], %1;" :: "l"(src), "r"(bytes) : "memory");
}
__device__ __forceinline__ void tma_store_2d(const CUtensorMap* tm, uint32_t src, int c0, int c1) {
  asm volatile("cp.async.bulk.tensor.2d.global.shared::cta.bulk_group [%0, {%2, %3}], [%1];" :: "l"(tm), "r"(src), "r"(c0), "r"(c1) : "memory");
}
__device__ __forceinline__ void bulk_store(void* dst, uint32_t src, uint32_t bytes) {
  asm volatile("cp.async.bulk.global.shared::cta.bulk_group [%0], [%1], %2;" :: "l"(dst), "r"(src), "r"(bytes) : "memory");
}
__device__ __forceinline__ void bulk_reduce_f32(void* dst, uint32_t src, uint32_t bytes) {
  asm volatile("cp.reduce.async.bulk.global.shared::cta.bulk_group.add.f32 [%0], [%1], %2;" :: "l"(dst), "r"(src), "r"(bytes) : "memory");
}
__device__ __forceinline__ void tma_load_3d(uint32_t dst, const CUtensorMap* tm, int c0, int c1, int c2, uint32_t bar) {
  asm volatile("cp.async.bulk.tensor.3d.shared::cluster.global.mbarrier::complete_tx::bytes [%0], [%1, {%3, %4, %5}], [%2];"
    :: "r"(dst), "l"(tm), "r"(bar), "r"(c0), "r"(c1), "r"(c2) : "memory");
}
__device__ __forceinline__ void cp_async16(uint32_t dst, const void* src) { asm volatile("cp.async.cg.shared.global [%0], [%1], 16;" :: "r"(dst), "l"(src) : "memory"); }
__device__ __forceinline__ void cp_async_commit() { asm volatile("cp.async.commit_group;" ::: "memory"); }
template <int N> __device__ __forceinline__ void cp_async_wait() { asm volatile("cp.async.wait_group %0;" :: "n"(N) : "memory"); }
__device__ __forceinline__ void prefetch_map(const CUtensorMap* tm) { asm volatile("prefetch.tensormap [%0];" :: "l"(tm) : "memory"); }
__device__ __forceinline__ void bulk_commit() { asm volatile("cp.async.bulk.commit_group;" ::: "memory"); }
__device__ __forceinline__ void bulk_wait0() { asm volatile("cp.async.bulk.wait_group 0;" ::: "memory"); }
__device__ __forceinline__ void bulk_wait0_read() { asm volatile("cp.async.bulk.wait_group.read 0;" ::: "memory"); }
__device__ __forceinline__ void mma16816(float& d0, float& d1, float& d2, float& d3, uint32_t a0, uint32_t a1, uint32_t a2, uint32_t a3, uint32_t b0, uint32_t b1) {
  asm volatile("mma.sync.aligned.m16n8k16.row.col.f32.bf16.bf16.f32 {%0, %1, %2, %3}, {%4, %5, %6, %7}, {%8, %9}, {%0, %1, %2, %3};"
    : "+f"(d0), "+f"(d1), "+f"(d2), "+f"(d3) : "r"(a0), "r"(a1), "r"(a2), "r"(a3), "r"(b0), "r"(b1));
}
__device__ __forceinline__ uint32_t hmul2(uint32_t a, uint32_t b) { uint32_t r; asm("mul.rn.bf16x2 %0, %1, %2;" : "=r"(r) : "r"(a), "r"(b)); return r; }
__device__ __forceinline__ uint32_t hfma2(uint32_t a, uint32_t b, uint32_t c) { uint32_t r; asm("fma.rn.bf16x2 %0, %1, %2, %3;" : "=r"(r) : "r"(a), "r"(b), "r"(c)); return r; }
__device__ __forceinline__ uint32_t hadd2(uint32_t a, uint32_t b) { uint32_t r; asm("add.rn.bf16x2 %0, %1, %2;" : "=r"(r) : "r"(a), "r"(b)); return r; }
__device__ __forceinline__ float sigmoidf_(float v) { return rcp(1.0f + ex2(v * -1.4426950408889634f)); }

__device__ __forceinline__ void hedgehog(const float (&p)[16], uint32_t (&phi)[16]) {
  float mx0 = p[0], mn0 = p[0], mx1 = p[2], mn1 = p[2];
#pragma unroll
  for (int j = 0; j < 4; j++) {
    mx0 = fmaxf(mx0, fmaxf(p[4 * j], p[4 * j + 1])); mn0 = fminf(mn0, fminf(p[4 * j], p[4 * j + 1]));
    mx1 = fmaxf(mx1, fmaxf(p[4 * j + 2], p[4 * j + 3])); mn1 = fminf(mn1, fminf(p[4 * j + 2], p[4 * j + 3]));
  }
#pragma unroll
  for (int o = 1; o <= 2; o <<= 1) {
    mx0 = fmaxf(mx0, __shfl_xor_sync(0xffffffffu, mx0, o)); mn0 = fminf(mn0, __shfl_xor_sync(0xffffffffu, mn0, o));
    mx1 = fmaxf(mx1, __shfl_xor_sync(0xffffffffu, mx1, o)); mn1 = fminf(mn1, __shfl_xor_sync(0xffffffffu, mn1, o));
  }
  float ep[16], en[16];
  float sp0 = 0.f, sn0 = 0.f, sp1 = 0.f, sn1 = 0.f;
#pragma unroll
  for (int j = 0; j < 4; j++) {
#pragma unroll
    for (int c = 0; c < 2; c++) {
      ep[4 * j + c] = ex2(p[4 * j + c] - mx0); en[4 * j + c] = ex2(mn0 - p[4 * j + c]);
      ep[4 * j + 2 + c] = ex2(p[4 * j + 2 + c] - mx1); en[4 * j + 2 + c] = ex2(mn1 - p[4 * j + 2 + c]);
      sp0 += ep[4 * j + c]; sn0 += en[4 * j + c]; sp1 += ep[4 * j + 2 + c]; sn1 += en[4 * j + 2 + c];
    }
  }
#pragma unroll
  for (int o = 1; o <= 2; o <<= 1) {
    sp0 += __shfl_xor_sync(0xffffffffu, sp0, o); sn0 += __shfl_xor_sync(0xffffffffu, sn0, o);
    sp1 += __shfl_xor_sync(0xffffffffu, sp1, o); sn1 += __shfl_xor_sync(0xffffffffu, sn1, o);
  }
  sp0 = rcp(sp0); sn0 = rcp(sn0); sp1 = rcp(sp1); sn1 = rcp(sn1);
#pragma unroll
  for (int j = 0; j < 4; j++) {
    phi[2 * j] = pack_bf16(ep[4 * j] * sp0, ep[4 * j + 1] * sp0);
    phi[2 * j + 1] = pack_bf16(ep[4 * j + 2] * sp1, ep[4 * j + 3] * sp1);
    phi[8 + 2 * j] = pack_bf16(en[4 * j + 1] * sn0, en[4 * j] * sn0);
    phi[8 + 2 * j + 1] = pack_bf16(en[4 * j + 3] * sn1, en[4 * j + 2] * sn1);
  }
}

__device__ __noinline__ void hedgehog_slow(float* buf, int n) {
#pragma unroll 1
  for (int u = 0; u < n; u++) {
    float p[16]; uint32_t phi[16];
#pragma unroll
    for (int i = 0; i < 16; i++) p[i] = buf[u * 16 + i];
    hedgehog(p, phi);
#pragma unroll
    for (int i = 0; i < 16; i++) buf[u * 16 + i] = __uint_as_float(phi[i]);
  }
}

__device__ __forceinline__ void store_phi_k(const uint32_t (&phi)[16], uint32_t a) {
#pragma unroll
  for (int jj = 0; jj < 4; jj++) stsm4(a ^ (jj << 5), phi[4 * jj], phi[4 * jj + 1], phi[4 * jj + 2], phi[4 * jj + 3]);
}
__device__ __forceinline__ void hand_over_smem(uint32_t bar, bool ok) {
  fence_async_smem();
  __syncwarp();
  if (elect_one() & ok) mbar_arrive(bar);
}
__device__ __noinline__ void redo_phi_k(float* buf, unsigned done, uint32_t pa, uint32_t bar) {
  hedgehog_slow(buf, 4);
#pragma unroll 1
  for (int u = 0; u < 4; u++) {
    if ((done >> u) & 1) continue;
    uint32_t phi[16];
#pragma unroll
    for (int i = 0; i < 16; i++) phi[i] = __float_as_uint(buf[u * 16 + i]);
    store_phi_k(phi, pa + (~u & 1) * 32768 + (u >> 1) * 4096);
    if (u >= 2) hand_over_smem(bar + (u - 2) * 8, true);
  }
}

__device__ __forceinline__ uint32_t dup_lo(uint32_t v) { uint32_t r; asm("{\n.reg .b16 l, h;\nmov.b32 {l, h}, %1;\nmov.b32 %0, {l, l};\n}" : "=r"(r) : "r"(v)); return r; }
__device__ __forceinline__ uint32_t dup_hi(uint32_t v) { uint32_t r; asm("{\n.reg .b16 l, h;\nmov.b32 {l, h}, %1;\nmov.b32 %0, {h, h};\n}" : "=r"(r) : "r"(v)); return r; }
struct HState { uint32_t a[16]; float s[5]; };
template <bool QD>
__device__ __forceinline__ void hedgehog_fast1(const float (&p)[16], HState& a) {
  float sm[8], m[8], r[8];
#pragma unroll
  for (int i = 0; i < 8; i++) {
    const float t0 = ex2(p[2 * i]), t1 = ex2(p[2 * i + 1]);
    a.a[i] = pack_bf16(t0, t1); sm[i] = t0 + t1; m[i] = t0 * t1;
  }
  if (QD) {
    float mq[4];
#pragma unroll
    for (int i = 0; i < 4; i++) {
      mq[i] = m[2 * i] * m[2 * i + 1];
      const float R = rcp(mq[i]);
      r[2 * i] = R * m[2 * i + 1]; r[2 * i + 1] = R * m[2 * i];
    }
    a.s[4] = (mq[0] + mq[1]) + (mq[2] + mq[3]);
  } else {
#pragma unroll
    for (int i = 0; i < 8; i++) r[i] = rcp(m[i]);
    a.s[4] = 0.f;
  }
#pragma unroll
  for (int i = 0; i < 4; i++) {
    const uint32_t rr = pack_bf16(r[2 * i], r[2 * i + 1]);
    a.a[8 + 2 * i] = hmul2(a.a[2 * i], dup_lo(rr)); a.a[9 + 2 * i] = hmul2(a.a[2 * i + 1], dup_hi(rr));
  }
#pragma unroll
  for (int c = 0; c < 2; c++) {
    a.s[2 * c] = (sm[c] + sm[2 + c]) + (sm[4 + c] + sm[6 + c]);
    a.s[2 * c + 1] = fmaf(r[6 + c], sm[6 + c], fmaf(r[4 + c], sm[4 + c], fmaf(r[2 + c], sm[2 + c], r[c] * sm[c])));
  }
}
template <bool NORM>
__device__ __forceinline__ bool hedgehog_fast2(const HState& a, uint32_t (&phi)[16], float& s0, float& s1) {
  float s[4] = {a.s[0], a.s[1], a.s[2], a.s[3]};
#pragma unroll
  for (int o = 1; o <= 2; o <<= 1)
#pragma unroll
    for (int i = 0; i < 4; i++) s[i] += __shfl_xor_sync(0xffffffffu, s[i], o);
  const bool ok = ((s[0] + s[1]) + (s[2] + s[3]) <= 7.2e16f) & (a.s[4] <= 1.3e36f);
  if (NORM) {
    const float R0 = rcp(s[0] * s[1]), R1 = rcp(s[2] * s[3]);
    const uint32_t n0 = pack_bf16(R0 * s[1], R0 * s[0]), n1 = pack_bf16(R1 * s[3], R1 * s[2]);
#pragma unroll
    for (int i = 0; i < 8; i++) { phi[i] = hmul2(a.a[i], dup_lo((i & 1) ? n1 : n0)); phi[8 + i] = hmul2(a.a[8 + i], dup_hi((i & 1) ? n1 : n0)); }
  } else {
    const uint32_t n = pack_bf16(s[0] * rcp(s[1]), s[2] * rcp(s[3]));
    s0 = s[0]; s1 = s[2];
#pragma unroll
    for (int i = 0; i < 8; i++) { phi[i] = a.a[i]; phi[8 + i] = hmul2(a.a[8 + i], (i & 1) ? dup_hi(n) : dup_lo(n)); }
  }
  return ok;
}
template <bool NORM>
__device__ __forceinline__ bool hedgehog_fast(const float (&p)[16], uint32_t (&phi)[16], float& s0, float& s1) {
  HState a;
  hedgehog_fast1<NORM ? QUAD : QUAD_Q>(p, a);
  return hedgehog_fast2<NORM>(a, phi, s0, s1);
}

template <int OFF>
__device__ __forceinline__ void pack_frags(const float (&acc)[96], uint32_t (&a)[16]) {
#pragma unroll
  for (int i = 0; i < 16; i++) a[i] = pack_bf16(acc[OFF + 2 * i], acc[OFF + 2 * i + 1]);
#pragma unroll
  for (int i = 0; i < 16; i++) asm volatile("" : "+r"(a[i]) :: "memory");
}
__device__ __forceinline__ void issue_feat(const uint32_t (&a)[16], float (&p0)[16], float (&p1)[16], uint32_t wphi) {
  wgmma_fence();
#pragma unroll
  for (int kk = 0; kk < 2; kk++) {
    wgmma_rs_n32<1, H64>(p0, a[4 * kk], a[4 * kk + 1], a[4 * kk + 2], a[4 * kk + 3], dlo(wphi + kk * 1024, 16), kk);
    wgmma_rs_n32<1, H64>(p1, a[8 + 4 * kk], a[8 + 4 * kk + 1], a[8 + 4 * kk + 2], a[8 + 4 * kk + 3], dlo(wphi + 2048 + kk * 1024, 16), kk);
  }
  wgmma_commit();
}
__device__ __forceinline__ void keep_alive(const uint32_t (&a)[16]) {
#pragma unroll
  for (int i = 0; i < 16; i++) asm volatile("" :: "r"(a[i]) : "memory");
}

__device__ __forceinline__ void fma8(float (&a)[8], float xv, const uint4& w) {
  a[0] = fmaf(xv, bf_lo(w.x), a[0]); a[1] = fmaf(xv, bf_hi(w.x), a[1]);
  a[2] = fmaf(xv, bf_lo(w.y), a[2]); a[3] = fmaf(xv, bf_hi(w.y), a[3]);
  a[4] = fmaf(xv, bf_lo(w.z), a[4]); a[5] = fmaf(xv, bf_hi(w.z), a[5]);
  a[6] = fmaf(xv, bf_lo(w.w), a[6]); a[7] = fmaf(xv, bf_hi(w.w), a[7]);
}

template <int J0, int J1>
__device__ __forceinline__ void stage_out(const float (&acc)[64], uint32_t xa) {
#pragma unroll
  for (int jj = J0; jj < J1; jj++)
    stsm4((xa ^ ((jj & 3) << 5)) + (jj >> 2) * 16384, pack_bf16(acc[8 * jj], acc[8 * jj + 1]), pack_bf16(acc[8 * jj + 2], acc[8 * jj + 3]),
          pack_bf16(acc[8 * jj + 4], acc[8 * jj + 5]), pack_bf16(acc[8 * jj + 6], acc[8 * jj + 7]));
}
__device__ __forceinline__ float lds_bf16(uint32_t addr) {
  unsigned short v; asm volatile("ld.shared.u16 %0, [%1];" : "=h"(v) : "r"(addr) : "memory"); return __uint_as_float((uint32_t)v << 16);
}
__device__ __noinline__ void redo_rows(const __nv_bfloat16* x, const __nv_bfloat16* wo, uint32_t sb, int b, int wq, uint32_t xa) {
  const int lane = threadIdx.x & 31, wi = (threadIdx.x >> 5) & 3, blk = (b >> 3) * 2 + wq, row0 = blk * 64 + wi * 16;
  const __nv_bfloat16 *pieces = g_o + (size_t)blk * 16 * 4096, *wo_cols = wo + (b & 7) * 128, *xrows = x + (size_t)row0 * D_ + (b & 7) * 128;
  const unsigned* done = g_z.done + (b & ~15);
  const uint32_t gate = sb + SM_GATE + (row0 & 255) * 2, upd = sb + SM_UPD;
  const int routed = (int)lds_u32(sb + SM_INFO + 4) - row0;
  int it = 0;
  while (!__all_sync(0xffffffffu, ld_acquire(done + (lane & 15)) != 0)) { if (++it > (1 << 20)) __trap(); }
  float acc[64];
  const int g = lane >> 2, q = lane & 3, r0 = wi * 16 + g;
#pragma unroll
  for (int i = 0; i < 32; i++) {
    const int r = g + (i & 1) * 8, c = (i >> 1) * 8 + q * 2;
    const uint32_t v = *reinterpret_cast<const uint32_t*>(xrows + (size_t)r * D_ + c);
    const float og = round_bf16(1.0f - lds_bf16(gate + r * 2));
    acc[2 * i] = og * bf_lo(v); acc[2 * i + 1] = og * bf_hi(v);
    if (r == routed) {
      const uint32_t u = lds_u32(upd + (c >> 6) * 2048 + (c & 63) * 2);
      acc[2 * i] += bf_lo(u); acc[2 * i + 1] += bf_hi(u);
    }
  }
#pragma unroll 1
  for (int ks = 0; ks < 64; ks++) {
    const unsigned* pc = reinterpret_cast<const unsigned*>(pieces + (ks >> 2) * 4096) + r0 * 32 + q;
    const int c0 = ((2 * (ks & 3)) ^ (r0 & 7)) * 4, c1 = ((2 * (ks & 3) + 1) ^ (r0 & 7)) * 4;
    const uint32_t a0 = ld_relaxed(pc + c0), a1 = ld_relaxed(pc + 256 + c0), a2 = ld_relaxed(pc + c1), a3 = ld_relaxed(pc + 256 + c1);
    const unsigned short* wp = reinterpret_cast<const unsigned short*>(wo_cols) + (size_t)(ks * 16 + 2 * q) * D_ + g;
#pragma unroll
    for (int nb = 0; nb < 16; nb++) {
      const uint32_t b0 = wp[nb * 8] | ((uint32_t)wp[nb * 8 + D_] << 16), b1 = wp[nb * 8 + 8 * D_] | ((uint32_t)wp[nb * 8 + 9 * D_] << 16);
      mma16816(acc[4 * nb], acc[4 * nb + 1], acc[4 * nb + 2], acc[4 * nb + 3], a0, a1, a2, a3, b0, b1);
    }
  }
  __syncwarp();
  stage_out<0, 8>(acc, xa);
}

__global__ void __cluster_dims__(2, 1, 1) __launch_bounds__(512, 1)
fused_kernel(const __grid_constant__ Maps maps, const __nv_bfloat16* __restrict__ x,
             const __nv_bfloat16* __restrict__ wo, const __nv_bfloat16* __restrict__ w_r, const __nv_bfloat16* __restrict__ gate_w) {
  extern __shared__ __align__(1024) uint8_t smem_raw[];
  if (threadIdx.x == 0) { prefetch_map(&maps.w); prefetch_map(&maps.x); }
  const int tid = threadIdx.x, warp = __shfl_sync(0xffffffffu, tid >> 5, 0), lane = tid & 31;
  const int rank = blockIdx.x & 1;
  const unsigned cl = blockIdx.x >> 1, hi = (cl - 36) * 37 >> 8, lo7 = cl - 36 - hi * 7;
  const bool r8 = cl < 36;
  const unsigned c4 = cl - 4, col = cl < 4 ? 15 : r8 ? c4 & 7 : 8 + lo7, pos = cl < 4 ? cl : r8 ? c4 >> 3 : hi;
  const int b = ((unsigned)(COLMAP >> (4 * col)) & 15) * 8 + pos * 2 + rank;
  const int e = EXPT == 12 ? 200 : blockIdx.x;
  const int tg = b >> 4, hp = b & 15;
  const int half = hp >> 3, ct = hp & 7;
  constexpr uint32_t SB0 = 1024;
  const uint32_t sb = SB0 + ((uint32_t)rank << 24);
  auto BAR = [&](int i) { return sb + SM_BAR + 8 * i; };
  auto load_stage = [&](int kt, int s, bool mc) {
    const uint32_t a = sb + SM_RA + s * A_BYTES, full = BAR(B_FULL + s);
    mbar_expect_tx(full, STAGE_BYTES);
    tma_load_3d(sb + SM_RB + s * B_BYTES, &maps.w, hp * 64, kt * 32, 0, full);
    if (mc) tma_load_2d_mc(a + rank * 8192, &maps.x, kt * 32, tg * 256 + rank * 128, full);
    else { tma_load_2d(a, &maps.x, kt * 32, tg * 256, full); tma_load_2d(a + 8192, &maps.x, kt * 32, tg * 256 + 128, full); }
  };
  auto slice_of = [&](int i) { const int t = i - 2 * ((unsigned)(i - 2) < (unsigned)(ct & 6)); return ((i >> 1) ? t : t ^ ct) ^ (half * 8); };
  auto load_b2 = [&](int i) {
    const int j = slice_of(i), sl = i + 4 - (i >= 3) * NB2 - (i >= 10) * NB2;
    mbar_expect_tx(BAR(B_FB2 + i), 16384);
    tma_load_3d(sb + SM_RB + sl * 16384, &maps.wo, 0, j * 64, ct * 2, BAR(B_FB2 + i));
  };
  auto load_xt = [&](int w) {
    mbar_expect_tx(BAR(B_XT + w), 16384);
    tma_load_2d(sb + SM_XT + w * 8192, &maps.xt, ct * 128, tg * 256 + half * 128 + w * 64, BAR(B_XT + w));
    tma_load_2d(sb + SM_XT + w * 8192 + 16384, &maps.xt, ct * 128 + 64, tg * 256 + half * 128 + w * 64, BAR(B_XT + w));
  };
  auto o_piece = [&](int hf, int mb, int j) { return g_o + (size_t)((((tg * 2 + hf) * 2 + mb) * 16 + j) * 4096); };

  if (blockIdx.x >= NCTA) {
    if (warp == 0 && blockIdx.x == NCTA) {
      if (smem_u32(smem_raw) != sb) __trap();
      const unsigned tag = (ld_relaxed(&g_bcast[0].y) + 1) & 0xfffu;
#pragma unroll 1
      for (int round = 0; round < 2; round++) {
        bool all;
        int it = 0;
        do {
          uint4 k;
          asm volatile("ld.relaxed.gpu.global.v4.u32 {%0, %1, %2, %3}, [%4];" : "=r"(k.x), "=r"(k.y), "=r"(k.z), "=r"(k.w) : "l"(g_key + round * NCTA + lane * 4) : "memory");
          all = __all_sync(0xffffffffu, (((k.x ^ tag) | (k.y ^ tag) | (k.z ^ tag) | (k.w ^ tag)) & 0xfffu) == 0);
          auto full = [&](unsigned m, int c) { return (m & 0xffff0000u) | ((127u - (lane * 4 + c)) << 4) | ((m >> 12) & 15u); };
          const unsigned val = __reduce_max_sync(0xffffffffu, max(max(full(k.x, 0), full(k.y, 1)), max(full(k.z, 2), full(k.w, 3))));
          asm volatile("{\n.reg .pred p;\nsetp.ne.u32 p, %3, 0;\n@p st.relaxed.gpu.global.v2.u32 [%0], {%1, %2};\n}"
                       :: "l"(g_bcast + round * 128 + (lane & 7) * 16), "r"(val), "r"(tag), "r"((uint32_t)(all && lane < 8)) : "memory");
          if (++it > (1 << 20)) __trap();
        } while (!all);
      }
    }
    return;
  }
  auto load_xr = [&](int xc) {
    mbar_expect_tx(BAR(B_XR + xc), xc ? 8192 : 12288);
    tma_load_2d(sb + SM_XR + xc * 8192, &maps.xr, xc * 256, b * 16, BAR(B_XR + xc));
    tma_load_2d(sb + SM_XR + xc * 8192 + 4096, &maps.xr, xc * 256 + 128, b * 16, BAR(B_XR + xc));
    if (xc == 0) { bulk_load(sb + SM_XR + 32768, w_r, 2048, BAR(B_XR)); bulk_load(sb + SM_XR + 34816, gate_w, 2048, BAR(B_XR)); }
  };
  if (warp == 8) {
    if (elect_one()) {
      mbar_init(BAR(0), 1);
      if (NPRE > 1) { mbar_init(BAR(1), 1); mbar_init(BAR(2), 1); }
      if (NPRE > 0 && INIT_FENCE) fence_async_smem();
      TSTAMP(40);
      if (NPRE > 0) load_stage(0, 0, false);
      if (NPRE > 1) load_stage(1, 1, false);
      if (NPRE > 2) load_stage(2, 2, false);
      TSTAMP(41);
    }
  } else if (elect_one()) {
    const int i = 3 + warp - (warp > 8);
    mbar_init(BAR(i), i < B_EMPTY ? 1 : 4);
    if (NPRE < 2 && warp >= 14) mbar_init(BAR(warp - 13), 1);
    if (warp == 13) mbar_init(BAR(B_INIT), 3);
  }
  asm volatile("fence.mbarrier_init.release.cluster;" ::: "memory");
  __syncwarp();
  asm volatile("barrier.cluster.arrive.relaxed.aligned;" ::: "memory");
  auto cluster_wait = [&]() { asm volatile("barrier.cluster.wait.aligned;" ::: "memory"); };

  if (warp >= 12) {
    asm volatile("setmaxnreg.dec.sync.aligned.u32 40;");
    const int aw = warp - 12;
    cluster_wait();
    const unsigned old_gate = ld_relaxed(g_gate + b * 16 + aw * 4);
    const uint32_t zero = smem_u32(smem_raw) ^ sb;
    {
      float r[4], l[4];
#pragma unroll
      for (int t = 0; t < 4; t++) { r[t] = 0.f; l[t] = 0.f; }
      uint32_t xa = sb + SM_XR + aw * 1024 + lane * 8, wa = sb + SM_XR + 32768 + lane * 8;
#pragma unroll 1
      for (int i = 0; i < 8; i++) {
        if (!(i & 1)) mbar_wait(BAR(B_XR) + i * 4, 0);
        if (tid == 384 && i == 6) TSTAMP(30);
        uint2 wr = lds64(wa);
        const uint2 gw = lds64(wa + 2048);
        uint2 xv[4];
#pragma unroll
        for (int t = 0; t < 4; t++) xv[t] = lds64(xa + t * 256);
        xa += 4096; wa += 256;
        wr.x |= (xv[1].x | xv[2].x | xv[3].x) & zero;
        const float w0 = bf_lo(wr.x), w1 = bf_hi(wr.x), w2 = bf_lo(wr.y), w3 = bf_hi(wr.y);
#pragma unroll
        for (int t = 0; t < 4; t++) {
          const uint32_t p0 = hmul2(xv[t].x, gw.x), p1 = hmul2(xv[t].y, gw.y);
          r[t] = fmaf(bf_hi(xv[t].y), w3, fmaf(bf_lo(xv[t].y), w2, fmaf(bf_hi(xv[t].x), w1, fmaf(bf_lo(xv[t].x), w0, r[t]))));
          if (GATE_EXACT) l[t] += (bf_lo(p0) + bf_hi(p0)) + (bf_lo(p1) + bf_hi(p1));
          else l[t] = fmaf(bf_hi(xv[t].y), bf_hi(gw.y), fmaf(bf_lo(xv[t].y), bf_lo(gw.y), fmaf(bf_hi(xv[t].x), bf_hi(gw.x), fmaf(bf_lo(xv[t].x), bf_lo(gw.x), l[t]))));
        }
      }
      float u[4];
#pragma unroll
      for (int t = 0; t < 4; t++) u[t] = ((lane & 4) ? l[t] : r[t]) + __shfl_xor_sync(0xffffffffu, (lane & 4) ? r[t] : l[t], 4);
      const float v0 = ((lane & 1) ? u[1] : u[0]) + __shfl_xor_sync(0xffffffffu, (lane & 1) ? u[0] : u[1], 1);
      const float v1 = ((lane & 1) ? u[3] : u[2]) + __shfl_xor_sync(0xffffffffu, (lane & 1) ? u[2] : u[3], 1);
      float v = ((lane & 2) ? v1 : v0) + __shfl_xor_sync(0xffffffffu, (lane & 2) ? v0 : v1, 2);
      v += __shfl_xor_sync(0xffffffffu, v, 8);
      v += __shfl_xor_sync(0xffffffffu, v, 16);
      v = round_bf16(v);
      unsigned k = __float_as_uint(v) >> 16;
      k = (k & 0x8000u) ? (~k & 0xffffu) : (k | 0x8000u);
      k = __reduce_max_sync(0xffffffffu, lane < 4 ? (k << 4) | (15u - (aw * 4 + lane)) : 0u);
      if (lane == 0) sts_u32(sb + SM_KEYS + aw * 4, k);
      if ((lane >> 2) == 1) st_relaxed(g_gate + b * 16 + aw * 4 + (lane & 3), __float_as_uint(round_bf16(sigmoidf_(v))) | ((old_gate + 1) & 0xfffu));
      mbar_wait(BAR(B_INIT), 0);
    }
    if (tid == 384) { TSTAMP(31); GSTAMP(60); }
    fence_async_smem();
    __syncwarp();
    if (elect_one()) mbar_arrive(BAR(B_XRD));
    mbar_wait_bounded(BAR(B_XSEL), 0);
    if (tid == 384) TSTAMP(36);
    float ag[8];
#pragma unroll
    for (int i = 0; i < 8; i++) ag[i] = 0.f;
    if (e < NMOE) {
      const uint32_t lw = sb + SM_MOE + aw * 2048 + (lane >> 3) * 512 + (lane & 7) * 16;
      uint32_t lx = sb + SM_XSEL + aw * 32 + (lane >> 3) * 8, fb = BAR(B_MOE), wa = lw;
      bool got = false;
#pragma unroll 1
      for (int m = 0; m < 12; m++) {
#pragma unroll
        for (int c = 0; c < 2; c++) {
          if (!got) mbar_wait(fb + c * 8, (m >> 1) & 1);
          uint4 w0, w1, w2, w3;
          lds128x4(wa + c * 8192, w0, w1, w2, w3);
          uint2 xv = lds64(lx + c * 128);
          got = mbar_test(c ? fb ^ 16 : fb + 8, ((m + c) >> 1) & 1);
          const uint32_t dep = ((w0.x | w1.x | w2.x) | w3.x) & zero;
          xv.x |= dep;
          if (elect_one()) mbar_arrive(fb + dep + (B_MOEE - B_MOE + c) * 8);
          fma8(ag, bf_lo(xv.x), w0); fma8(ag, bf_hi(xv.x), w1); fma8(ag, bf_lo(xv.y), w2); fma8(ag, bf_hi(xv.y), w3);
        }
        fb ^= 16; wa = 2 * lw + 16384 - wa; lx += 256;
        if (m == (FFN_LOOP ? 15 : 7)) {
          int ln;
          asm volatile("mov.u32 %0, %%laneid;" : "=r"(ln));
#pragma unroll
          for (int i = 0; i < 4; i++) ag[i] = ((ln & 16) ? ag[4 + i] : ag[i]) + __shfl_xor_sync(0xffffffffu, (ln & 16) ? ag[i] : ag[4 + i], 16);
          const float v0 = ((ln & 8) ? ag[2] : ag[0]) + __shfl_xor_sync(0xffffffffu, (ln & 8) ? ag[0] : ag[2], 8);
          const float v1 = ((ln & 8) ? ag[3] : ag[1]) + __shfl_xor_sync(0xffffffffu, (ln & 8) ? ag[1] : ag[3], 8);
          const uint32_t own = (uint32_t)(ln & 4) << 22;
          asm volatile("st.async.shared::cluster.mbarrier::complete_tx::bytes.v2.f32 [%0], {%1, %2}, [%3];"
                       :: "r"(own + SB0 + SM_RED + rank * 512 + aw * 128 + (ln & 3) * 32 + (ln >> 3) * 8), "f"(v0), "f"(v1), "r"(own + SB0 + SM_BAR + 8 * B_H) : "memory");
          mbar_wait_bounded(BAR(B_H), 0);
          const uint32_t ra = sb + SM_RED + ln * 4;
          float gv = round_bf16((lds_f32(ra) + lds_f32(ra + 128)) + (lds_f32(ra + 256) + lds_f32(ra + 384)));
          const float uv = round_bf16((lds_f32(ra + 512) + lds_f32(ra + 640)) + (lds_f32(ra + 768) + lds_f32(ra + 896)));
          gv = round_bf16(gv * sigmoidf_(gv));
          lx = sb + SM_XSEL + aw * 32;
          asm volatile("st.shared.b16 [%0], %1;" :: "r"(lx + (ln >> 2) * 128 + (ln & 3) * 2), "h"(__bfloat16_as_ushort(__float2bfloat16_rn(gv * uv))) : "memory");
          __syncwarp();
#pragma unroll
          for (int i = 0; i < 8; i++) ag[i] = 0.f;
          if (tid == 384) TSTAMP(33);
        }
      }
      mbar_wait(BAR(B_RDY), 0);
#pragma unroll
      for (int j = 0; j < 3; j++)
        asm volatile("red.global.add.v4.f32 [%0], {%1, %2, %3, %4};" :: "l"(g_z.y + (e & (NY - 1)) * 2 * D_ + (j * 128 + aw * 32 + lane) * 4),
                     "f"(ag[3 * j]), "f"(ag[3 * j + 1]), "f"(j < 2 ? ag[3 * j + 2] : 0.f), "f"(1.0f) : "memory");
    }
    fence_async_smem();
    if (tid == 384) TSTAMP(34);
    bar_sync(4, 128);
    if (aw == 3) {
      const uint4 info = lds128(sb + SM_INFO);
      int it = 0;
      if ((info.y >> 7) == tg * 2 + half && EXPT != 12) {
        mbar_wait(BAR(B_RDY), 0);
        const float rs = round_bf16(sigmoidf_(__uint_as_float(info.z)));
        float y[9];
        do {
          __nanosleep(100);
#pragma unroll
          for (int i = 0; i < 9; i++) y[i] = 0.f;
#pragma unroll 1
          for (int c = lane >> 4; c < NY; c += 2) {
            const float* yp = g_z.y + c * 2 * D_ + (ct * 16 + (lane & 15)) * 4;
            const float4 a0 = ldg_l2(yp), a1 = ldg_l2(yp + 512), a2 = ldg_l2(yp + 1024);
            y[0] += a0.x; y[1] += a0.y; y[2] += a0.z; y[3] += a1.x; y[4] += a1.y; y[5] += a1.z; y[6] += a2.x; y[7] += a2.y;
            y[8] += a0.w + a1.w + a2.w;
          }
#pragma unroll
          for (int i = 0; i < 9; i++) y[i] += __shfl_xor_sync(0xffffffffu, y[i], 16);
          if (++it > (1 << 20)) __trap();
        } while (!__all_sync(0xffffffffu, y[8] == 3.f * NMOE));
        const int hw = lane >> 4;
        const uint2 xv = __ldg(reinterpret_cast<const uint2*>(x + (size_t)info.y * D_ + ct * 128) + (lane & 15) * 2 + hw);
        const float og = round_bf16(1.0f - lds_bf16(sb + SM_GATE + (info.y & 255) * 2));
        const uint32_t rs2 = pack_bf16(rs, rs);
        const uint32_t t0 = hadd2(xv.x, hmul2(pack_bf16(hw ? y[4] : y[0], hw ? y[5] : y[1]), rs2));
        const uint32_t t1 = hadd2(xv.y, hmul2(pack_bf16(hw ? y[6] : y[2], hw ? y[7] : y[3]), rs2));
        mbar_wait(BAR(B_OP), 0); mbar_wait(BAR(B_OP + 2), 0);
        sts64(sb + SM_UPD + (lane & 8) * 256 + (lane & 7) * 16 + hw * 8,
              __uint_as_float(pack_bf16(og * (bf_lo(t0) - bf_lo(xv.x)), og * (bf_hi(t0) - bf_hi(xv.x)))),
              __uint_as_float(pack_bf16(og * (bf_lo(t1) - bf_lo(xv.y)), og * (bf_hi(t1) - bf_hi(xv.y)))));
        fence_async_smem();
        __syncwarp();
        if (elect_one()) { mbar_arrive(BAR(B_Y)); TSTAMP(39); }
      }
    } else {
      if (aw == 0) mbar_wait(BAR(B_PHI), 0);
      if (elect_one()) load_b2(aw);
      if (aw) {
#pragma unroll 1
        for (int i = 0; i < 16; i++) {
          mbar_wait_bounded(BAR(B_FB2 + i), 0);
          if (i == 0) mbar_wait(BAR(B_OP + half * 2 + aw - 1), 0);
          if (elect_one()) mbar_expect_tx(BAR(B_F2 + (aw - 1) * 16 + i), i ? 8192 : 0);
        }
      }
    }
  } else if (warp >= 8) {
    asm volatile("setmaxnreg.dec.sync.aligned.u32 24;");
    cluster_wait();
    if (tid == 256) TSTAMP(58);
    if (warp != 8) {
      if (elect_one()) {
#pragma unroll 1
        for (int i = B_ST + warp - 9; i < NBAR; i += 3) mbar_init(BAR(i), bar_count(i) + (LEAD2 && i == B_F2 + 32 - LEAD2));
        asm volatile("fence.mbarrier_init.release.cluster;" ::: "memory");
      }
#pragma unroll
      for (int i = 0; i < (ZB + 1535) / 1536; i++) sts128(sb + SM_KVB + (i * 96 + tid - 288) * 16, make_uint4(0, 0, 0, 0));
      if (warp < 11) sts128(sb + SM_ONES + (tid - 288) * 16, make_uint4(0x3f803f80u, 0x3f803f80u, 0x3f803f80u, 0x3f803f80u));
      hand_over_smem(BAR(B_INIT), true);
      if (tid == 288) TSTAMP(57);
    }
    if (warp == 8) {
      int s = NPRE, ph = 1;
#pragma unroll 1
      for (int kt = NPRE; kt < KT; kt++) {
        mbar_wait_bounded(BAR(B_EMPTY + s), ph);
        if (elect_one()) {
          load_stage(kt, s, true);
          const unsigned xc = kt - XR_AFTER;
          if (xc < 4) load_xr(xc);
          const int pg = kt - STAGES - PF_START + PF_OFF;
          if (pg >= (e < NMOE ? PF_OFF : 24) && pg < 26 && (EXPT != 3 || pg >= 24)) {
            const CUtensorMap* tm = &maps.tg + (pg < 16 ? (b & 1) : pg < 24 ? 2 : 3);
            const int c0 = pg < 16 ? (e >> 1) * 64 : 0, c1 = (pg < 16 ? pg : pg < 24 ? e * 8 + pg - 16 : b * 2 + pg - 24) * 64;
            asm volatile("cp.async.bulk.prefetch.tensor.2d.L2.global [%0, {%1, %2}];" :: "l"(tm), "r"(c0), "r"(c1) : "memory");
          }
        }
        if (++s == STAGES) { s = 0; ph ^= 1; }
      }
      mbar_wait(BAR(B_EMPTY + 1), 1);
#pragma unroll 1
      for (int i = 3; i < (XT_IN_A ? NB2 : 5); i++)
        if (elect_one()) { if (!XT_IN_A) load_xt(i - 3); load_b2(i); }
    } else if (warp == 9) {
      const unsigned tag = (ld_relaxed(g_key + b) + 1) & 0xfffu;
      if (elect_one()) {
        mbar_expect_tx(BAR(B_WPHI), 4096);
        tma_load_2d(sb + SM_WPHI, &maps.wphi, 0, hp * 64, BAR(B_WPHI));
      }
      mbar_wait(BAR(B_WPHI), 0);
#pragma unroll 1
      for (uint32_t ad = sb + SM_WPHI + lane * 16; ad < sb + SM_WPHI + 4096; ad += 512) {
        constexpr float L = 1.4426950408889634f;
        const uint4 w = lds128(ad);
        sts128(ad, make_uint4(pack_bf16(bf_lo(w.x) * L, bf_hi(w.x) * L), pack_bf16(bf_lo(w.y) * L, bf_hi(w.y) * L),
                              pack_bf16(bf_lo(w.z) * L, bf_hi(w.z) * L), pack_bf16(bf_lo(w.w) * L, bf_hi(w.w) * L)));
      }
      fence_async_smem();
      mbar_wait(BAR(B_XRD), 0);
      {
        const uint4 k = lds128(sb + SM_KEYS);
        if (lane == 0) st_relaxed(g_key + b, (max(max(k.x, k.y), max(k.z, k.w)) << 12) | tag);
      }
      const unsigned best = __shfl_sync(0xffffffffu, wait_tagged<KEY_SLEEP>(g_bcast + tg * 16, tag), 0);
      const unsigned idx = 2047u - (best & 0x7ffu);
      unsigned u = best >> 16;
      u = (u & 0x8000u) ? (u & 0x7fffu) : (~u & 0xffffu);
      if (elect_one()) {
        sts128(sb + SM_INFO, make_uint4(tag, idx, u << 16, 0));
        mbar_expect_tx(BAR(B_H), 1024);
        mbar_expect_tx(BAR(B_XSEL), 2048);
        bulk_load(sb + SM_XSEL, x + (size_t)idx * D_, 2048, BAR(B_XSEL));
        TSTAMP(32); GSTAMP(61);
        bulk_store(reinterpret_cast<char*>(&g_z) + b * ZB, sb + SM_KVB, ZB);
      }
      bulk_commit(); bulk_wait0();
      fence_gpu();
      __syncwarp();
      if (lane == 0) { st_relaxed(g_key + NCTA + b, tag); TSTAMP(42); }
      int it = 0;
#pragma unroll 1
      for (int c = 0; c < 2; c++) {
        uint4 gv;
        do {
          asm volatile("ld.relaxed.gpu.global.v4.u32 {%0, %1, %2, %3}, [%4];" : "=r"(gv.x), "=r"(gv.y), "=r"(gv.z), "=r"(gv.w)
                       : "l"(g_gate + tg * 256 + c * 128 + lane * 4) : "memory");
          if (++it > (1 << 20)) __trap();
        } while (!__all_sync(0xffffffffu, (((gv.x ^ tag) | (gv.y ^ tag) | (gv.z ^ tag) | (gv.w ^ tag)) & 0xfffu) == 0));
        sts64(sb + SM_GATE + c * 256 + lane * 8, __uint_as_float(__byte_perm(gv.x, gv.y, 0x7632)), __uint_as_float(__byte_perm(gv.z, gv.w, 0x7632)));
      }
      wait_tagged<200>(g_bcast + 128 + tg * 16, tag);
      __syncwarp();
      if (elect_one()) { mbar_arrive(BAR(B_RDY)); TSTAMP(43); }
    } else if (e < NMOE) {
      const int w = warp & 1;
      const CUtensorMap* tm = &maps.wg + rank;
      int c0 = (e >> 1) * 64, c1 = 0, c2 = 4 * w;
      uint32_t bar = BAR(B_MOE + w);
      mbar_wait(BAR(B_XRD), 0);
#pragma unroll 1
      for (int m = 0; m < 12; m++) {
        mbar_wait(bar + (B_MOEE - B_MOE) * 8, ((m >> 1) & 1) ^ 1);
        if (elect_one()) {
          mbar_expect_tx(bar, 8192);
          tma_load_3d(sb + SM_MOE + w * 8192 + (m & 1) * 16384, tm, c0, c1, c2, bar);
        }
        bar ^= 16;
        if (m < 7) c2 += 8; else c1 += 8;
        if (m == 7) { tm = &maps.wd; c0 = 0; c1 = e * 32 + w * 4; c2 = 0; }
      }
    }
    const int wi = warp - 8, st = tid - 256;
    bar_sync(5, 128);
    asm volatile("setmaxnreg.inc.sync.aligned.u32 " STR(REG_K) ";");
    {
      auto kv_half = [&](float (&d)[20], int h, int mb) {
#pragma unroll
        for (int i = 0; i < 8; i++)
          wgmma_ss_n40<1, 1, H128, H64>(d, dlo(SB0 + SM_PHIK + 32768, 16) - h * 2048 + (((i & 2) << 2) + (i & 4) + mb * 2 + (i & 1)) * 128,
                                        dlo(SB0 + SM_V, SM_ONES - SM_V) + (h * 16 + (i & 4) * 2 + mb * 4 + (i & 3)) * (64 - (64 << 16)), (mb | i) != 0);
      };
      auto kv_out = [&](float (&d)[20], int h) {
        fence_regs(d);
        float* dst = g_z.kv + (hp * 2 + h) * KVH + st * 2;
        const int q = lane & 3;
        uint32_t w[8];
#pragma unroll
        for (int i = 0; i < 8; i++) w[i] = pack_bf16(d[2 * i], d[2 * i + 1]);
#pragma unroll
        for (int c = 0; c < 4; c++)
          asm volatile("red.global.add.noftz.v2.bf16x2 [%0], {%1, %2};" :: "l"(dst + c * 256), "r"(w[2 * c]), "r"(q == c ? 0x3f80u : w[2 * c + 1]) : "memory");
        asm volatile("red.global.add.noftz.v2.bf16x2 [%0], {%1, %2};" :: "l"(dst + 1024), "r"((q & 2) ? ((q & 1) ? w[7] : w[5]) : ((q & 1) ? w[3] : w[1])),
                     "r"(q == 0 ? 0x3f80u : q == 1 ? pack_bf16(d[16], d[18]) : 0u) : "memory");
      };
#pragma unroll 1
      for (int h = 0; h < 2; h++) {
        float kv[20];
        mbar_wait_bounded(BAR(B_PHI + h), 0);
        if (st == 0) TSTAMP(23 + h);
        wgmma_fence();
        kv_half(kv, h, 0); kv_half(kv, h, 1);
        wgmma_commit();
        if (KV_BAR && h && wi < 2 && elect_one()) load_xt(wi);
        wgmma_wait<0>();
        if (st == 0) TSTAMP(21 + h);
        kv_out(kv, h);
        if (!KV_BAR) {
          bar_sync(5, 128);
          if (XT_IN_A && h == XT_H && wi < 2 && elect_one()) load_xt(wi);
        }
      }
      if (wi == 3 && elect_one()) mbar_arrive_cluster(BAR(B_PEER) ^ (1u << 24));
      if (st == 0) TSTAMP(13);
      const int f = wi * 16 + (lane & 15), sw = (f >> 1) & 3, chi = lane >> 4;
      uint2 v[10];
      const float* src = g_z.kv + hp * 2 * KVH + st * 2;
      const int q = lane & 3;
      { const unsigned c0 = clock32(); while (clock32() - c0 < KV_DELAY) {} }
      int it = 0;
      unsigned need = 0x3ff;
#pragma unroll
      for (int i = 0; i < 10; i++) v[i] = make_uint2(0, 0);
      do {
        if (++it > (1 << 20)) __trap();
        unsigned bad = 0;
        if (st == 0 && it == 1) TSTAMP(35);
#pragma unroll
        for (int i = 0; i < 10; i++)
          asm volatile("{\n.reg .pred p;\nsetp.ne.u32 p, %3, 0;\n@p ld.relaxed.gpu.global.v2.u32 {%0, %1}, [%2];\n}"
                       : "+r"(v[i].x), "+r"(v[i].y) : "l"(src + i * 256), "r"(need & (1u << i)) : "memory");
#pragma unroll
        for (int i = 0; i < 10; i++) bad |= (v[i].y != 0x4100u) << i;
        need = __reduce_or_sync(0xffffffffu, bad & ((0x21u << q) | (q ? 0u : 0x210u)));
        if (st == 0 && it == 1) TSTAMP(20);
      } while (need);
      uint32_t zz[2];
#pragma unroll
      for (int h = 0; h < 2; h++) {
        const uint2* w = v + h * 5;
        const uint32_t kb = sb + SM_KVB + h * 4096 + f * 64;
        zz[h] = __shfl_sync(0xffffffffu, w[4].y, (lane & 28) + 1);
        stsm4(kb + ((chi ^ sw) << 4), w[0].x, q == 0 ? w[4].x : w[0].y, w[1].x, q == 1 ? w[4].x : w[1].y);
        stsm4(kb + (((2 + chi) ^ sw) << 4), w[2].x, q == 2 ? w[4].x : w[2].y, w[3].x, q == 3 ? w[4].x : w[3].y);
      }
      stsm4(sb + SM_KVB + 8192 + f * 64 + ((chi ^ sw) << 4), zz[0], zz[0] >> 16, zz[1], zz[1] >> 16);
      fence_async_smem();
      __syncwarp();
      if (elect_one()) mbar_arrive(BAR(B_KVB));
    }
    {
      const int pm = wi >> 1;
      if (wi & 1) {
        const int hf = half ^ pm;
        mbar_wait(BAR(B_PEER), 0);
        mbar_wait_bounded(BAR(B_OP + hf * 2), 0);
        const unsigned c0 = clock32();
        while (clock32() - c0 < (unsigned)(pm ? LATE_DELAY + ct * LATE_STEP : (ct >> 2) * URG_STEP)) {}
        __syncwarp();
        auto to_partner = [&](int mb) {
          asm volatile("cp.async.bulk.shared::cluster.shared::cta.mbarrier::complete_tx::bytes [%0], [%1], 8192, [%2];"
                       :: "r"((sb ^ (1u << 24)) + SM_RA + mb * 8192), "r"(sb + SM_O + mb * 8192), "r"(BAR(B_F2 + mb * 16 + 1) ^ (1u << 24)) : "memory");
        };
        uint4* hint = g_z.hint + (tg * 2 + hf) * 32 + hp;
#pragma unroll 1
        for (int mb = 0; mb < 2; mb++) {
          if (mb) mbar_wait(BAR(B_OP + hf * 2 + 1), 0);
          if (elect_one()) {
            bulk_store(o_piece(hf, mb, hp), sb + SM_O + pm * 16384 + mb * 8192, 8192);
            if (HINT_BULK >= 1 + pm) bulk_store(hint + mb * 16, sb + SM_ONES, 16);
            if (!pm) to_partner(mb);
          }
          bulk_commit();
          if (pm) {
            bulk_wait0();
            __syncwarp();
            if (HINT_BULK < 2 && lane == 0) st_relaxed(&hint[mb * 16].x, 1);
          }
          if (lane == 0) TSTAMP((pm ? 37 : 15) + mb);
        }
        bulk_wait0();
        __syncwarp();
        if (lane == 0) mbar_arrive(BAR(B_ST + pm));
        if (pm == 0) {
          if (lane < 2) mbar_arrive_cluster((lane << 24) + SB0 + SM_BAR + 8 * (B_GO + NA2));
          mbar_wait(BAR(B5_AFTER), 0);
#pragma unroll 1
          for (int i = XT_IN_A ? NB2 : 5; i < 16; i++) {
            mbar_wait(i < NB2 ? BAR(B_XTD) : BAR(B_DB + i - NB2), 0);
            if (elect_one()) load_b2(i);
          }
        } else {
          mbar_wait(BAR(B_ST), 0);
          fence_gpu();
          if (lane == 0) st_relaxed(g_z.done + b, 1);
        }
      } else if (pm) {
        const __nv_bfloat16* src = o_piece(half, rank, half * 8);
        uint32_t dst = sb + SM_RA + 16384 + rank * 8192;
        mbar_wait(BAR(B_PEER), 0);
#pragma unroll 1
        for (int i = 2; i < 16; i++) {
          if (i == (ct & 6) + 2) src += 2 * 4096;
          if (i == 8) src -= half * 16 * 4096;
          mbar_wait_bounded(BAR(B_GO + i), 0);
          if (elect_one()) {
            asm volatile("cp.async.bulk.shared::cluster.global.mbarrier::complete_tx::bytes.multicast::cluster [%0], [%1], 8192, [%2], %3;"
                         :: "r"(dst), "l"(src), "r"(BAR(B_F2 + rank * 16 + i)), "h"((uint16_t)3) : "memory");
            if (i == 2) TSTAMP(19);
          }
          src += 4096;
          dst += (i == 5 || i == 10) ? -4 * 16384 : 16384;
        }
      } else {
        const unsigned* flag = &g_z.hint[(tg * 2 + half) * 32 + rank * 16 + slice_of(lane & 15)].x;
        bool seen = lane < 2 || lane > 15;
        mbar_wait(BAR(B_OP + half * 2 + rank), 0);
        int it = 0;
        do {
          if (ld_relaxed(flag) != 0 && !seen) {
            mbar_arrive(BAR(B_GO) + lane * 8);
            seen = true;
          }
          if (++it > (1 << 20)) __trap();
        } while (!__all_sync(0xffffffffu, seen));
      }
    }
  } else {
    asm volatile("setmaxnreg.inc.sync.aligned.u32 224;");
    const int wg = warp >> 2, wi = warp & 3;
    cluster_wait();
    if (tid == 0) TSTAMP(59);
    float acc0[96], acc1[96];
    {
      int s = 0, ph = 0, sprev = 0;
#pragma unroll 1
      for (int kt = 0; kt < KT - STAGES; kt++) {
        mbar_wait(BAR(B_FULL + s), ph);
        if (kt == 0 && tid == 0) TSTAMP(1);
        if (tid == 0 && !(kt & 1)) TSTAMP(44 + kt / 2);
        const uint32_t da = dlo(SB0 + SM_RA, 16) + s * (A_BYTES >> 4) + wg * 512;
        const uint32_t db = dlo(SB0 + SM_RB, 4096) + s * (B_BYTES >> 4);
        wgmma_fence();
#pragma unroll
        for (int k = 0; k < 2; k++) {
          wgmma_ss_n192<0, 1, H64, H128>(acc0, da + k * 2, db + k * 128, (kt | k) != 0);
          wgmma_ss_n192<0, 1, H64, H128>(acc1, da + 256 + k * 2, db + k * 128, (kt | k) != 0);
        }
        wgmma_commit();
        wgmma_wait<1>();
        if (kt > 0 && wi < 2 && elect_one()) mbar_arrive_cluster((wi << 24) + SB0 + SM_BAR + 8 * (B_EMPTY + sprev));
        sprev = s;
        if (++s == STAGES) { s = 0; ph ^= 1; }
      }
#pragma unroll 1
      for (int kt = 0; kt < STAGES; kt++) {
        mbar_wait(BAR(B_FULL + s), ph);
        const uint32_t da = dlo(SB0 + SM_RA, 16) + s * (A_BYTES >> 4) + wg * 512;
        const uint32_t db = dlo(SB0 + SM_RB, 4096) + s * (B_BYTES >> 4);
        wgmma_fence();
        wgmma_ss_n192<0, 1, H64, H128>(acc0, da, db, 1);
        wgmma_ss_n192<0, 1, H64, H128>(acc0, da + 2, db + 128, 1);
        wgmma_commit();
        wgmma_wait<1>();
        if (kt == 0 && wi < 2 && elect_one()) mbar_arrive_cluster((wi << 24) + SB0 + SM_BAR + 8 * (B_EMPTY + 1));
        if (++s == STAGES) { s = 0; ph ^= 1; }
      }
      mbar_wait(BAR(B_RDY), 0);
    }
    const int trow = wg * 128 + wi * 16 + (lane & 15);
    const int chi = lane >> 4;
    uint32_t ak[16], aq[2][16];
    float p[4][16];
    auto catch_one = [&](int i) {
      const int s = (2 + (i >> 1)) % STAGES;
      wgmma_ss_n192<0, 1, H64, H128>(acc1, dlo(SB0 + SM_RA + s * A_BYTES + 4096 + (i & 1) * 32, 16) + wg * 512, dlo(SB0 + SM_RB + s * B_BYTES + (i & 1) * 2048, 4096), 1);
    };
    auto catch_up = [&](int s) { wgmma_fence(); catch_one(2 * s - 4); catch_one(2 * s - 3); wgmma_commit(); };
    auto store_v = [&](const float (&acc)[96], int mb) {
#pragma unroll
      for (int h = 0; h < 2; h++)
#pragma unroll
        for (int jj = 0; jj < 2; jj++) {
          const int o = 64 + h * 16 + jj * 8;
          stsm4(sb + SM_V + h * 16384 + (trow + mb * 64) * 64 + (((2 * jj + chi) ^ ((trow >> 1) & 3)) << 4),
                pack_bf16(acc[o], acc[o + 1]), pack_bf16(acc[o + 2], acc[o + 3]), pack_bf16(acc[o + 4], acc[o + 5]), pack_bf16(acc[o + 6], acc[o + 7]));
        }
    };
    const uint32_t pa = sb + SM_PHIK + (wi >> 1) * 16384 + wg * 8192 + (trow & 31) * 128 + ((chi ^ (trow & 7)) << 4);
    auto store_phi = [&](const uint32_t (&phi)[16], int h, int mb) { store_phi_k(phi, pa + (1 - h) * 32768 + mb * 4096); };
    auto hand_over = [&](int i, bool ok) { hand_over_smem(BAR(B_PHI + i), ok); };
    bool okk[3];
    {
      HState hs;
      uint32_t phi[16];
      float d0, d1;
      catch_up(2);
      wgmma_wait<1>();
      fence_regs(acc0);
      if (tid == 0) TSTAMP(2);
      store_v(acc0, 0);
      pack_frags<32>(acc0, ak);
      issue_feat(ak, p[0], p[1], SB0 + SM_WPHI);
      catch_up(3);
      pack_frags<0>(acc0, aq[0]);
      wgmma_wait<1>();
      fence_regs(p[0]); fence_regs(p[1]); keep_alive(ak);
      wgmma_fence();
#pragma unroll
      for (int i = 4; i < 4 + NFIRST; i++) catch_one(i);
      okk[0] = hedgehog_fast<true>(p[0], phi, d0, d1);
      store_phi(phi, 0, 0);
#pragma unroll
      for (int i = 4 + NFIRST; i < 12; i++) catch_one(i);
      wgmma_commit();
      okk[0] &= hedgehog_fast<true>(p[1], phi, d0, d1);
      store_phi(phi, 1, 0);
      if (tid == 0) TSTAMP(17);
      wgmma_wait<0>();
      fence_regs(acc1);
      if (tid == 0) TSTAMP(27);
      if (wi < 2 && elect_one()) mbar_arrive_cluster((wi << 24) + SB0 + SM_BAR + 8 * (B_EMPTY + 1));
      pack_frags<32>(acc1, ak);
      issue_feat(ak, p[2], p[3], SB0 + SM_WPHI);
      store_v(acc1, 1);
      pack_frags<0>(acc1, aq[1]);
      wgmma_wait<0>();
      fence_regs(p[2]); fence_regs(p[3]); keep_alive(ak);
      asm volatile("setmaxnreg.dec.sync.aligned.u32 " STR(REG_C) ";");
      if (tid == 0) TSTAMP(28);
      HState h2;
      hedgehog_fast1<QUAD>(p[2], hs);
      hedgehog_fast1<QUAD>(p[3], h2);
      okk[1] = __all_sync(0xffffffffu, okk[0] & hedgehog_fast2<true>(hs, phi, d0, d1));
      store_phi(phi, 0, 1);
      hand_over(0, okk[1]);
      h2.s[0] += lds_f32(sb + SM_INFO + 12);
      okk[2] = __all_sync(0xffffffffu, okk[0] & hedgehog_fast2<true>(h2, phi, d0, d1));
      store_phi(phi, 1, 1);
      hand_over(1, okk[2]);
    }
    if (__builtin_expect(!(okk[1] & okk[2]), 0)) {
      __align__(16) float buf[64];
#pragma unroll
      for (int i = 0; i < 64; i++) buf[i] = p[i >> 4][i & 15];
      redo_phi_k(buf, okk[1] * 5 + okk[2] * 10, pa, BAR(B_PHI));
    }
    if (wi == 0 && lane == 0) TSTAMP(wg ? 29 : 3);
    uint32_t pq[4][16];
    float sc[8];
    issue_feat(aq[0], p[0], p[1], SB0 + SM_WPHI);
    issue_feat(aq[1], p[2], p[3], SB0 + SM_WPHI);
    mbar_wait(BAR(Q_AFTER), 0);
    wgmma_wait<0>();
#pragma unroll
    for (int u = 0; u < 4; u++) fence_regs(p[u]);
    keep_alive(aq[0]); keep_alive(aq[1]);
    if (tid == 0) TSTAMP(4);
    {
      bool ok = true;
#pragma unroll
      for (int u = 0; u < 4; u++) ok &= hedgehog_fast<false>(p[u], pq[u], sc[2 * u], sc[2 * u + 1]);
      if (__builtin_expect(!__all_sync(0xffffffffu, ok), 0)) {
        __align__(16) float buf[64];
#pragma unroll
        for (int i = 0; i < 64; i++) buf[i] = p[i >> 4][i & 15];
        hedgehog_slow(buf, 4);
#pragma unroll
        for (int i = 0; i < 64; i++) pq[i >> 4][i & 15] = __float_as_uint(buf[i]);
#pragma unroll
        for (int i = 0; i < 8; i++) sc[i] = 1.0f;
      }
    }
    if (tid == 0) TSTAMP(5);
    float acc[64];
    const int wq = wg ^ half;
    const uint32_t xo = wq * 8192 + wi * 2048 + (lane & 15) * 128 + ((chi ^ (lane & 7)) << 4);
    const uint32_t ga = sb + SM_GATE + (half * 128 + wq * 64 + wi * 16) * 2 + (lane >> 2) * 2;
    mbar_wait(BAR(B_XT + wq), 0);
    float gt[4];
#pragma unroll
    for (int i = 0; i < 4; i++) gt[i] = lds_bf16(sb + SM_GATE + (wg * 128 + (i >> 1) * 64 + wi * 16 + (i & 1) * 8 + (lane >> 2)) * 2);
    const float g0 = lds_bf16(ga), g1 = lds_bf16(ga + 16);
    const unsigned routed = lds_u32(sb + SM_INFO + 4);
    const uint32_t par = lds_u32(sb + SM_INFO) & 1, tmask = (lane & 3) ? ~0u : ~1u, tbit = (lane & 3) ? 0u : par;
    mbar_wait(BAR(B_KVB), 0);
    if (tid == 0) TSTAMP(7);
    if (wg != half) mbar_wait(BAR(B_OP + half * 2 + O_YIELD - 1), 0);
    {
      float nd[4][20];
#pragma unroll
      for (int u = 0; u < 4; u++)
#pragma unroll
        for (int i = 0; i < 16; i++) asm volatile("" : "+r"(pq[u][i]) :: "memory");
      auto num = [&](int mb, int k0, int k1) {
#pragma unroll
        for (int kk = k0; kk < k1; kk++)
#pragma unroll
          for (int h = 0; h < 2; h++) {
            const int u = mb * 2 + h;
            wgmma_rs_n40<1, H64>(nd[u], pq[u][4 * kk], pq[u][4 * kk + 1], pq[u][4 * kk + 2], pq[u][4 * kk + 3],
                                 dlo(SB0 + SM_KVB + h * 4096 + kk * 1024, 8192 - h * 4096 + h * 16), kk != 0);
          }
        wgmma_commit();
      };
      wgmma_fence();
      num(0, 0, 4);
      if (O_OVL == 2) num(1, 0, 4);
#pragma unroll
      for (int mb = 0; mb < 2; mb++) {
        if (O_OVL == 2 && mb == 0) wgmma_wait<1>(); else wgmma_wait<0>();
        fence_regs(nd[2 * mb]); fence_regs(nd[2 * mb + 1]);
        if (O_OVL == 1 && mb == 0) { wgmma_fence(); num(1, 0, 4); }
        if (tid == 0 && mb == 0) TSTAMP(18);
#pragma unroll
        for (int h = 0; h < 2; h++) {
          const int u = mb * 2 + h;
          const float i0 = gt[2 * mb] * rcp(fmaf(sc[2 * u], 1e-6f, nd[u][16])), i1 = gt[2 * mb + 1] * rcp(fmaf(sc[2 * u + 1], 1e-6f, nd[u][18]));
#pragma unroll
          for (int jj = 0; jj < 2; jj++) {
            const int o = jj * 8;
            stsm4(sb + SM_O + (wg ^ half) * 16384 + ((trow & 63) + mb * 64) * 128 + (((h * 4 + 2 * jj + chi) ^ (trow & 7)) << 4),
                  (pack_bf16(nd[u][o] * i0, nd[u][o + 1] * i0) & tmask) | tbit, (pack_bf16(nd[u][o + 2] * i1, nd[u][o + 3] * i1) & tmask) | tbit,
                  pack_bf16(nd[u][o + 4] * i0, nd[u][o + 5] * i0), pack_bf16(nd[u][o + 6] * i1, nd[u][o + 7] * i1));
          }
        }
        fence_async_smem();
        __syncwarp();
        if (elect_one()) mbar_arrive(BAR(B_OP + wg * 2 + mb));
        if (!O_OVL && mb == 0) { wgmma_fence(); num(1, 0, 4); }
      }
#pragma unroll
      for (int u = 0; u < 4; u++)
#pragma unroll
        for (int i = 0; i < 16; i++) asm volatile("" :: "r"(pq[u][i]) : "memory");
    }
    if (tid == 0) TSTAMP(8);
    uint32_t stale = 0;
    {
      const uint32_t ca = sb - SB0 - (dlo(0, 16) << 4) + wi * 2048 + (lane >> 2) * 128 + ((((lane & 3) * 2) ^ (lane >> 2)) << 4);
      const uint32_t da_end = dlo(SB0 + SM_RA + NA2 * 16384, 16) + wq * 512, f_end = BAR(B_F2 + wq * 16 + 16);
      uint32_t da = da_end - 1024, db = dlo(SB0 + SM_RB + 4 * 16384, 8192), f = f_end - 128;
      uint32_t xs[32];
#pragma unroll
      for (int i = 0; i < 2; i++) {
        mbar_wait(f + i * 8, 0);
        wgmma_fence();
#pragma unroll
        for (int k = 0; k < 4; k++) wgmma_ss_n128<0, 1, H128, H128>(acc, da - i * 4096 + k * 2, db + i * 1024 + k * 128, (i | k) != 0);
        wgmma_commit();
        if (i == 0) {
#pragma unroll
          for (int jj = 0; jj < 8; jj++)
            ldsm4(((sb + SM_XT + xo) ^ ((jj & 3) << 5)) + (jj >> 2) * 16384, xs[4 * jj], xs[4 * jj + 1], xs[4 * jj + 2], xs[4 * jj + 3]);
          fence_async_smem();
          __syncwarp();
          if (elect_one()) mbar_arrive_cluster(((XT_IN_A ? wq : rank) << 24) + SB0 + SM_BAR + 8 * (XT_IN_A ? B_GO + 3 : B_XTD));
        }
      }
      const float og0 = round_bf16(1.0f - g0), og1 = round_bf16(1.0f - g1);
      da -= 3072; db += 2048; f += 16;
      wgmma_wait<0>();
      fence_regs(acc);
      uint32_t dn = SB0 + SM_BAR + (wi ? (wq << 24) + 8 * (B_GO + NA2) : (rank << 24) + 8 * B_DB);
      if (wi < 2 && elect_one()) mbar_arrive_cluster(dn);
#pragma unroll
      for (int i = 0; i < 32; i++) { acc[2 * i] = fmaf((i & 1) ? og1 : og0, bf_lo(xs[i]), acc[2 * i]); acc[2 * i + 1] = fmaf((i & 1) ? og1 : og0, bf_hi(xs[i]), acc[2 * i + 1]); }
      fence_regs(acc);
      bool got = false;
#pragma unroll 1
      do {
        if (!got) mbar_wait(f, 0);
        wgmma_fence();
        wgmma_ss_n128<0, 1, H128, H128>(acc, da, db, 1);
        const uint32_t ta = ca + (da << 4), t0 = lds_u32(ta), t1 = lds_u32(ta + 1024);
        got = mbar_test(f + 8, 0);
#pragma unroll
        for (int k = 1; k < 4; k++) wgmma_ss_n128<0, 1, H128, H128>(acc, da + k * 2, db + k * 128, 1);
        wgmma_commit();
        da += 1024; if (da == da_end) da -= NA2 * 1024;
        db += 1024; if (db == dlo(SB0 + SM_RB + NB2 * 16384, 8192)) db -= NB2 * 1024;
        f += 8;
        stale |= (t0 ^ par) | (t1 ^ par);
        if (LEAD2 && wq == 0 && wi == 2 && f == f_end - 8 * LEAD_AT && elect_one()) mbar_arrive(BAR(B_F2 + 32 - LEAD2));
        wgmma_wait<1>();
        dn += 8;
        if (wi < 2 && f <= f_end - 32 && elect_one()) mbar_arrive_cluster(dn);
      } while (f != f_end);
      if (__builtin_expect((routed >> 6) == tg * 4 + half * 2 + wq && EXPT != 12, 0)) {
        const unsigned r = (routed & 63) - wi * 16 - (lane >> 2);
        const uint32_t one = (lane & 3) ? 0u : 0x3f80u;
        mbar_wait_bounded(BAR(B_Y), 0);
        wgmma_fence();
        wgmma_rs_n128<1, H128>(acc, r == 0 ? one : 0u, r == 8 ? one : 0u, 0, 0, dlo(SB0 + SM_UPD, 2048), 1);
        wgmma_commit();
      }
      const uint32_t xa = sb + SM_RA + xo, xt = sb + SM_RA + wq * 8192 + wi * 2048;
      const int orow = tg * 256 + half * 128 + wq * 64 + wi * 16;
      const bool redo = __any_sync(0xffffffffu, stale & 1);
      wgmma_wait<0>();
      fence_regs(acc);
      if (wi == 0 && lane == 0) TSTAMP(wq ? 25 : 11);
      stage_out<0, 4>(acc, xa);
      fence_async_smem();
      __syncwarp();
      if (!redo && elect_one()) tma_store_2d(&maps.out, xt, ct * 128, orow);
      stage_out<4, 8>(acc, xa);
      if (__builtin_expect(redo, 0))
        redo_rows(x, wo, sb, b, wq, xa);
      fence_async_smem();
      __syncwarp();
      if (elect_one()) {
        tma_store_2d(&maps.out, xt + 16384, ct * 128 + 64, orow);
        if (redo) tma_store_2d(&maps.out, xt, ct * 128, orow);
      }
      bulk_commit();
      bulk_wait0_read();
    }
  }
}

typedef CUresult (*PFN_encodeTiled)(CUtensorMap*, CUtensorMapDataType, cuuint32_t, void*, const cuuint64_t*, const cuuint64_t*,
                                    const cuuint32_t*, const cuuint32_t*, CUtensorMapInterleave, CUtensorMapSwizzle,
                                    CUtensorMapL2promotion, CUtensorMapFloatOOBfill);
static void make_map(PFN_encodeTiled fn, CUtensorMap* m, const void* ptr, uint64_t rows, uint64_t cols, uint32_t brows, uint32_t bcols,
                     CUtensorMapSwizzle sw, CUtensorMapL2promotion prom) {
  cuuint64_t dims[2] = {cols, rows}; cuuint64_t strides[1] = {cols * 2}; cuuint32_t box[2] = {bcols, brows}; cuuint32_t es[2] = {1, 1};
  fn(m, CU_TENSOR_MAP_DATA_TYPE_BFLOAT16, 2, const_cast<void*>(ptr), dims, strides, box, es, CU_TENSOR_MAP_INTERLEAVE_NONE, sw, prom,
     CU_TENSOR_MAP_FLOAT_OOB_FILL_NONE);
}

extern "C" void kernel_launch(void* const* d_in, const int* in_sizes, int n_in, void* d_out, int out_size) {
  const __nv_bfloat16* x = (const __nv_bfloat16*)d_in[0];
  const __nv_bfloat16* wqkv = (const __nv_bfloat16*)d_in[1];
  const __nv_bfloat16* wphi = (const __nv_bfloat16*)d_in[2];
  const __nv_bfloat16* wo = (const __nv_bfloat16*)d_in[3];
  const __nv_bfloat16* w_r = (const __nv_bfloat16*)d_in[5];
  const __nv_bfloat16* w_gate = (const __nv_bfloat16*)d_in[6];
  const __nv_bfloat16* w_up = (const __nv_bfloat16*)d_in[7];
  const __nv_bfloat16* w_down = (const __nv_bfloat16*)d_in[8];
  const __nv_bfloat16* gate_w = (const __nv_bfloat16*)d_in[9];
  void* fp = nullptr; cudaDriverEntryPointQueryResult qr;
  cudaGetDriverEntryPoint("cuTensorMapEncodeTiled", &fp, cudaEnableDefault, &qr);
  PFN_encodeTiled fn = (PFN_encodeTiled)fp;
  Maps m;
  const CUtensorMapL2promotion P128 = CU_TENSOR_MAP_L2_PROMOTION_L2_128B;
  make_map(fn, &m.x, x, S_, D_, 128, 32, CU_TENSOR_MAP_SWIZZLE_64B, P128);
  {
    cuuint64_t dims[3] = {D_, D_, 3}; cuuint64_t strides[2] = {3 * D_ * 2, D_ * 2}; cuuint32_t box[3] = {64, 32, 3}; cuuint32_t es[3] = {1, 1, 1};
    fn(&m.w, CU_TENSOR_MAP_DATA_TYPE_BFLOAT16, 3, (void*)wqkv, dims, strides, box, es, CU_TENSOR_MAP_INTERLEAVE_NONE,
       CU_TENSOR_MAP_SWIZZLE_128B, P128, CU_TENSOR_MAP_FLOAT_OOB_FILL_NONE);
  }
  {
    cuuint64_t dims[3] = {64, D_, 16}; cuuint64_t strides[2] = {D_ * 2, 128}; cuuint32_t box[3] = {64, 64, 2}; cuuint32_t es[3] = {1, 1, 1};
    fn(&m.wo, CU_TENSOR_MAP_DATA_TYPE_BFLOAT16, 3, (void*)wo, dims, strides, box, es, CU_TENSOR_MAP_INTERLEAVE_NONE,
       CU_TENSOR_MAP_SWIZZLE_128B, P128, CU_TENSOR_MAP_FLOAT_OOB_FILL_NONE);
  }
  make_map(fn, &m.wphi, wphi, 1024, 32, 64, 32, CU_TENSOR_MAP_SWIZZLE_64B, P128);
  for (int i = 0; i < 3; i++) {
    cuuint64_t dims[3] = {i < 2 ? (cuuint64_t)F_ : 64, i < 2 ? (cuuint64_t)16 : F_, i < 2 ? (cuuint64_t)64 : 16};
    cuuint64_t strides[2] = {i < 2 ? (cuuint64_t)F_ * 2 : D_ * 2, i < 2 ? (cuuint64_t)F_ * 32 : 128};
    cuuint32_t box[3] = {64, i < 2 ? 16u : 4u, i < 2 ? 4u : 16u}; cuuint32_t es[3] = {1, 1, 1};
    fn(&m.wg + i, CU_TENSOR_MAP_DATA_TYPE_BFLOAT16, 3, (void*)(i == 0 ? w_gate : i == 1 ? w_up : w_down), dims, strides, box, es,
       CU_TENSOR_MAP_INTERLEAVE_NONE, CU_TENSOR_MAP_SWIZZLE_NONE, P128, CU_TENSOR_MAP_FLOAT_OOB_FILL_NONE);
  }
  make_map(fn, &m.xt, x, S_, D_, 64, 64, CU_TENSOR_MAP_SWIZZLE_128B, P128);
  make_map(fn, &m.out, d_out, S_, D_, 16, 64, CU_TENSOR_MAP_SWIZZLE_128B, P128);
  make_map(fn, &m.xr, x, S_, D_, 16, 128, CU_TENSOR_MAP_SWIZZLE_NONE, P128);
  make_map(fn, &m.tg, w_gate, D_, F_, 64, 64, CU_TENSOR_MAP_SWIZZLE_NONE, P128);
  make_map(fn, &m.tu, w_up, D_, F_, 64, 64, CU_TENSOR_MAP_SWIZZLE_NONE, P128);
  make_map(fn, &m.td, w_down, F_ * 16, 64, 64, 64, CU_TENSOR_MAP_SWIZZLE_NONE, P128);
  make_map(fn, &m.to, wo, D_ * 16, 64, 64, 64, CU_TENSOR_MAP_SWIZZLE_NONE, P128);
  cudaFuncSetAttribute(fused_kernel, cudaFuncAttributeMaxDynamicSharedMemorySize, SM_TOTAL);
  fused_kernel<<<NCTA + 2, 512, SM_TOTAL>>>(m, x, wo, w_r, gate_w);
}
```

```cpp
#include <cuda_runtime.h>
#include <cuda_bf16.h>
#include <cuda.h>
#include <stdint.h>

__device__ __forceinline__ uint32_t smem_u32(const void* p) { return (uint32_t)__cvta_generic_to_shared(p); }
__device__ __forceinline__ void mbar_init(uint32_t bar, uint32_t cnt) { asm volatile("mbarrier.init.shared::cta.b64 [%0], %1;" :: "r"(bar), "r"(cnt) : "memory"); }
__device__ __forceinline__ void mbar_expect_tx(uint32_t bar, uint32_t bytes) { asm volatile("mbarrier.arrive.expect_tx.shared::cta.b64 _, [%0], %1;" :: "r"(bar), "r"(bytes) : "memory"); }
__device__ __forceinline__ void mbar_arrive(uint32_t bar) { asm volatile("mbarrier.arrive.shared::cta.b64 _, [%0];" :: "r"(bar) : "memory"); }
__device__ __forceinline__ bool mbar_try_wait(uint32_t bar, uint32_t parity) {
  uint32_t ok;
  asm volatile("{\n.reg .pred p;\nmbarrier.try_wait.parity.shared::cta.b64 p, [%1], %2;\nselp.u32 %0, 1, 0, p;\n}" : "=r"(ok) : "r"(bar), "r"(parity) : "memory");
  return ok;
}
__device__ __forceinline__ bool mbar_test(uint32_t bar, uint32_t parity) {
  uint32_t ok;
  asm volatile("{\n.reg .pred p;\nmbarrier.test_wait.parity.shared::cta.b64 p, [%1], %2;\nselp.u32 %0, 1, 0, p;\n}" : "=r"(ok) : "r"(bar), "r"(parity) : "memory");
  return ok;
}
__device__ __forceinline__ void mbar_wait(uint32_t bar, uint32_t parity) {
  asm volatile("{\n.reg .pred p;\nWAIT: mbarrier.try_wait.parity.shared::cta.b64 p, [%0], %1;\n@!p bra.uni WAIT;\n}" :: "r"(bar), "r"(parity) : "memory");
}
__device__ __forceinline__ void mbar_wait_bounded(uint32_t bar, uint32_t parity) {
#pragma unroll 1
  for (int it = 0; it < (1 << 22); it++) { if (mbar_try_wait(bar, parity)) return; }
  __trap();
}
__device__ __forceinline__ void tma_load_2d(uint32_t dst, const CUtensorMap* tm, int c0, int c1, uint32_t bar) {
  asm volatile("cp.async.bulk.tensor.2d.shared::cluster.global.mbarrier::complete_tx::bytes [%0], [%1, {%3, %4}], [%2];"
    :: "r"(dst), "l"(tm), "r"(bar), "r"(c0), "r"(c1) : "memory");
}
__device__ __forceinline__ void tma_load_2d_mc(uint32_t dst, const CUtensorMap* tm, int c0, int c1, uint32_t bar) {
  asm volatile("cp.async.bulk.tensor.2d.shared::cluster.global.mbarrier::complete_tx::bytes.multicast::cluster [%0], [%1, {%3, %4}], [%2], %5;"
    :: "r"(dst), "l"(tm), "r"(bar), "r"(c0), "r"(c1), "h"((uint16_t)3) : "memory");
}
__device__ __forceinline__ void mbar_arrive_cluster(uint32_t bar) { asm volatile("mbarrier.arrive.shared::cluster.b64 _, [%0];" :: "r"(bar) : "memory"); }
__device__ __forceinline__ void wgmma_fence() { asm volatile("wgmma.fence.sync.aligned;" ::: "memory"); }
__device__ __forceinline__ void wgmma_commit() { asm volatile("wgmma.commit_group.sync.aligned;" ::: "memory"); }
template <int N> __device__ __forceinline__ void wgmma_wait() { asm volatile("wgmma.wait_group.sync.aligned %0;" :: "n"(N) : "memory"); }
template <int N> __device__ __forceinline__ void fence_regs(float (&d)[N]) {
#pragma unroll
  for (int i = 0; i < N; i++) asm volatile("" : "+f"(d[i]) :: "memory");
}
__host__ __device__ constexpr uint32_t dlo(uint32_t addr, uint32_t lbo) { return (addr >> 4) | ((lbo >> 4) << 16); }
constexpr uint32_t H128 = (1024 >> 4) | (1u << 30);
constexpr uint32_t H64 = (512 >> 4) | (2u << 30);

template <int TA, int TB, uint32_t HA, uint32_t HB>
__device__ __forceinline__ void wgmma_ss_n192(float (&d)[96], uint32_t da, uint32_t db, int scale_d) {
  asm volatile("{\n.reg .pred p;\n.reg .b64 da, db;\nsetp.ne.b32 p, %98, 0;\nmov.b64 da, {%96, %101};\nmov.b64 db, {%97, %102};\n"
    "wgmma.mma_async.sync.aligned.m64n192k16.f32.bf16.bf16 {%0, %1, %2, %3, %4, %5, %6, %7, %8, %9, %10, %11, %12, %13, %14, %15, %16, %17, %18, %19, %20, %21, %22, %23, %24, %25, %26, %27, %28, %29, %30, %31, %32, %33, %34, %35, %36, %37, %38, %39, %40, %41, %42, %43, %44, %45, %46, %47, %48, %49, %50, %51, %52, %53, %54, %55, %56, %57, %58, %59, %60, %61, %62, %63, %64, %65, %66, %67, %68, %69, %70, %71, %72, %73, %74, %75, %76, %77, %78, %79, %80, %81, %82, %83, %84, %85, %86, %87, %88, %89, %90, %91, %92, %93, %94, %95}, da, db, p, 1, 1, %99, %100;\n}\n"
    : "+f"(d[0]), "+f"(d[1]), "+f"(d[2]), "+f"(d[3]), "+f"(d[4]), "+f"(d[5]), "+f"(d[6]), "+f"(d[7]), "+f"(d[8]), "+f"(d[9]), "+f"(d[10]), "+f"(d[11]), "+f"(d[12]), "+f"(d[13]), "+f"(d[14]), "+f"(d[15]), "+f"(d[16]), "+f"(d[17]), "+f"(d[18]), "+f"(d[19]), "+f"(d[20]), "+f"(d[21]), "+f"(d[22]), "+f"(d[23]), "+f"(d[24]), "+f"(d[25]), "+f"(d[26]), "+f"(d[27]), "+f"(d[28]), "+f"(d[29]), "+f"(d[30]), "+f"(d[31]), "+f"(d[32]), "+f"(d[33]), "+f"(d[34]), "+f"(d[35]), "+f"(d[36]), "+f"(d[37]), "+f"(d[38]), "+f"(d[39]), "+f"(d[40]), "+f"(d[41]), "+f"(d[42]), "+f"(d[43]), "+f"(d[44]), "+f"(d[45]), "+f"(d[46]), "+f"(d[47]), "+f"(d[48]), "+f"(d[49]), "+f"(d[50]), "+f"(d[51]), "+f"(d[52]), "+f"(d[53]), "+f"(d[54]), "+f"(d[55]), "+f"(d[56]), "+f"(d[57]), "+f"(d[58]), "+f"(d[59]), "+f"(d[60]), "+f"(d[61]), "+f"(d[62]), "+f"(d[63]), "+f"(d[64]), "+f"(d[65]), "+f"(d[66]), "+f"(d[67]), "+f"(d[68]), "+f"(d[69]), "+f"(d[70]), "+f"(d[71]), "+f"(d[72]), "+f"(d[73]), "+f"(d[74]), "+f"(d[75]), "+f"(d[76]), "+f"(d[77]), "+f"(d[78]), "+f"(d[79]), "+f"(d[80]), "+f"(d[81]), "+f"(d[82]), "+f"(d[83]), "+f"(d[84]), "+f"(d[85]), "+f"(d[86]), "+f"(d[87]), "+f"(d[88]), "+f"(d[89]), "+f"(d[90]), "+f"(d[91]), "+f"(d[92]), "+f"(d[93]), "+f"(d[94]), "+f"(d[95])
    : "r"(da), "r"(db), "r"(scale_d), "n"(TA), "n"(TB), "n"(HA), "n"(HB));
}

template <int TA, int TB, uint32_t HA, uint32_t HB>
__device__ __forceinline__ void wgmma_ss_n128(float (&d)[64], uint32_t da, uint32_t db, int scale_d) {
  asm volatile("{\n.reg .pred p;\n.reg .b64 da, db;\nsetp.ne.b32 p, %66, 0;\nmov.b64 da, {%64, %69};\nmov.b64 db, {%65, %70};\n"
    "wgmma.mma_async.sync.aligned.m64n128k16.f32.bf16.bf16 {%0, %1, %2, %3, %4, %5, %6, %7, %8, %9, %10, %11, %12, %13, %14, %15, %16, %17, %18, %19, %20, %21, %22, %23, %24, %25, %26, %27, %28, %29, %30, %31, %32, %33, %34, %35, %36, %37, %38, %39, %40, %41, %42, %43, %44, %45, %46, %47, %48, %49, %50, %51, %52, %53, %54, %55, %56, %57, %58, %59, %60, %61, %62, %63}, da, db, p, 1, 1, %67, %68;\n}\n"
    : "+f"(d[0]), "+f"(d[1]), "+f"(d[2]), "+f"(d[3]), "+f"(d[4]), "+f"(d[5]), "+f"(d[6]), "+f"(d[7]), "+f"(d[8]), "+f"(d[9]), "+f"(d[10]), "+f"(d[11]), "+f"(d[12]), "+f"(d[13]), "+f"(d[14]), "+f"(d[15]), "+f"(d[16]), "+f"(d[17]), "+f"(d[18]), "+f"(d[19]), "+f"(d[20]), "+f"(d[21]), "+f"(d[22]), "+f"(d[23]), "+f"(d[24]), "+f"(d[25]), "+f"(d[26]), "+f"(d[27]), "+f"(d[28]), "+f"(d[29]), "+f"(d[30]), "+f"(d[31]), "+f"(d[32]), "+f"(d[33]), "+f"(d[34]), "+f"(d[35]), "+f"(d[36]), "+f"(d[37]), "+f"(d[38]), "+f"(d[39]), "+f"(d[40]), "+f"(d[41]), "+f"(d[42]), "+f"(d[43]), "+f"(d[44]), "+f"(d[45]), "+f"(d[46]), "+f"(d[47]), "+f"(d[48]), "+f"(d[49]), "+f"(d[50]), "+f"(d[51]), "+f"(d[52]), "+f"(d[53]), "+f"(d[54]), "+f"(d[55]), "+f"(d[56]), "+f"(d[57]), "+f"(d[58]), "+f"(d[59]), "+f"(d[60]), "+f"(d[61]), "+f"(d[62]), "+f"(d[63])
    : "r"(da), "r"(db), "r"(scale_d), "n"(TA), "n"(TB), "n"(HA), "n"(HB));
}

template <int TA, int TB, uint32_t HA, uint32_t HB>
__device__ __forceinline__ void wgmma_ss_n40(float (&d)[20], uint32_t da, uint32_t db, int scale_d) {
  asm volatile("{\n.reg .pred p;\n.reg .b64 da, db;\nsetp.ne.b32 p, %22, 0;\nmov.b64 da, {%20, %25};\nmov.b64 db, {%21, %26};\n"
    "wgmma.mma_async.sync.aligned.m64n40k16.f32.bf16.bf16 {%0, %1, %2, %3, %4, %5, %6, %7, %8, %9, %10, %11, %12, %13, %14, %15, %16, %17, %18, %19}, da, db, p, 1, 1, %23, %24;\n}\n"
    : "+f"(d[0]), "+f"(d[1]), "+f"(d[2]), "+f"(d[3]), "+f"(d[4]), "+f"(d[5]), "+f"(d[6]), "+f"(d[7]), "+f"(d[8]), "+f"(d[9]), "+f"(d[10]), "+f"(d[11]), "+f"(d[12]), "+f"(d[13]), "+f"(d[14]), "+f"(d[15]), "+f"(d[16]), "+f"(d[17]), "+f"(d[18]), "+f"(d[19])
    : "r"(da), "r"(db), "r"(scale_d), "n"(TA), "n"(TB), "n"(HA), "n"(HB));
}

template <int TB, uint32_t HB>
__device__ __forceinline__ void wgmma_rs_n32(float (&d)[16], uint32_t a0, uint32_t a1, uint32_t a2, uint32_t a3, uint32_t db, int scale_d) {
  asm volatile("{\n.reg .pred p;\n.reg .b64 db;\nsetp.ne.b32 p, %21, 0;\nmov.b64 db, {%20, %23};\n"
    "wgmma.mma_async.sync.aligned.m64n32k16.f32.bf16.bf16 {%0, %1, %2, %3, %4, %5, %6, %7, %8, %9, %10, %11, %12, %13, %14, %15}, {%16, %17, %18, %19}, db, p, 1, 1, %22;\n}\n"
    : "+f"(d[0]), "+f"(d[1]), "+f"(d[2]), "+f"(d[3]), "+f"(d[4]), "+f"(d[5]), "+f"(d[6]), "+f"(d[7]), "+f"(d[8]), "+f"(d[9]), "+f"(d[10]), "+f"(d[11]), "+f"(d[12]), "+f"(d[13]), "+f"(d[14]), "+f"(d[15])
    : "r"(a0), "r"(a1), "r"(a2), "r"(a3), "r"(db), "r"(scale_d), "n"(TB), "n"(HB));
}

template <int TB, uint32_t HB>
__device__ __forceinline__ void wgmma_rs_n40(float (&d)[20], uint32_t a0, uint32_t a1, uint32_t a2, uint32_t a3, uint32_t db, int scale_d) {
  asm volatile("{\n.reg .pred p;\n.reg .b64 db;\nsetp.ne.b32 p, %25, 0;\nmov.b64 db, {%24, %27};\n"
    "wgmma.mma_async.sync.aligned.m64n40k16.f32.bf16.bf16 {%0, %1, %2, %3, %4, %5, %6, %7, %8, %9, %10, %11, %12, %13, %14, %15, %16, %17, %18, %19}, {%20, %21, %22, %23}, db, p, 1, 1, %26;\n}\n"
    : "+f"(d[0]), "+f"(d[1]), "+f"(d[2]), "+f"(d[3]), "+f"(d[4]), "+f"(d[5]), "+f"(d[6]), "+f"(d[7]), "+f"(d[8]), "+f"(d[9]), "+f"(d[10]), "+f"(d[11]), "+f"(d[12]), "+f"(d[13]), "+f"(d[14]), "+f"(d[15]), "+f"(d[16]), "+f"(d[17]), "+f"(d[18]), "+f"(d[19])
    : "r"(a0), "r"(a1), "r"(a2), "r"(a3), "r"(db), "r"(scale_d), "n"(TB), "n"(HB));
}

template <int TB, uint32_t HB>
__device__ __forceinline__ void wgmma_rs_n128(float (&d)[64], uint32_t a0, uint32_t a1, uint32_t a2, uint32_t a3, uint32_t db, int scale_d) {
  asm volatile("{\n.reg .pred p;\n.reg .b64 db;\nsetp.ne.b32 p, %69, 0;\nmov.b64 db, {%68, %71};\n"
    "wgmma.mma_async.sync.aligned.m64n128k16.f32.bf16.bf16 {%0, %1, %2, %3, %4, %5, %6, %7, %8, %9, %10, %11, %12, %13, %14, %15, %16, %17, %18, %19, %20, %21, %22, %23, %24, %25, %26, %27, %28, %29, %30, %31, %32, %33, %34, %35, %36, %37, %38, %39, %40, %41, %42, %43, %44, %45, %46, %47, %48, %49, %50, %51, %52, %53, %54, %55, %56, %57, %58, %59, %60, %61, %62, %63}, {%64, %65, %66, %67}, db, p, 1, 1, %70;\n}\n"
    : "+f"(d[0]), "+f"(d[1]), "+f"(d[2]), "+f"(d[3]), "+f"(d[4]), "+f"(d[5]), "+f"(d[6]), "+f"(d[7]), "+f"(d[8]), "+f"(d[9]), "+f"(d[10]), "+f"(d[11]), "+f"(d[12]), "+f"(d[13]), "+f"(d[14]), "+f"(d[15]), "+f"(d[16]), "+f"(d[17]), "+f"(d[18]), "+f"(d[19]), "+f"(d[20]), "+f"(d[21]), "+f"(d[22]), "+f"(d[23]), "+f"(d[24]), "+f"(d[25]), "+f"(d[26]), "+f"(d[27]), "+f"(d[28]), "+f"(d[29]), "+f"(d[30]), "+f"(d[31]), "+f"(d[32]), "+f"(d[33]), "+f"(d[34]), "+f"(d[35]), "+f"(d[36]), "+f"(d[37]), "+f"(d[38]), "+f"(d[39]), "+f"(d[40]), "+f"(d[41]), "+f"(d[42]), "+f"(d[43]), "+f"(d[44]), "+f"(d[45]), "+f"(d[46]), "+f"(d[47]), "+f"(d[48]), "+f"(d[49]), "+f"(d[50]), "+f"(d[51]), "+f"(d[52]), "+f"(d[53]), "+f"(d[54]), "+f"(d[55]), "+f"(d[56]), "+f"(d[57]), "+f"(d[58]), "+f"(d[59]), "+f"(d[60]), "+f"(d[61]), "+f"(d[62]), "+f"(d[63])
    : "r"(a0), "r"(a1), "r"(a2), "r"(a3), "r"(db), "r"(scale_d), "n"(TB), "n"(HB));
}

constexpr int S_ = 2048, D_ = 1024, F_ = 3584;
constexpr int NCTA = 128;
#define NMOE_ 112
constexpr int NMOE = NMOE_;
#define KV16 1
constexpr int KVH = 5 * 128 * 2;

#define NY 8
struct Zeroed {
  float kv[32 * KVH];
  float y[NY * 2 * D_];
  uint4 hint[512];
  unsigned done[128];
  unsigned pad[1920];
};
constexpr int ZB = KVH + 128 + NY * 64;
static_assert(sizeof(Zeroed) == NCTA * ZB, "zeroed block");
__device__ __align__(128) Zeroed g_z;
__device__ __align__(128) unsigned g_key[2 * NCTA];
__device__ __align__(128) uint2 g_bcast[2 * 8 * 16];
__device__ __align__(128) unsigned g_gate[S_];
__device__ __align__(1024) __nv_bfloat16 g_o[S_ * D_];
#define TSTAMP(i)
#define GSTAMP(i)

constexpr int STAGES = 6, KT = 32;
constexpr int A_BYTES = 256 * 64, B_BYTES = 192 * 64, STAGE_BYTES = A_BYTES + B_BYTES;
constexpr int SM_RA = 0;
constexpr int SM_RB = STAGES * A_BYTES;
constexpr int SM_PHIK = 0;
constexpr int SM_V = 65536;
constexpr int SM_O = SM_V;
constexpr int NA2 = 5, NB2 = 7;
#define XT_IN_A 1
constexpr int SM_XT = (XT_IN_A ? SM_RA : SM_RB) + 2 * 16384;
constexpr int SM_XR = STAGES * STAGE_BYTES;
constexpr int SM_MOE = SM_XR;
constexpr int SM_XSEL = SM_XR + 36864;
constexpr int SM_RED = SM_XSEL + 2048;
constexpr int SM_WPHI = 212992;
constexpr int SM_KVB = SM_WPHI + 4096;
constexpr int SM_ONES = SM_KVB + 12288;
constexpr int SM_BAR = SM_ONES + 1024;
constexpr int SM_INFO = SM_BAR + 1008;
constexpr int SM_GATE = SM_BAR + 1024;
constexpr int SM_UPD = SM_WPHI;
constexpr int SM_KEYS = SM_GATE + 512;
constexpr int SM_TS = SM_KEYS + 32;
constexpr int SM_TOTAL = SM_TS + 256;
static_assert(SM_TOTAL <= 232448 && ZB <= 4608, "smem");
static_assert(SM_WPHI % 1024 == 0 && SM_KVB % 1024 == 0 && SM_ONES % 1024 == 0, "align");
static_assert(SM_MOE + 40960 <= SM_WPHI && SM_RB + NB2 * 16384 <= SM_WPHI, "map");
#define QUAD 1
#define Q_UNROLL 1
#define COLMAP 0x97fdb5316eca4208ull
#define INIT_FENCE 0
#define KV_BAR 0
#define KV_LOOP 0
#define GATE_EXACT 1
#define FFN_LOOP 0
#define QUAD_Q 1
#define HINT_BULK 1
#define PROM_X 2
#define PROM_W 2
#define PROM_F 2
#define BY_SMID 1
#define MAPMODE 1
#define EXPT 0
#define PF_START 0
#define PF_OFF 0
#define KV_DELAY 400
#define O_YIELD 1
#define TAILV -1
#define NFIRST 5
#define Q_AFTER B_PHI + 1
#define LEAD2 6
#define KEY_SLEEP 0
#define B5_AFTER B_F2 + 2
#define REG_C 192
#define REG_K 88
#define STR2(x) #x
#define STR(x) STR2(x)
#define XT_H 0
#define EARLY_MAP 1
#define NPRE 1
#define O_OVL 1
#define LATE_SLEEP 0
#define URG_STEP 0
#define LEAD_AT 1
#define XR_AFTER 3
#define LATE_DELAY 300
#define LATE_STEP 400

constexpr int B_FULL = 0, B_XR = 6, B_WPHI = 10;
constexpr int B_EMPTY = 11, B_XRD = 17;
constexpr int B_INIT = 123;
constexpr int B_ST = 18, B_MOE = 20, B_XSEL = 24, B_H = 25, B_RDY = 26, B_Y = 27, B_XT = 28, B_PEER = 30;
constexpr int B_FB2 = 31, B_F2 = 47;
constexpr int B_DB = 79;
constexpr int B_GO = 95;
constexpr int B_KVB = 111, B_OP = 112, B_MOEE = 116;
constexpr int B_PHI = 120, B_XTD = 122;
constexpr int NBAR = 123;
__host__ __device__ constexpr int bar_count(int i) {
  return i < B_DB ? 1 : i < B_GO ? 2 : i < B_KVB ? (int)(0x3333333333519111ull >> (4 * (i - B_GO))) & 15 : i < B_PHI ? 4 : 8;
}

struct Maps { CUtensorMap x, w, wo, wphi, wg, wu, wd, tg, tu, td, to, xr, xt, out; };

__device__ __forceinline__ uint32_t pack_bf16(float lo, float hi) {
  uint32_t r; asm("cvt.rn.bf16x2.f32 %0, %1, %2;" : "=r"(r) : "f"(hi), "f"(lo)); return r;
}
__device__ __forceinline__ float bf_lo(uint32_t v) { return __uint_as_float(v << 16); }
__device__ __forceinline__ float bf_hi(uint32_t v) { return __uint_as_float(v & 0xffff0000u); }
__device__ __forceinline__ float round_bf16(float v) { return __bfloat162float(__float2bfloat16_rn(v)); }
__device__ __forceinline__ float ex2(float v) { float r; asm("ex2.approx.ftz.f32 %0, %1;" : "=f"(r) : "f"(v)); return r; }
__device__ __forceinline__ float rcp(float v) { float r; asm("rcp.approx.ftz.f32 %0, %1;" : "=f"(r) : "f"(v)); return r; }
__device__ __forceinline__ void stsm4(uint32_t addr, uint32_t r0, uint32_t r1, uint32_t r2, uint32_t r3) {
  asm volatile("stmatrix.sync.aligned.m8n8.x4.shared.b16 [%0], {%1, %2, %3, %4};" :: "r"(addr), "r"(r0), "r"(r1), "r"(r2), "r"(r3) : "memory");
}
__device__ __forceinline__ void stsm2(uint32_t addr, uint32_t r0, uint32_t r1) {
  asm volatile("stmatrix.sync.aligned.m8n8.x2.shared.b16 [%0], {%1, %2};" :: "r"(addr), "r"(r0), "r"(r1) : "memory");
}
__device__ __forceinline__ uint2 lds64(uint32_t addr) {
  uint2 v; asm volatile("ld.shared.v2.u32 {%0, %1}, [%2];" : "=r"(v.x), "=r"(v.y) : "r"(addr) : "memory"); return v;
}
__device__ __forceinline__ void lds128x4(uint32_t addr, uint4& a, uint4& b, uint4& c, uint4& d) {
  asm volatile("ld.shared.v4.u32 {%0, %1, %2, %3}, [%16];\nld.shared.v4.u32 {%4, %5, %6, %7}, [%16 + 128];\n"
               "ld.shared.v4.u32 {%8, %9, %10, %11}, [%16 + 256];\nld.shared.v4.u32 {%12, %13, %14, %15}, [%16 + 384];"
    : "=r"(a.x), "=r"(a.y), "=r"(a.z), "=r"(a.w), "=r"(b.x), "=r"(b.y), "=r"(b.z), "=r"(b.w),
      "=r"(c.x), "=r"(c.y), "=r"(c.z), "=r"(c.w), "=r"(d.x), "=r"(d.y), "=r"(d.z), "=r"(d.w) : "r"(addr) : "memory");
}
__device__ __forceinline__ void ldsm4(uint32_t addr, uint32_t& r0, uint32_t& r1, uint32_t& r2, uint32_t& r3) {
  asm volatile("ldmatrix.sync.aligned.m8n8.x4.shared.b16 {%0, %1, %2, %3}, [%4];" : "=r"(r0), "=r"(r1), "=r"(r2), "=r"(r3) : "r"(addr) : "memory");
}
__device__ __forceinline__ uint4 lds128(uint32_t addr) {
  uint4 v; asm volatile("ld.shared.v4.u32 {%0, %1, %2, %3}, [%4];" : "=r"(v.x), "=r"(v.y), "=r"(v.z), "=r"(v.w) : "r"(addr) : "memory"); return v;
}
__device__ __forceinline__ void sts128(uint32_t addr, uint4 v) {
  asm volatile("st.shared.v4.u32 [%0], {%1, %2, %3, %4};" :: "r"(addr), "r"(v.x), "r"(v.y), "r"(v.z), "r"(v.w) : "memory");
}
__device__ __forceinline__ float lds_f32(uint32_t addr) { float v; asm volatile("ld.shared.f32 %0, [%1];" : "=f"(v) : "r"(addr) : "memory"); return v; }
__device__ __forceinline__ void sts_f32(uint32_t addr, float v) { asm volatile("st.shared.f32 [%0], %1;" :: "r"(addr), "f"(v) : "memory"); }
__device__ __forceinline__ uint32_t lds_u32(uint32_t addr) { uint32_t v; asm volatile("ld.shared.u32 %0, [%1];" : "=r"(v) : "r"(addr) : "memory"); return v; }
__device__ __forceinline__ void sts_u32(uint32_t addr, uint32_t v) { asm volatile("st.shared.u32 [%0], %1;" :: "r"(addr), "r"(v) : "memory"); }
__device__ __forceinline__ unsigned clock32() { unsigned c; asm volatile("mov.u32 %0, %%clock;" : "=r"(c)); return c; }
__device__ __forceinline__ bool elect_one() {
  uint32_t p; asm volatile("{\n.reg .pred q;\nelect.sync _|q, 0xffffffff;\nselp.u32 %0, 1, 0, q;\n}" : "=r"(p)); return p;
}
__device__ __forceinline__ void bar_sync(int id, int n) { asm volatile("bar.sync %0, %1;" :: "r"(id), "r"(n) : "memory"); }
__device__ __forceinline__ void fence_async_smem() { asm volatile("fence.proxy.async.shared::cta;" ::: "memory"); }
__device__ __forceinline__ void fence_async_all() { asm volatile("fence.proxy.async;" ::: "memory"); }
__device__ __forceinline__ void fence_gpu() { asm volatile("fence.acq_rel.gpu;" ::: "memory"); }
__device__ __forceinline__ unsigned ld_acquire(const unsigned* p) { unsigned v; asm volatile("ld.acquire.gpu.global.u32 %0, [%1];" : "=r"(v) : "l"(p) : "memory"); return v; }
__device__ __forceinline__ void red_release(unsigned* p, unsigned v) { asm volatile("red.release.gpu.global.add.u32 [%0], %1;" :: "l"(p), "r"(v) : "memory"); }
__device__ __forceinline__ void st_release(unsigned* p, unsigned v) { asm volatile("st.release.gpu.global.u32 [%0], %1;" :: "l"(p), "r"(v) : "memory"); }
__device__ __forceinline__ unsigned ld_relaxed(const unsigned* p) { unsigned v; asm volatile("ld.relaxed.gpu.global.u32 %0, [%1];" : "=r"(v) : "l"(p) : "memory"); return v; }
__device__ __forceinline__ void red_relaxed(unsigned* p, unsigned v) { asm volatile("red.relaxed.gpu.global.add.u32 [%0], %1;" :: "l"(p), "r"(v) : "memory"); }
__device__ __forceinline__ void st_relaxed(unsigned* p, unsigned v) { asm volatile("st.relaxed.gpu.global.u32 [%0], %1;" :: "l"(p), "r"(v) : "memory"); }
__device__ __forceinline__ void st_relaxed2(uint2* p, unsigned a, unsigned b) { asm volatile("st.relaxed.gpu.global.v2.u32 [%0], {%1, %2};" :: "l"(p), "r"(a), "r"(b) : "memory"); }
template <int SLEEP>
__device__ __forceinline__ unsigned wait_tagged(const uint2* p, unsigned tag) {
  uint2 v;
  int it = 0;
  do {
    if (SLEEP && it > 0) __nanosleep(SLEEP);
    asm volatile("ld.relaxed.gpu.global.v2.u32 {%0, %1}, [%2];" : "=r"(v.x), "=r"(v.y) : "l"(p) : "memory");
    if (++it > (1 << 20)) __trap();
  } while (!__all_sync(0xffffffffu, v.y == tag));
  return v.x;
}
__device__ __forceinline__ void wait_counter(const unsigned* p, unsigned target) {
#pragma unroll 1
  for (int it = 0; it < (1 << 20); it++) { if ((int)(ld_relaxed(p) - target) >= 0) return; }
  __trap();
}
__device__ __forceinline__ float4 ldg_l2(const float* p) {
  float4 v; asm volatile("ld.relaxed.gpu.global.v4.f32 {%0, %1, %2, %3}, [%4];" : "=f"(v.x), "=f"(v.y), "=f"(v.z), "=f"(v.w) : "l"(p) : "memory"); return v;
}
__device__ __forceinline__ float ldg_l2_f(const float* p) { float v; asm volatile("ld.relaxed.gpu.global.f32 %0, [%1];" : "=f"(v) : "l"(p) : "memory"); return v; }
__device__ __forceinline__ void sts64(uint32_t addr, float a, float b) { asm volatile("st.shared.v2.f32 [%0], {%1, %2};" :: "r"(addr), "f"(a), "f"(b) : "memory"); }
__device__ __forceinline__ void bulk_load(uint32_t dst, const void* src, uint32_t bytes, uint32_t bar) {
  asm volatile("cp.async.bulk.shared::cluster.global.mbarrier::complete_tx::bytes [%0], [%1], %2, [%3];" :: "r"(dst), "l"(src), "r"(bytes), "r"(bar) : "memory");
}
__device__ __forceinline__ void bulk_prefetch(const void* src, uint32_t bytes) {
  asm volatile("cp.async.bulk.prefetch.L2.global [%0], %1;" :: "l"(src), "r"(bytes) : "memory");
}
__device__ __forceinline__ void tma_store_2d(const CUtensorMap* tm, uint32_t src, int c0, int c1) {
  asm volatile("cp.async.bulk.tensor.2d.global.shared::cta.bulk_group [%0, {%2, %3}], [%1];" :: "l"(tm), "r"(src), "r"(c0), "r"(c1) : "memory");
}
__device__ __forceinline__ void bulk_store(void* dst, uint32_t src, uint32_t bytes) {
  asm volatile("cp.async.bulk.global.shared::cta.bulk_group [%0], [%1], %2;" :: "l"(dst), "r"(src), "r"(bytes) : "memory");
}
__device__ __forceinline__ void bulk_reduce_f32(void* dst, uint32_t src, uint32_t bytes) {
  asm volatile("cp.reduce.async.bulk.global.shared::cta.bulk_group.add.f32 [%0], [%1], %2;" :: "l"(dst), "r"(src), "r"(bytes) : "memory");
}
__device__ __forceinline__ void tma_load_3d(uint32_t dst, const CUtensorMap* tm, int c0, int c1, int c2, uint32_t bar) {
  asm volatile("cp.async.bulk.tensor.3d.shared::cluster.global.mbarrier::complete_tx::bytes [%0], [%1, {%3, %4, %5}], [%2];"
    :: "r"(dst), "l"(tm), "r"(bar), "r"(c0), "r"(c1), "r"(c2) : "memory");
}
__device__ __forceinline__ void cp_async16(uint32_t dst, const void* src) { asm volatile("cp.async.cg.shared.global [%0], [%1], 16;" :: "r"(dst), "l"(src) : "memory"); }
__device__ __forceinline__ void cp_async_commit() { asm volatile("cp.async.commit_group;" ::: "memory"); }
template <int N> __device__ __forceinline__ void cp_async_wait() { asm volatile("cp.async.wait_group %0;" :: "n"(N) : "memory"); }
__device__ __forceinline__ void prefetch_map(const CUtensorMap* tm) { asm volatile("prefetch.tensormap [%0];" :: "l"(tm) : "memory"); }
__device__ __forceinline__ void bulk_commit() { asm volatile("cp.async.bulk.commit_group;" ::: "memory"); }
__device__ __forceinline__ void bulk_wait0() { asm volatile("cp.async.bulk.wait_group 0;" ::: "memory"); }
__device__ __forceinline__ void bulk_wait0_read() { asm volatile("cp.async.bulk.wait_group.read 0;" ::: "memory"); }
__device__ __forceinline__ void mma16816(float& d0, float& d1, float& d2, float& d3, uint32_t a0, uint32_t a1, uint32_t a2, uint32_t a3, uint32_t b0, uint32_t b1) {
  asm volatile("mma.sync.aligned.m16n8k16.row.col.f32.bf16.bf16.f32 {%0, %1, %2, %3}, {%4, %5, %6, %7}, {%8, %9}, {%0, %1, %2, %3};"
    : "+f"(d0), "+f"(d1), "+f"(d2), "+f"(d3) : "r"(a0), "r"(a1), "r"(a2), "r"(a3), "r"(b0), "r"(b1));
}
__device__ __forceinline__ uint32_t hmul2(uint32_t a, uint32_t b) { uint32_t r; asm("mul.rn.bf16x2 %0, %1, %2;" : "=r"(r) : "r"(a), "r"(b)); return r; }
__device__ __forceinline__ uint32_t hfma2(uint32_t a, uint32_t b, uint32_t c) { uint32_t r; asm("fma.rn.bf16x2 %0, %1, %2, %3;" : "=r"(r) : "r"(a), "r"(b), "r"(c)); return r; }
__device__ __forceinline__ uint32_t hadd2(uint32_t a, uint32_t b) { uint32_t r; asm("add.rn.bf16x2 %0, %1, %2;" : "=r"(r) : "r"(a), "r"(b)); return r; }
__device__ __forceinline__ float sigmoidf_(float v) { return rcp(1.0f + ex2(v * -1.4426950408889634f)); }

__device__ __forceinline__ void hedgehog(const float (&p)[16], uint32_t (&phi)[16]) {
  float mx0 = p[0], mn0 = p[0], mx1 = p[2], mn1 = p[2];
#pragma unroll
  for (int j = 0; j < 4; j++) {
    mx0 = fmaxf(mx0, fmaxf(p[4 * j], p[4 * j + 1])); mn0 = fminf(mn0, fminf(p[4 * j], p[4 * j + 1]));
    mx1 = fmaxf(mx1, fmaxf(p[4 * j + 2], p[4 * j + 3])); mn1 = fminf(mn1, fminf(p[4 * j + 2], p[4 * j + 3]));
  }
#pragma unroll
  for (int o = 1; o <= 2; o <<= 1) {
    mx0 = fmaxf(mx0, __shfl_xor_sync(0xffffffffu, mx0, o)); mn0 = fminf(mn0, __shfl_xor_sync(0xffffffffu, mn0, o));
    mx1 = fmaxf(mx1, __shfl_xor_sync(0xffffffffu, mx1, o)); mn1 = fminf(mn1, __shfl_xor_sync(0xffffffffu, mn1, o));
  }
  float ep[16], en[16];
  float sp0 = 0.f, sn0 = 0.f, sp1 = 0.f, sn1 = 0.f;
#pragma unroll
  for (int j = 0; j < 4; j++) {
#pragma unroll
    for (int c = 0; c < 2; c++) {
      ep[4 * j + c] = ex2(p[4 * j + c] - mx0); en[4 * j + c] = ex2(mn0 - p[4 * j + c]);
      ep[4 * j + 2 + c] = ex2(p[4 * j + 2 + c] - mx1); en[4 * j + 2 + c] = ex2(mn1 - p[4 * j + 2 + c]);
      sp0 += ep[4 * j + c]; sn0 += en[4 * j + c]; sp1 += ep[4 * j + 2 + c]; sn1 += en[4 * j + 2 + c];
    }
  }
#pragma unroll
  for (int o = 1; o <= 2; o <<= 1) {
    sp0 += __shfl_xor_sync(0xffffffffu, sp0, o); sn0 += __shfl_xor_sync(0xffffffffu, sn0, o);
    sp1 += __shfl_xor_sync(0xffffffffu, sp1, o); sn1 += __shfl_xor_sync(0xffffffffu, sn1, o);
  }
  sp0 = rcp(sp0); sn0 = rcp(sn0); sp1 = rcp(sp1); sn1 = rcp(sn1);
#pragma unroll
  for (int j = 0; j < 4; j++) {
    phi[2 * j] = pack_bf16(ep[4 * j] * sp0, ep[4 * j + 1] * sp0);
    phi[2 * j + 1] = pack_bf16(ep[4 * j + 2] * sp1, ep[4 * j + 3] * sp1);
    phi[8 + 2 * j] = pack_bf16(en[4 * j + 1] * sn0, en[4 * j] * sn0);
    phi[8 + 2 * j + 1] = pack_bf16(en[4 * j + 3] * sn1, en[4 * j + 2] * sn1);
  }
}

__device__ __noinline__ void hedgehog_slow(float* buf, int n) {
#pragma unroll 1
  for (int u = 0; u < n; u++) {
    float p[16]; uint32_t phi[16];
#pragma unroll
    for (int i = 0; i < 16; i++) p[i] = buf[u * 16 + i];
    hedgehog(p, phi);
#pragma unroll
    for (int i = 0; i < 16; i++) buf[u * 16 + i] = __uint_as_float(phi[i]);
  }
}

__device__ __forceinline__ void store_phi_k(const uint32_t (&phi)[16], uint32_t a) {
#pragma unroll
  for (int jj = 0; jj < 4; jj++) stsm4(a ^ (jj << 5), phi[4 * jj], phi[4 * jj + 1], phi[4 * jj + 2], phi[4 * jj + 3]);
}
__device__ __forceinline__ void hand_over_smem(uint32_t bar, bool ok) {
  fence_async_smem();
  __syncwarp();
  if (elect_one() & ok) mbar_arrive(bar);
}
__device__ __noinline__ void redo_phi_k(float* buf, unsigned done, uint32_t pa, uint32_t bar) {
  hedgehog_slow(buf, 4);
#pragma unroll 1
  for (int u = 0; u < 4; u++) {
    if ((done >> u) & 1) continue;
    uint32_t phi[16];
#pragma unroll
    for (int i = 0; i < 16; i++) phi[i] = __float_as_uint(buf[u * 16 + i]);
    store_phi_k(phi, pa + (~u & 1) * 32768 + (u >> 1) * 4096);
    if (u >= 2) hand_over_smem(bar + (u - 2) * 8, true);
  }
}

__device__ __forceinline__ uint32_t dup_lo(uint32_t v) { uint32_t r; asm("{\n.reg .b16 l, h;\nmov.b32 {l, h}, %1;\nmov.b32 %0, {l, l};\n}" : "=r"(r) : "r"(v)); return r; }
__device__ __forceinline__ uint32_t dup_hi(uint32_t v) { uint32_t r; asm("{\n.reg .b16 l, h;\nmov.b32 {l, h}, %1;\nmov.b32 %0, {h, h};\n}" : "=r"(r) : "r"(v)); return r; }
struct HState { uint32_t a[16]; float s[5]; };
template <bool QD>
__device__ __forceinline__ void hedgehog_fast1(const float (&p)[16], HState& a) {
  float sm[8], m[8], r[8];
#pragma unroll
  for (int i = 0; i < 8; i++) {
    const float t0 = ex2(p[2 * i]), t1 = ex2(p[2 * i + 1]);
    a.a[i] = pack_bf16(t0, t1); sm[i] = t0 + t1; m[i] = t0 * t1;
  }
  if (QD) {
    float mq[4];
#pragma unroll
    for (int i = 0; i < 4; i++) {
      mq[i] = m[2 * i] * m[2 * i + 1];
      const float R = rcp(mq[i]);
      r[2 * i] = R * m[2 * i + 1]; r[2 * i + 1] = R * m[2 * i];
    }
    a.s[4] = (mq[0] + mq[1]) + (mq[2] + mq[3]);
  } else {
#pragma unroll
    for (int i = 0; i < 8; i++) r[i] = rcp(m[i]);
    a.s[4] = 0.f;
  }
#pragma unroll
  for (int i = 0; i < 4; i++) {
    const uint32_t rr = pack_bf16(r[2 * i], r[2 * i + 1]);
    a.a[8 + 2 * i] = hmul2(a.a[2 * i], dup_lo(rr)); a.a[9 + 2 * i] = hmul2(a.a[2 * i + 1], dup_hi(rr));
  }
#pragma unroll
  for (int c = 0; c < 2; c++) {
    a.s[2 * c] = (sm[c] + sm[2 + c]) + (sm[4 + c] + sm[6 + c]);
    a.s[2 * c + 1] = fmaf(r[6 + c], sm[6 + c], fmaf(r[4 + c], sm[4 + c], fmaf(r[2 + c], sm[2 + c], r[c] * sm[c])));
  }
}
template <bool NORM>
__device__ __forceinline__ bool hedgehog_fast2(const HState& a, uint32_t (&phi)[16], float& s0, float& s1) {
  float s[4] = {a.s[0], a.s[1], a.s[2], a.s[3]};
#pragma unroll
  for (int o = 1; o <= 2; o <<= 1)
#pragma unroll
    for (int i = 0; i < 4; i++) s[i] += __shfl_xor_sync(0xffffffffu, s[i], o);
  const bool ok = ((s[0] + s[1]) + (s[2] + s[3]) <= 7.2e16f) & (a.s[4] <= 1.3e36f);
  if (NORM) {
    const float R0 = rcp(s[0] * s[1]), R1 = rcp(s[2] * s[3]);
    const uint32_t n0 = pack_bf16(R0 * s[1], R0 * s[0]), n1 = pack_bf16(R1 * s[3], R1 * s[2]);
#pragma unroll
    for (int i = 0; i < 8; i++) { phi[i] = hmul2(a.a[i], dup_lo((i & 1) ? n1 : n0)); phi[8 + i] = hmul2(a.a[8 + i], dup_hi((i & 1) ? n1 : n0)); }
  } else {
    const uint32_t n = pack_bf16(s[0] * rcp(s[1]), s[2] * rcp(s[3]));
    s0 = s[0]; s1 = s[2];
#pragma unroll
    for (int i = 0; i < 8; i++) { phi[i] = a.a[i]; phi[8 + i] = hmul2(a.a[8 + i], (i & 1) ? dup_hi(n) : dup_lo(n)); }
  }
  return ok;
}
template <bool NORM>
__device__ __forceinline__ bool hedgehog_fast(const float (&p)[16], uint32_t (&phi)[16], float& s0, float& s1) {
  HState a;
  hedgehog_fast1<NORM ? QUAD : QUAD_Q>(p, a);
  return hedgehog_fast2<NORM>(a, phi, s0, s1);
}

template <int OFF>
__device__ __forceinline__ void pack_frags(const float (&acc)[96], uint32_t (&a)[16]) {
#pragma unroll
  for (int i = 0; i < 16; i++) a[i] = pack_bf16(acc[OFF + 2 * i], acc[OFF + 2 * i + 1]);
#pragma unroll
  for (int i = 0; i < 16; i++) asm volatile("" : "+r"(a[i]) :: "memory");
}
__device__ __forceinline__ void issue_feat(const uint32_t (&a)[16], float (&p0)[16], float (&p1)[16], uint32_t wphi) {
  wgmma_fence();
#pragma unroll
  for (int kk = 0; kk < 2; kk++) {
    wgmma_rs_n32<1, H64>(p0, a[4 * kk], a[4 * kk + 1], a[4 * kk + 2], a[4 * kk + 3], dlo(wphi + kk * 1024, 16), kk);
    wgmma_rs_n32<1, H64>(p1, a[8 + 4 * kk], a[8 + 4 * kk + 1], a[8 + 4 * kk + 2], a[8 + 4 * kk + 3], dlo(wphi + 2048 + kk * 1024, 16), kk);
  }
  wgmma_commit();
}
__device__ __forceinline__ void keep_alive(const uint32_t (&a)[16]) {
#pragma unroll
  for (int i = 0; i < 16; i++) asm volatile("" :: "r"(a[i]) : "memory");
}

__device__ __forceinline__ void fma8(float (&a)[8], float xv, const uint4& w) {
  a[0] = fmaf(xv, bf_lo(w.x), a[0]); a[1] = fmaf(xv, bf_hi(w.x), a[1]);
  a[2] = fmaf(xv, bf_lo(w.y), a[2]); a[3] = fmaf(xv, bf_hi(w.y), a[3]);
  a[4] = fmaf(xv, bf_lo(w.z), a[4]); a[5] = fmaf(xv, bf_hi(w.z), a[5]);
  a[6] = fmaf(xv, bf_lo(w.w), a[6]); a[7] = fmaf(xv, bf_hi(w.w), a[7]);
}

template <int J0, int J1>
__device__ __forceinline__ void stage_out(const float (&acc)[64], uint32_t xa) {
#pragma unroll
  for (int jj = J0; jj < J1; jj++)
    stsm4((xa ^ ((jj & 3) << 5)) + (jj >> 2) * 16384, pack_bf16(acc[8 * jj], acc[8 * jj + 1]), pack_bf16(acc[8 * jj + 2], acc[8 * jj + 3]),
          pack_bf16(acc[8 * jj + 4], acc[8 * jj + 5]), pack_bf16(acc[8 * jj + 6], acc[8 * jj + 7]));
}
__device__ __forceinline__ float lds_bf16(uint32_t addr) {
  unsigned short v; asm volatile("ld.shared.u16 %0, [%1];" : "=h"(v) : "r"(addr) : "memory"); return __uint_as_float((uint32_t)v << 16);
}
__device__ __noinline__ void redo_rows(const __nv_bfloat16* x, const __nv_bfloat16* wo, uint32_t sb, int b, int wq, uint32_t xa) {
  const int lane = threadIdx.x & 31, wi = (threadIdx.x >> 5) & 3, blk = (b >> 3) * 2 + wq, row0 = blk * 64 + wi * 16;
  const __nv_bfloat16 *pieces = g_o + (size_t)blk * 16 * 4096, *wo_cols = wo + (b & 7) * 128, *xrows = x + (size_t)row0 * D_ + (b & 7) * 128;
  const unsigned* done = g_z.done + (b & ~15);
  const uint32_t gate = sb + SM_GATE + (row0 & 255) * 2, upd = sb + SM_UPD;
  const int routed = (int)lds_u32(sb + SM_INFO + 4) - row0;
  int it = 0;
  while (!__all_sync(0xffffffffu, ld_acquire(done + (lane & 15)) != 0)) { if (++it > (1 << 20)) __trap(); }
  float acc[64];
  const int g = lane >> 2, q = lane & 3, r0 = wi * 16 + g;
#pragma unroll
  for (int i = 0; i < 32; i++) {
    const int r = g + (i & 1) * 8, c = (i >> 1) * 8 + q * 2;
    const uint32_t v = *reinterpret_cast<const uint32_t*>(xrows + (size_t)r * D_ + c);
    const float og = round_bf16(1.0f - lds_bf16(gate + r * 2));
    acc[2 * i] = og * bf_lo(v); acc[2 * i + 1] = og * bf_hi(v);
    if (r == routed) {
      const uint32_t u = lds_u32(upd + (c >> 6) * 2048 + (c & 63) * 2);
      acc[2 * i] += bf_lo(u); acc[2 * i + 1] += bf_hi(u);
    }
  }
#pragma unroll 1
  for (int ks = 0; ks < 64; ks++) {
    const unsigned* pc = reinterpret_cast<const unsigned*>(pieces + (ks >> 2) * 4096) + r0 * 32 + q;
    const int c0 = ((2 * (ks & 3)) ^ (r0 & 7)) * 4, c1 = ((2 * (ks & 3) + 1) ^ (r0 & 7)) * 4;
    const uint32_t a0 = ld_relaxed(pc + c0), a1 = ld_relaxed(pc + 256 + c0), a2 = ld_relaxed(pc + c1), a3 = ld_relaxed(pc + 256 + c1);
    const unsigned short* wp = reinterpret_cast<const unsigned short*>(wo_cols) + (size_t)(ks * 16 + 2 * q) * D_ + g;
#pragma unroll
    for (int nb = 0; nb < 16; nb++) {
      const uint32_t b0 = wp[nb * 8] | ((uint32_t)wp[nb * 8 + D_] << 16), b1 = wp[nb * 8 + 8 * D_] | ((uint32_t)wp[nb * 8 + 9 * D_] << 16);
      mma16816(acc[4 * nb], acc[4 * nb + 1], acc[4 * nb + 2], acc[4 * nb + 3], a0, a1, a2, a3, b0, b1);
    }
  }
  __syncwarp();
  stage_out<0, 8>(acc, xa);
}

__global__ void __cluster_dims__(2, 1, 1) __launch_bounds__(512, 1)
fused_kernel(const __grid_constant__ Maps maps, const __nv_bfloat16* __restrict__ x,
             const __nv_bfloat16* __restrict__ wo, const __nv_bfloat16* __restrict__ w_r, const __nv_bfloat16* __restrict__ gate_w, int by_smid) {
  extern __shared__ __align__(1024) uint8_t smem_raw[];
  if (threadIdx.x == 0) { prefetch_map(&maps.w); prefetch_map(&maps.x); }
  const int tid = threadIdx.x, warp = __shfl_sync(0xffffffffu, tid >> 5, 0), lane = tid & 31;
  const int rank = blockIdx.x & 1;
  unsigned smid; asm("mov.u32 %0, %%smid;" : "=r"(smid));
  const unsigned cl = !by_smid ? blockIdx.x >> 1 : smid < 124 ? (smid >> 1) + 4 : (smid >> 1) - 62;
  const unsigned hi = (cl - 36) * 37 >> 8, lo7 = cl - 36 - hi * 7;
  const bool r8 = cl < 36;
  const unsigned c4 = cl - 4, col = cl < 4 ? 15 : r8 ? c4 & 7 : 8 + lo7, pos = cl < 4 ? cl : r8 ? c4 >> 3 : hi;
  const unsigned cm = (unsigned)(COLMAP >> (4 * col)) & 15;
  const int b = MAPMODE == 1 ? ((cm >> 3) * 4 + pos) * 16 + (cm & 7) * 2 + rank
              : MAPMODE == 2 ? ((cm >> 2) * 2 + (pos & 1)) * 16 + (cm & 3) * 4 + (pos >> 1) * 2 + rank : cm * 8 + pos * 2 + rank;
  const unsigned cta = cl * 2 + rank;
  const int e = EXPT == 12 ? 200 : cta;
  const int tg = b >> 4, hp = b & 15;
  const int half = hp >> 3, ct = hp & 7;
  constexpr uint32_t SB0 = 1024;
  const uint32_t sb = SB0 + ((uint32_t)rank << 24);
  auto BAR = [&](int i) { return sb + SM_BAR + 8 * i; };
  auto load_stage = [&](int kt, int s, bool mc) {
    const uint32_t a = sb + SM_RA + s * A_BYTES, full = BAR(B_FULL + s);
    mbar_expect_tx(full, STAGE_BYTES);
    tma_load_3d(sb + SM_RB + s * B_BYTES, &maps.w, hp * 64, kt * 32, 0, full);
    if (mc) tma_load_2d_mc(a + rank * 8192, &maps.x, kt * 32, tg * 256 + rank * 128, full);
    else { tma_load_2d(a, &maps.x, kt * 32, tg * 256, full); tma_load_2d(a + 8192, &maps.x, kt * 32, tg * 256 + 128, full); }
  };
  auto slice_of = [&](int i) { const int t = i - 2 * ((unsigned)(i - 2) < (unsigned)(ct & 6)); return ((i >> 1) ? t : t ^ ct) ^ (half * 8); };
  auto load_b2 = [&](int i) {
    const int j = slice_of(i), sl = i + 4 - (i >= 3) * NB2 - (i >= 10) * NB2;
    mbar_expect_tx(BAR(B_FB2 + i), 16384);
    tma_load_3d(sb + SM_RB + sl * 16384, &maps.wo, 0, j * 64, ct * 2, BAR(B_FB2 + i));
  };
  auto load_xt = [&](int w) {
    mbar_expect_tx(BAR(B_XT + w), 16384);
    tma_load_2d(sb + SM_XT + w * 8192, &maps.xt, ct * 128, tg * 256 + half * 128 + w * 64, BAR(B_XT + w));
    tma_load_2d(sb + SM_XT + w * 8192 + 16384, &maps.xt, ct * 128 + 64, tg * 256 + half * 128 + w * 64, BAR(B_XT + w));
  };
  auto o_piece = [&](int hf, int mb, int j) { return g_o + (size_t)((((tg * 2 + hf) * 2 + mb) * 16 + j) * 4096); };

  if (cta >= NCTA) {
    if (warp == 0 && cta == NCTA) {
      if (smem_u32(smem_raw) != sb) __trap();
      const unsigned tag = (ld_relaxed(&g_bcast[0].y) + 1) & 0xfffu;
#pragma unroll 1
      for (int round = 0; round < 2; round++) {
        bool all;
        int it = 0;
        do {
          uint4 k;
          asm volatile("ld.relaxed.gpu.global.v4.u32 {%0, %1, %2, %3}, [%4];" : "=r"(k.x), "=r"(k.y), "=r"(k.z), "=r"(k.w) : "l"(g_key + round * NCTA + lane * 4) : "memory");
          all = __all_sync(0xffffffffu, (((k.x ^ tag) | (k.y ^ tag) | (k.z ^ tag) | (k.w ^ tag)) & 0xfffu) == 0);
          auto full = [&](unsigned m, int c) { return (m & 0xffff0000u) | ((127u - (lane * 4 + c)) << 4) | ((m >> 12) & 15u); };
          const unsigned val = __reduce_max_sync(0xffffffffu, max(max(full(k.x, 0), full(k.y, 1)), max(full(k.z, 2), full(k.w, 3))));
          asm volatile("{\n.reg .pred p;\nsetp.ne.u32 p, %3, 0;\n@p st.relaxed.gpu.global.v2.u32 [%0], {%1, %2};\n}"
                       :: "l"(g_bcast + round * 128 + (lane & 7) * 16), "r"(val), "r"(tag), "r"((uint32_t)(all && lane < 8)) : "memory");
          if (++it > (1 << 20)) __trap();
        } while (!all);
      }
    }
    return;
  }
  auto load_xr = [&](int xc) {
    mbar_expect_tx(BAR(B_XR + xc), xc ? 8192 : 12288);
    tma_load_2d(sb + SM_XR + xc * 8192, &maps.xr, xc * 256, b * 16, BAR(B_XR + xc));
    tma_load_2d(sb + SM_XR + xc * 8192 + 4096, &maps.xr, xc * 256 + 128, b * 16, BAR(B_XR + xc));
    if (xc == 0) { bulk_load(sb + SM_XR + 32768, w_r, 2048, BAR(B_XR)); bulk_load(sb + SM_XR + 34816, gate_w, 2048, BAR(B_XR)); }
  };
  if (warp == 8) {
    if (elect_one()) {
      mbar_init(BAR(0), 1);
      if (NPRE > 1) { mbar_init(BAR(1), 1); mbar_init(BAR(2), 1); }
      if (NPRE > 0 && INIT_FENCE) fence_async_smem();
      TSTAMP(40);
      if (NPRE > 0) load_stage(0, 0, false);
      if (NPRE > 1) load_stage(1, 1, false);
      if (NPRE > 2) load_stage(2, 2, false);
      TSTAMP(41);
    }
  } else if (elect_one()) {
    const int i = 3 + warp - (warp > 8);
    mbar_init(BAR(i), i < B_EMPTY ? 1 : 4);
    if (NPRE < 2 && warp >= 14) mbar_init(BAR(warp - 13), 1);
    if (warp == 13) mbar_init(BAR(B_INIT), 3);
  }
  asm volatile("fence.mbarrier_init.release.cluster;" ::: "memory");
  __syncwarp();
  asm volatile("barrier.cluster.arrive.relaxed.aligned;" ::: "memory");
  auto cluster_wait = [&]() { asm volatile("barrier.cluster.wait.aligned;" ::: "memory"); };

  if (warp >= 12) {
    asm volatile("setmaxnreg.dec.sync.aligned.u32 40;");
    const int aw = warp - 12;
    cluster_wait();
    const unsigned old_gate = ld_relaxed(g_gate + b * 16 + aw * 4);
    const uint32_t zero = smem_u32(smem_raw) ^ sb;
    {
      float r[4], l[4];
#pragma unroll
      for (int t = 0; t < 4; t++) { r[t] = 0.f; l[t] = 0.f; }
      uint32_t xa = sb + SM_XR + aw * 1024 + lane * 8, wa = sb + SM_XR + 32768 + lane * 8;
#pragma unroll 1
      for (int i = 0; i < 8; i++) {
        if (!(i & 1)) mbar_wait(BAR(B_XR) + i * 4, 0);
        if (tid == 384 && i == 6) TSTAMP(30);
        uint2 wr = lds64(wa);
        const uint2 gw = lds64(wa + 2048);
        uint2 xv[4];
#pragma unroll
        for (int t = 0; t < 4; t++) xv[t] = lds64(xa + t * 256);
        xa += 4096; wa += 256;
        wr.x |= (xv[1].x | xv[2].x | xv[3].x) & zero;
        const float w0 = bf_lo(wr.x), w1 = bf_hi(wr.x), w2 = bf_lo(wr.y), w3 = bf_hi(wr.y);
#pragma unroll
        for (int t = 0; t < 4; t++) {
          const uint32_t p0 = hmul2(xv[t].x, gw.x), p1 = hmul2(xv[t].y, gw.y);
          r[t] = fmaf(bf_hi(xv[t].y), w3, fmaf(bf_lo(xv[t].y), w2, fmaf(bf_hi(xv[t].x), w1, fmaf(bf_lo(xv[t].x), w0, r[t]))));
          if (GATE_EXACT) l[t] += (bf_lo(p0) + bf_hi(p0)) + (bf_lo(p1) + bf_hi(p1));
          else l[t] = fmaf(bf_hi(xv[t].y), bf_hi(gw.y), fmaf(bf_lo(xv[t].y), bf_lo(gw.y), fmaf(bf_hi(xv[t].x), bf_hi(gw.x), fmaf(bf_lo(xv[t].x), bf_lo(gw.x), l[t]))));
        }
      }
      float u[4];
#pragma unroll
      for (int t = 0; t < 4; t++) u[t] = ((lane & 4) ? l[t] : r[t]) + __shfl_xor_sync(0xffffffffu, (lane & 4) ? r[t] : l[t], 4);
      const float v0 = ((lane & 1) ? u[1] : u[0]) + __shfl_xor_sync(0xffffffffu, (lane & 1) ? u[0] : u[1], 1);
      const float v1 = ((lane & 1) ? u[3] : u[2]) + __shfl_xor_sync(0xffffffffu, (lane & 1) ? u[2] : u[3], 1);
      float v = ((lane & 2) ? v1 : v0) + __shfl_xor_sync(0xffffffffu, (lane & 2) ? v0 : v1, 2);
      v += __shfl_xor_sync(0xffffffffu, v, 8);
      v += __shfl_xor_sync(0xffffffffu, v, 16);
      v = round_bf16(v);
      unsigned k = __float_as_uint(v) >> 16;
      k = (k & 0x8000u) ? (~k & 0xffffu) : (k | 0x8000u);
      k = __reduce_max_sync(0xffffffffu, lane < 4 ? (k << 4) | (15u - (aw * 4 + lane)) : 0u);
      if (lane == 0) sts_u32(sb + SM_KEYS + aw * 4, k);
      if ((lane >> 2) == 1) st_relaxed(g_gate + b * 16 + aw * 4 + (lane & 3), __float_as_uint(round_bf16(sigmoidf_(v))) | ((old_gate + 1) & 0xfffu));
      mbar_wait(BAR(B_INIT), 0);
    }
    if (tid == 384) { TSTAMP(31); GSTAMP(60); }
    fence_async_smem();
    __syncwarp();
    if (elect_one()) mbar_arrive(BAR(B_XRD));
    mbar_wait_bounded(BAR(B_XSEL), 0);
    if (tid == 384) TSTAMP(36);
    float ag[8];
#pragma unroll
    for (int i = 0; i < 8; i++) ag[i] = 0.f;
    if (e < NMOE) {
      const uint32_t lw = sb + SM_MOE + aw * 2048 + (lane >> 3) * 512 + (lane & 7) * 16;
      uint32_t lx = sb + SM_XSEL + aw * 32 + (lane >> 3) * 8, fb = BAR(B_MOE), wa = lw;
      bool got = false;
#pragma unroll 1
      for (int m = 0; m < 12; m++) {
#pragma unroll
        for (int c = 0; c < 2; c++) {
          if (!got) mbar_wait(fb + c * 8, (m >> 1) & 1);
          uint4 w0, w1, w2, w3;
          lds128x4(wa + c * 8192, w0, w1, w2, w3);
          uint2 xv = lds64(lx + c * 128);
          got = mbar_test(c ? fb ^ 16 : fb + 8, ((m + c) >> 1) & 1);
          const uint32_t dep = ((w0.x | w1.x | w2.x) | w3.x) & zero;
          xv.x |= dep;
          if (elect_one()) mbar_arrive(fb + dep + (B_MOEE - B_MOE + c) * 8);
          fma8(ag, bf_lo(xv.x), w0); fma8(ag, bf_hi(xv.x), w1); fma8(ag, bf_lo(xv.y), w2); fma8(ag, bf_hi(xv.y), w3);
        }
        fb ^= 16; wa = 2 * lw + 16384 - wa; lx += 256;
        if (m == (FFN_LOOP ? 15 : 7)) {
          int ln;
          asm volatile("mov.u32 %0, %%laneid;" : "=r"(ln));
#pragma unroll
          for (int i = 0; i < 4; i++) ag[i] = ((ln & 16) ? ag[4 + i] : ag[i]) + __shfl_xor_sync(0xffffffffu, (ln & 16) ? ag[i] : ag[4 + i], 16);
          const float v0 = ((ln & 8) ? ag[2] : ag[0]) + __shfl_xor_sync(0xffffffffu, (ln & 8) ? ag[0] : ag[2], 8);
          const float v1 = ((ln & 8) ? ag[3] : ag[1]) + __shfl_xor_sync(0xffffffffu, (ln & 8) ? ag[1] : ag[3], 8);
          const uint32_t own = (uint32_t)(ln & 4) << 22;
          asm volatile("st.async.shared::cluster.mbarrier::complete_tx::bytes.v2.f32 [%0], {%1, %2}, [%3];"
                       :: "r"(own + SB0 + SM_RED + rank * 512 + aw * 128 + (ln & 3) * 32 + (ln >> 3) * 8), "f"(v0), "f"(v1), "r"(own + SB0 + SM_BAR + 8 * B_H) : "memory");
          mbar_wait_bounded(BAR(B_H), 0);
          const uint32_t ra = sb + SM_RED + ln * 4;
          float gv = round_bf16((lds_f32(ra) + lds_f32(ra + 128)) + (lds_f32(ra + 256) + lds_f32(ra + 384)));
          const float uv = round_bf16((lds_f32(ra + 512) + lds_f32(ra + 640)) + (lds_f32(ra + 768) + lds_f32(ra + 896)));
          gv = round_bf16(gv * sigmoidf_(gv));
          lx = sb + SM_XSEL + aw * 32;
          asm volatile("st.shared.b16 [%0], %1;" :: "r"(lx + (ln >> 2) * 128 + (ln & 3) * 2), "h"(__bfloat16_as_ushort(__float2bfloat16_rn(gv * uv))) : "memory");
          __syncwarp();
#pragma unroll
          for (int i = 0; i < 8; i++) ag[i] = 0.f;
          if (tid == 384) TSTAMP(33);
        }
      }
      mbar_wait(BAR(B_RDY), 0);
#pragma unroll
      for (int j = 0; j < 3; j++)
        asm volatile("red.global.add.v4.f32 [%0], {%1, %2, %3, %4};" :: "l"(g_z.y + (e & (NY - 1)) * 2 * D_ + (j * 128 + aw * 32 + lane) * 4),
                     "f"(ag[3 * j]), "f"(ag[3 * j + 1]), "f"(j < 2 ? ag[3 * j + 2] : 0.f), "f"(1.0f) : "memory");
    }
    fence_async_smem();
    if (tid == 384) TSTAMP(34);
    bar_sync(4, 128);
    if (aw == 3) {
      const uint4 info = lds128(sb + SM_INFO);
      int it = 0;
      if ((info.y >> 7) == tg * 2 + half && EXPT != 12) {
        mbar_wait(BAR(B_RDY), 0);
        const float rs = round_bf16(sigmoidf_(__uint_as_float(info.z)));
        float y[9];
        do {
          __nanosleep(100);
#pragma unroll
          for (int i = 0; i < 9; i++) y[i] = 0.f;
#pragma unroll 1
          for (int c = lane >> 4; c < NY; c += 2) {
            const float* yp = g_z.y + c * 2 * D_ + (ct * 16 + (lane & 15)) * 4;
            const float4 a0 = ldg_l2(yp), a1 = ldg_l2(yp + 512), a2 = ldg_l2(yp + 1024);
            y[0] += a0.x; y[1] += a0.y; y[2] += a0.z; y[3] += a1.x; y[4] += a1.y; y[5] += a1.z; y[6] += a2.x; y[7] += a2.y;
            y[8] += a0.w + a1.w + a2.w;
          }
#pragma unroll
          for (int i = 0; i < 9; i++) y[i] += __shfl_xor_sync(0xffffffffu, y[i], 16);
          if (++it > (1 << 20)) __trap();
        } while (!__all_sync(0xffffffffu, y[8] == 3.f * NMOE));
        const int hw = lane >> 4;
        const uint2 xv = __ldg(reinterpret_cast<const uint2*>(x + (size_t)info.y * D_ + ct * 128) + (lane & 15) * 2 + hw);
        const float og = round_bf16(1.0f - lds_bf16(sb + SM_GATE + (info.y & 255) * 2));
        const uint32_t rs2 = pack_bf16(rs, rs);
        const uint32_t t0 = hadd2(xv.x, hmul2(pack_bf16(hw ? y[4] : y[0], hw ? y[5] : y[1]), rs2));
        const uint32_t t1 = hadd2(xv.y, hmul2(pack_bf16(hw ? y[6] : y[2], hw ? y[7] : y[3]), rs2));
        mbar_wait(BAR(B_OP), 0); mbar_wait(BAR(B_OP + 2), 0);
        sts64(sb + SM_UPD + (lane & 8) * 256 + (lane & 7) * 16 + hw * 8,
              __uint_as_float(pack_bf16(og * (bf_lo(t0) - bf_lo(xv.x)), og * (bf_hi(t0) - bf_hi(xv.x)))),
              __uint_as_float(pack_bf16(og * (bf_lo(t1) - bf_lo(xv.y)), og * (bf_hi(t1) - bf_hi(xv.y)))));
        fence_async_smem();
        __syncwarp();
        if (elect_one()) { mbar_arrive(BAR(B_Y)); TSTAMP(39); }
      }
    } else {
      if (aw == 0) mbar_wait(BAR(B_PHI), 0);
      if (elect_one()) load_b2(aw);
      if (aw) {
#pragma unroll 1
        for (int i = 0; i < 16; i++) {
          mbar_wait_bounded(BAR(B_FB2 + i), 0);
          if (i == 0) mbar_wait(BAR(B_OP + half * 2 + aw - 1), 0);
          if (elect_one()) mbar_expect_tx(BAR(B_F2 + (aw - 1) * 16 + i), i ? 8192 : 0);
        }
      }
    }
  } else if (warp >= 8) {
    asm volatile("setmaxnreg.dec.sync.aligned.u32 24;");
    cluster_wait();
    if (tid == 256) TSTAMP(58);
    if (warp != 8) {
      if (elect_one()) {
#pragma unroll 1
        for (int i = B_ST + warp - 9; i < NBAR; i += 3) mbar_init(BAR(i), bar_count(i) + (LEAD2 && i == B_F2 + 32 - LEAD2));
        asm volatile("fence.mbarrier_init.release.cluster;" ::: "memory");
      }
#pragma unroll
      for (int i = 0; i < (ZB + 1535) / 1536; i++) sts128(sb + SM_KVB + (i * 96 + tid - 288) * 16, make_uint4(0, 0, 0, 0));
      if (warp < 11) sts128(sb + SM_ONES + (tid - 288) * 16, make_uint4(0x3f803f80u, 0x3f803f80u, 0x3f803f80u, 0x3f803f80u));
      if (tid == 352) asm volatile("st.shared::cluster.u32 [%0], %1;" :: "r"((sb ^ (1u << 24)) + SM_KEYS + 16), "r"(cl) : "memory");
      hand_over_smem(BAR(B_INIT), true);
      if (tid == 288) TSTAMP(57);
    }
    if (warp == 8) {
      int s = NPRE, ph = 1;
#pragma unroll 1
      for (int kt = NPRE; kt < KT; kt++) {
        mbar_wait_bounded(BAR(B_EMPTY + s), ph);
        if (elect_one()) {
          load_stage(kt, s, true);
          const unsigned xc = kt - XR_AFTER;
          if (xc < 4) load_xr(xc);
          const int pg = kt - STAGES - PF_START + PF_OFF;
          if (pg >= (e < NMOE ? PF_OFF : 24) && pg < 26 && (EXPT != 3 || pg >= 24)) {
            const CUtensorMap* tm = &maps.tg + (pg < 16 ? (b & 1) : pg < 24 ? 2 : 3);
            const int c0 = pg < 16 ? (e >> 1) * 64 : 0, c1 = (pg < 16 ? pg : pg < 24 ? e * 8 + pg - 16 : b * 2 + pg - 24) * 64;
            asm volatile("cp.async.bulk.prefetch.tensor.2d.L2.global [%0, {%1, %2}];" :: "l"(tm), "r"(c0), "r"(c1) : "memory");
          }
        }
        if (++s == STAGES) { s = 0; ph ^= 1; }
      }
      mbar_wait(BAR(B_EMPTY + 1), 1);
#pragma unroll 1
      for (int i = 3; i < (XT_IN_A ? NB2 : 5); i++)
        if (elect_one()) { if (!XT_IN_A) load_xt(i - 3); load_b2(i); }
    } else if (warp == 9) {
      const unsigned tag = (ld_relaxed(g_key + b) + 1) & 0xfffu;
      if (elect_one()) {
        mbar_expect_tx(BAR(B_WPHI), 4096);
        tma_load_2d(sb + SM_WPHI, &maps.wphi, 0, hp * 64, BAR(B_WPHI));
      }
      mbar_wait(BAR(B_WPHI), 0);
#pragma unroll 1
      for (uint32_t ad = sb + SM_WPHI + lane * 16; ad < sb + SM_WPHI + 4096; ad += 512) {
        constexpr float L = 1.4426950408889634f;
        const uint4 w = lds128(ad);
        sts128(ad, make_uint4(pack_bf16(bf_lo(w.x) * L, bf_hi(w.x) * L), pack_bf16(bf_lo(w.y) * L, bf_hi(w.y) * L),
                              pack_bf16(bf_lo(w.z) * L, bf_hi(w.z) * L), pack_bf16(bf_lo(w.w) * L, bf_hi(w.w) * L)));
      }
      fence_async_smem();
      mbar_wait(BAR(B_XRD), 0);
      {
        const uint4 k = lds128(sb + SM_KEYS);
        if (lane == 0) st_relaxed(g_key + b, (max(max(k.x, k.y), max(k.z, k.w)) << 12) | tag);
      }
      const unsigned best = __shfl_sync(0xffffffffu, wait_tagged<KEY_SLEEP>(g_bcast + tg * 16, tag), 0);
      const unsigned idx = 2047u - (best & 0x7ffu);
      unsigned u = best >> 16;
      u = (u & 0x8000u) ? (u & 0x7fffu) : (~u & 0xffffu);
      if (elect_one()) {
        sts128(sb + SM_INFO, make_uint4(tag, idx, u << 16, 0));
        mbar_expect_tx(BAR(B_H), 1024);
        mbar_expect_tx(BAR(B_XSEL), 2048);
        bulk_load(sb + SM_XSEL, x + (size_t)idx * D_, 2048, BAR(B_XSEL));
        TSTAMP(32); GSTAMP(61);
        bulk_store(reinterpret_cast<char*>(&g_z) + b * ZB, sb + SM_KVB, ZB);
      }
      bulk_commit(); bulk_wait0();
      fence_gpu();
      __syncwarp();
      if (lane == 0) { st_relaxed(g_key + NCTA + b, tag); TSTAMP(42); }
      int it = 0;
#pragma unroll 1
      for (int c = 0; c < 2; c++) {
        uint4 gv;
        do {
          asm volatile("ld.relaxed.gpu.global.v4.u32 {%0, %1, %2, %3}, [%4];" : "=r"(gv.x), "=r"(gv.y), "=r"(gv.z), "=r"(gv.w)
                       : "l"(g_gate + tg * 256 + c * 128 + lane * 4) : "memory");
          if (++it > (1 << 20)) __trap();
        } while (!__all_sync(0xffffffffu, (((gv.x ^ tag) | (gv.y ^ tag) | (gv.z ^ tag) | (gv.w ^ tag)) & 0xfffu) == 0));
        sts64(sb + SM_GATE + c * 256 + lane * 8, __uint_as_float(__byte_perm(gv.x, gv.y, 0x7632)), __uint_as_float(__byte_perm(gv.z, gv.w, 0x7632)));
      }
      wait_tagged<200>(g_bcast + 128 + tg * 16, tag);
      if (lds_u32(sb + SM_KEYS + 16) != cl) __trap();
      __syncwarp();
      if (elect_one()) { mbar_arrive(BAR(B_RDY)); TSTAMP(43); }
    } else if (e < NMOE) {
      const int w = warp & 1;
      const CUtensorMap* tm = &maps.wg + rank;
      int c0 = (e >> 1) * 64, c1 = 0, c2 = 4 * w;
      uint32_t bar = BAR(B_MOE + w);
      mbar_wait(BAR(B_XRD), 0);
#pragma unroll 1
      for (int m = 0; m < 12; m++) {
        mbar_wait(bar + (B_MOEE - B_MOE) * 8, ((m >> 1) & 1) ^ 1);
        if (elect_one()) {
          mbar_expect_tx(bar, 8192);
          tma_load_3d(sb + SM_MOE + w * 8192 + (m & 1) * 16384, tm, c0, c1, c2, bar);
        }
        bar ^= 16;
        if (m < 7) c2 += 8; else c1 += 8;
        if (m == 7) { tm = &maps.wd; c0 = 0; c1 = e * 32 + w * 4; c2 = 0; }
      }
    }
    const int wi = warp - 8, st = tid - 256;
    bar_sync(5, 128);
    asm volatile("setmaxnreg.inc.sync.aligned.u32 " STR(REG_K) ";");
    {
      auto kv_half = [&](float (&d)[20], int h, int mb) {
#pragma unroll
        for (int i = 0; i < 8; i++)
          wgmma_ss_n40<1, 1, H128, H64>(d, dlo(SB0 + SM_PHIK + 32768, 16) - h * 2048 + (((i & 2) << 2) + (i & 4) + mb * 2 + (i & 1)) * 128,
                                        dlo(SB0 + SM_V, SM_ONES - SM_V) + (h * 16 + (i & 4) * 2 + mb * 4 + (i & 3)) * (64 - (64 << 16)), (mb | i) != 0);
      };
      auto kv_out = [&](float (&d)[20], int h) {
        fence_regs(d);
        float* dst = g_z.kv + (hp * 2 + h) * KVH + st * 2;
        const int q = lane & 3;
        uint32_t w[8];
#pragma unroll
        for (int i = 0; i < 8; i++) w[i] = pack_bf16(d[2 * i], d[2 * i + 1]);
#pragma unroll
        for (int c = 0; c < 4; c++)
          asm volatile("red.global.add.noftz.v2.bf16x2 [%0], {%1, %2};" :: "l"(dst + c * 256), "r"(w[2 * c]), "r"(q == c ? 0x3f80u : w[2 * c + 1]) : "memory");
        asm volatile("red.global.add.noftz.v2.bf16x2 [%0], {%1, %2};" :: "l"(dst + 1024), "r"((q & 2) ? ((q & 1) ? w[7] : w[5]) : ((q & 1) ? w[3] : w[1])),
                     "r"(q == 0 ? 0x3f80u : q == 1 ? pack_bf16(d[16], d[18]) : 0u) : "memory");
      };
#pragma unroll 1
      for (int h = 0; h < 2; h++) {
        float kv[20];
        mbar_wait_bounded(BAR(B_PHI + h), 0);
        if (st == 0) TSTAMP(23 + h);
        wgmma_fence();
        kv_half(kv, h, 0); kv_half(kv, h, 1);
        wgmma_commit();
        if (KV_BAR && h && wi < 2 && elect_one()) load_xt(wi);
        wgmma_wait<0>();
        if (st == 0) TSTAMP(21 + h);
        kv_out(kv, h);
        if (!KV_BAR) {
          bar_sync(5, 128);
          if (XT_IN_A && h == XT_H && wi < 2 && elect_one()) load_xt(wi);
        }
      }
      if (wi == 3 && elect_one()) mbar_arrive_cluster(BAR(B_PEER) ^ (1u << 24));
      if (st == 0) TSTAMP(13);
      const int f = wi * 16 + (lane & 15), sw = (f >> 1) & 3, chi = lane >> 4;
      uint2 v[10];
      const float* src = g_z.kv + hp * 2 * KVH + st * 2;
      const int q = lane & 3;
      { const unsigned c0 = clock32(); while (clock32() - c0 < KV_DELAY) {} }
      int it = 0;
      unsigned need = 0x3ff;
#pragma unroll
      for (int i = 0; i < 10; i++) v[i] = make_uint2(0, 0);
      do {
        if (++it > (1 << 20)) __trap();
        unsigned bad = 0;
        if (st == 0 && it == 1) TSTAMP(35);
#pragma unroll
        for (int i = 0; i < 10; i++)
          asm volatile("{\n.reg .pred p;\nsetp.ne.u32 p, %3, 0;\n@p ld.relaxed.gpu.global.v2.u32 {%0, %1}, [%2];\n}"
                       : "+r"(v[i].x), "+r"(v[i].y) : "l"(src + i * 256), "r"(need & (1u << i)) : "memory");
#pragma unroll
        for (int i = 0; i < 10; i++) bad |= (v[i].y != 0x4100u) << i;
        need = __reduce_or_sync(0xffffffffu, bad & ((0x21u << q) | (q ? 0u : 0x210u)));
        if (st == 0 && it == 1) TSTAMP(20);
      } while (need);
      uint32_t zz[2];
#pragma unroll
      for (int h = 0; h < 2; h++) {
        const uint2* w = v + h * 5;
        const uint32_t kb = sb + SM_KVB + h * 4096 + f * 64;
        zz[h] = __shfl_sync(0xffffffffu, w[4].y, (lane & 28) + 1);
        stsm4(kb + ((chi ^ sw) << 4), w[0].x, q == 0 ? w[4].x : w[0].y, w[1].x, q == 1 ? w[4].x : w[1].y);
        stsm4(kb + (((2 + chi) ^ sw) << 4), w[2].x, q == 2 ? w[4].x : w[2].y, w[3].x, q == 3 ? w[4].x : w[3].y);
      }
      stsm4(sb + SM_KVB + 8192 + f * 64 + ((chi ^ sw) << 4), zz[0], zz[0] >> 16, zz[1], zz[1] >> 16);
      fence_async_smem();
      __syncwarp();
      if (elect_one()) mbar_arrive(BAR(B_KVB));
    }
    {
      const int pm = wi >> 1;
      if (wi & 1) {
        const int hf = half ^ pm;
        mbar_wait(BAR(B_PEER), 0);
        mbar_wait_bounded(BAR(B_OP + hf * 2), 0);
        const unsigned c0 = clock32();
        while (clock32() - c0 < (unsigned)(pm ? LATE_DELAY + ct * LATE_STEP : (ct >> 2) * URG_STEP)) {}
        __syncwarp();
        auto to_partner = [&](int mb) {
          asm volatile("cp.async.bulk.shared::cluster.shared::cta.mbarrier::complete_tx::bytes [%0], [%1], 8192, [%2];"
                       :: "r"((sb ^ (1u << 24)) + SM_RA + mb * 8192), "r"(sb + SM_O + mb * 8192), "r"(BAR(B_F2 + mb * 16 + 1) ^ (1u << 24)) : "memory");
        };
        uint4* hint = g_z.hint + (tg * 2 + hf) * 32 + hp;
#pragma unroll 1
        for (int mb = 0; mb < 2; mb++) {
          if (mb) mbar_wait(BAR(B_OP + hf * 2 + 1), 0);
          if (elect_one()) {
            bulk_store(o_piece(hf, mb, hp), sb + SM_O + pm * 16384 + mb * 8192, 8192);
            if (HINT_BULK >= 1 + pm) bulk_store(hint + mb * 16, sb + SM_ONES, 16);
            if (!pm) to_partner(mb);
          }
          bulk_commit();
          if (pm) {
            bulk_wait0();
            __syncwarp();
            if (HINT_BULK < 2 && lane == 0) st_relaxed(&hint[mb * 16].x, 1);
          }
          if (lane == 0) TSTAMP((pm ? 37 : 15) + mb);
        }
        bulk_wait0();
        __syncwarp();
        if (lane == 0) mbar_arrive(BAR(B_ST + pm));
        if (pm == 0) {
          if (lane < 2) mbar_arrive_cluster((lane << 24) + SB0 + SM_BAR + 8 * (B_GO + NA2));
          mbar_wait(BAR(B5_AFTER), 0);
#pragma unroll 1
          for (int i = XT_IN_A ? NB2 : 5; i < 16; i++) {
            mbar_wait(i < NB2 ? BAR(B_XTD) : BAR(B_DB + i - NB2), 0);
            if (elect_one()) load_b2(i);
          }
        } else {
          mbar_wait(BAR(B_ST), 0);
          fence_gpu();
          if (lane == 0) st_relaxed(g_z.done + b, 1);
        }
      } else if (pm) {
        const __nv_bfloat16* src = o_piece(half, rank, half * 8);
        uint32_t dst = sb + SM_RA + 16384 + rank * 8192;
        mbar_wait(BAR(B_PEER), 0);
#pragma unroll 1
        for (int i = 2; i < 16; i++) {
          if (i == (ct & 6) + 2) src += 2 * 4096;
          if (i == 8) src -= half * 16 * 4096;
          mbar_wait_bounded(BAR(B_GO + i), 0);
          if (elect_one()) {
            asm volatile("cp.async.bulk.shared::cluster.global.mbarrier::complete_tx::bytes.multicast::cluster [%0], [%1], 8192, [%2], %3;"
                         :: "r"(dst), "l"(src), "r"(BAR(B_F2 + rank * 16 + i)), "h"((uint16_t)3) : "memory");
            if (i == 2) TSTAMP(19);
          }
          src += 4096;
          dst += (i == 5 || i == 10) ? -4 * 16384 : 16384;
        }
      } else {
        const unsigned* flag = &g_z.hint[(tg * 2 + half) * 32 + rank * 16 + slice_of(lane & 15)].x;
        bool seen = lane < 2 || lane > 15;
        mbar_wait(BAR(B_OP + half * 2 + rank), 0);
        int it = 0;
        do {
          if (ld_relaxed(flag) != 0 && !seen) {
            mbar_arrive(BAR(B_GO) + lane * 8);
            seen = true;
          }
          if (++it > (1 << 20)) __trap();
        } while (!__all_sync(0xffffffffu, seen));
      }
    }
  } else {
    asm volatile("setmaxnreg.inc.sync.aligned.u32 224;");
    const int wg = warp >> 2, wi = warp & 3;
    cluster_wait();
    if (tid == 0) TSTAMP(59);
    float acc0[96], acc1[96];
    {
      int s = 0, ph = 0, sprev = 0;
#pragma unroll 1
      for (int kt = 0; kt < KT - STAGES; kt++) {
        mbar_wait(BAR(B_FULL + s), ph);
        if (kt == 0 && tid == 0) TSTAMP(1);
        if (tid == 0 && !(kt & 1)) TSTAMP(44 + kt / 2);
        const uint32_t da = dlo(SB0 + SM_RA, 16) + s * (A_BYTES >> 4) + wg * 512;
        const uint32_t db = dlo(SB0 + SM_RB, 4096) + s * (B_BYTES >> 4);
        wgmma_fence();
#pragma unroll
        for (int k = 0; k < 2; k++) {
          wgmma_ss_n192<0, 1, H64, H128>(acc0, da + k * 2, db + k * 128, (kt | k) != 0);
          wgmma_ss_n192<0, 1, H64, H128>(acc1, da + 256 + k * 2, db + k * 128, (kt | k) != 0);
        }
        wgmma_commit();
        wgmma_wait<1>();
        if (kt > 0 && wi < 2 && elect_one()) mbar_arrive_cluster((wi << 24) + SB0 + SM_BAR + 8 * (B_EMPTY + sprev));
        sprev = s;
        if (++s == STAGES) { s = 0; ph ^= 1; }
      }
#pragma unroll 1
      for (int kt = 0; kt < STAGES; kt++) {
        mbar_wait(BAR(B_FULL + s), ph);
        const uint32_t da = dlo(SB0 + SM_RA, 16) + s * (A_BYTES >> 4) + wg * 512;
        const uint32_t db = dlo(SB0 + SM_RB, 4096) + s * (B_BYTES >> 4);
        wgmma_fence();
        wgmma_ss_n192<0, 1, H64, H128>(acc0, da, db, 1);
        wgmma_ss_n192<0, 1, H64, H128>(acc0, da + 2, db + 128, 1);
        wgmma_commit();
        wgmma_wait<1>();
        if (kt == 0 && wi < 2 && elect_one()) mbar_arrive_cluster((wi << 24) + SB0 + SM_BAR + 8 * (B_EMPTY + 1));
        if (++s == STAGES) { s = 0; ph ^= 1; }
      }
      mbar_wait(BAR(B_RDY), 0);
    }
    const int trow = wg * 128 + wi * 16 + (lane & 15);
    const int chi = lane >> 4;
    uint32_t ak[16], aq[2][16];
    float p[4][16];
    auto catch_one = [&](int i) {
      const int s = (2 + (i >> 1)) % STAGES;
      wgmma_ss_n192<0, 1, H64, H128>(acc1, dlo(SB0 + SM_RA + s * A_BYTES + 4096 + (i & 1) * 32, 16) + wg * 512, dlo(SB0 + SM_RB + s * B_BYTES + (i & 1) * 2048, 4096), 1);
    };
    auto catch_up = [&](int s) { wgmma_fence(); catch_one(2 * s - 4); catch_one(2 * s - 3); wgmma_commit(); };
    auto store_v = [&](const float (&acc)[96], int mb) {
#pragma unroll
      for (int h = 0; h < 2; h++)
#pragma unroll
        for (int jj = 0; jj < 2; jj++) {
          const int o = 64 + h * 16 + jj * 8;
          stsm4(sb + SM_V + h * 16384 + (trow + mb * 64) * 64 + (((2 * jj + chi) ^ ((trow >> 1) & 3)) << 4),
                pack_bf16(acc[o], acc[o + 1]), pack_bf16(acc[o + 2], acc[o + 3]), pack_bf16(acc[o + 4], acc[o + 5]), pack_bf16(acc[o + 6], acc[o + 7]));
        }
    };
    const uint32_t pa = sb + SM_PHIK + (wi >> 1) * 16384 + wg * 8192 + (trow & 31) * 128 + ((chi ^ (trow & 7)) << 4);
    auto store_phi = [&](const uint32_t (&phi)[16], int h, int mb) { store_phi_k(phi, pa + (1 - h) * 32768 + mb * 4096); };
    auto hand_over = [&](int i, bool ok) { hand_over_smem(BAR(B_PHI + i), ok); };
    bool okk[3];
    {
      HState hs;
      uint32_t phi[16];
      float d0, d1;
      catch_up(2);
      wgmma_wait<1>();
      fence_regs(acc0);
      if (tid == 0) TSTAMP(2);
      store_v(acc0, 0);
      pack_frags<32>(acc0, ak);
      issue_feat(ak, p[0], p[1], SB0 + SM_WPHI);
      catch_up(3);
      pack_frags<0>(acc0, aq[0]);
      wgmma_wait<1>();
      fence_regs(p[0]); fence_regs(p[1]); keep_alive(ak);
      wgmma_fence();
#pragma unroll
      for (int i = 4; i < 4 + NFIRST; i++) catch_one(i);
      okk[0] = hedgehog_fast<true>(p[0], phi, d0, d1);
      store_phi(phi, 0, 0);
#pragma unroll
      for (int i = 4 + NFIRST; i < 12; i++) catch_one(i);
      wgmma_commit();
      okk[0] &= hedgehog_fast<true>(p[1], phi, d0, d1);
      store_phi(phi, 1, 0);
      if (tid == 0) TSTAMP(17);
      wgmma_wait<0>();
      fence_regs(acc1);
      if (tid == 0) TSTAMP(27);
      if (wi < 2 && elect_one()) mbar_arrive_cluster((wi << 24) + SB0 + SM_BAR + 8 * (B_EMPTY + 1));
      pack_frags<32>(acc1, ak);
      issue_feat(ak, p[2], p[3], SB0 + SM_WPHI);
      store_v(acc1, 1);
      pack_frags<0>(acc1, aq[1]);
      wgmma_wait<0>();
      fence_regs(p[2]); fence_regs(p[3]); keep_alive(ak);
      asm volatile("setmaxnreg.dec.sync.aligned.u32 " STR(REG_C) ";");
      if (tid == 0) TSTAMP(28);
      HState h2;
      hedgehog_fast1<QUAD>(p[2], hs);
      hedgehog_fast1<QUAD>(p[3], h2);
      okk[1] = __all_sync(0xffffffffu, okk[0] & hedgehog_fast2<true>(hs, phi, d0, d1));
      store_phi(phi, 0, 1);
      hand_over(0, okk[1]);
      h2.s[0] += lds_f32(sb + SM_INFO + 12);
      okk[2] = __all_sync(0xffffffffu, okk[0] & hedgehog_fast2<true>(h2, phi, d0, d1));
      store_phi(phi, 1, 1);
      hand_over(1, okk[2]);
    }
    if (__builtin_expect(!(okk[1] & okk[2]), 0)) {
      __align__(16) float buf[64];
#pragma unroll
      for (int i = 0; i < 64; i++) buf[i] = p[i >> 4][i & 15];
      redo_phi_k(buf, okk[1] * 5 + okk[2] * 10, pa, BAR(B_PHI));
    }
    if (wi == 0 && lane == 0) TSTAMP(wg ? 29 : 3);
    uint32_t pq[4][16];
    float sc[8];
    issue_feat(aq[0], p[0], p[1], SB0 + SM_WPHI);
    issue_feat(aq[1], p[2], p[3], SB0 + SM_WPHI);
    mbar_wait(BAR(Q_AFTER), 0);
    wgmma_wait<0>();
#pragma unroll
    for (int u = 0; u < 4; u++) fence_regs(p[u]);
    keep_alive(aq[0]); keep_alive(aq[1]);
    if (tid == 0) TSTAMP(4);
    {
      bool ok = true;
#pragma unroll
      for (int u = 0; u < 4; u++) ok &= hedgehog_fast<false>(p[u], pq[u], sc[2 * u], sc[2 * u + 1]);
      if (__builtin_expect(!__all_sync(0xffffffffu, ok), 0)) {
        __align__(16) float buf[64];
#pragma unroll
        for (int i = 0; i < 64; i++) buf[i] = p[i >> 4][i & 15];
        hedgehog_slow(buf, 4);
#pragma unroll
        for (int i = 0; i < 64; i++) pq[i >> 4][i & 15] = __float_as_uint(buf[i]);
#pragma unroll
        for (int i = 0; i < 8; i++) sc[i] = 1.0f;
      }
    }
    if (tid == 0) TSTAMP(5);
    float acc[64];
    const int wq = wg ^ half;
    const uint32_t xo = wq * 8192 + wi * 2048 + (lane & 15) * 128 + ((chi ^ (lane & 7)) << 4);
    const uint32_t ga = sb + SM_GATE + (half * 128 + wq * 64 + wi * 16) * 2 + (lane >> 2) * 2;
    mbar_wait(BAR(B_XT + wq), 0);
    float gt[4];
#pragma unroll
    for (int i = 0; i < 4; i++) gt[i] = lds_bf16(sb + SM_GATE + (wg * 128 + (i >> 1) * 64 + wi * 16 + (i & 1) * 8 + (lane >> 2)) * 2);
    const float g0 = lds_bf16(ga), g1 = lds_bf16(ga + 16);
    const unsigned routed = lds_u32(sb + SM_INFO + 4);
    const uint32_t par = lds_u32(sb + SM_INFO) & 1, tmask = (lane & 3) ? ~0u : ~1u, tbit = (lane & 3) ? 0u : par;
    mbar_wait(BAR(B_KVB), 0);
    if (tid == 0) TSTAMP(7);
    if (wg != half) mbar_wait(BAR(B_OP + half * 2 + O_YIELD - 1), 0);
    {
      float nd[4][20];
#pragma unroll
      for (int u = 0; u < 4; u++)
#pragma unroll
        for (int i = 0; i < 16; i++) asm volatile("" : "+r"(pq[u][i]) :: "memory");
      auto num = [&](int mb, int k0, int k1) {
#pragma unroll
        for (int kk = k0; kk < k1; kk++)
#pragma unroll
          for (int h = 0; h < 2; h++) {
            const int u = mb * 2 + h;
            wgmma_rs_n40<1, H64>(nd[u], pq[u][4 * kk], pq[u][4 * kk + 1], pq[u][4 * kk + 2], pq[u][4 * kk + 3],
                                 dlo(SB0 + SM_KVB + h * 4096 + kk * 1024, 8192 - h * 4096 + h * 16), kk != 0);
          }
        wgmma_commit();
      };
      wgmma_fence();
      num(0, 0, 4);
      if (O_OVL == 2) num(1, 0, 4);
#pragma unroll
      for (int mb = 0; mb < 2; mb++) {
        if (O_OVL == 2 && mb == 0) wgmma_wait<1>(); else wgmma_wait<0>();
        fence_regs(nd[2 * mb]); fence_regs(nd[2 * mb + 1]);
        if (O_OVL == 1 && mb == 0) { wgmma_fence(); num(1, 0, 4); }
        if (tid == 0 && mb == 0) TSTAMP(18);
#pragma unroll
        for (int h = 0; h < 2; h++) {
          const int u = mb * 2 + h;
          const float i0 = gt[2 * mb] * rcp(fmaf(sc[2 * u], 1e-6f, nd[u][16])), i1 = gt[2 * mb + 1] * rcp(fmaf(sc[2 * u + 1], 1e-6f, nd[u][18]));
#pragma unroll
          for (int jj = 0; jj < 2; jj++) {
            const int o = jj * 8;
            stsm4(sb + SM_O + (wg ^ half) * 16384 + ((trow & 63) + mb * 64) * 128 + (((h * 4 + 2 * jj + chi) ^ (trow & 7)) << 4),
                  (pack_bf16(nd[u][o] * i0, nd[u][o + 1] * i0) & tmask) | tbit, (pack_bf16(nd[u][o + 2] * i1, nd[u][o + 3] * i1) & tmask) | tbit,
                  pack_bf16(nd[u][o + 4] * i0, nd[u][o + 5] * i0), pack_bf16(nd[u][o + 6] * i1, nd[u][o + 7] * i1));
          }
        }
        fence_async_smem();
        __syncwarp();
        if (elect_one()) mbar_arrive(BAR(B_OP + wg * 2 + mb));
        if (!O_OVL && mb == 0) { wgmma_fence(); num(1, 0, 4); }
      }
#pragma unroll
      for (int u = 0; u < 4; u++)
#pragma unroll
        for (int i = 0; i < 16; i++) asm volatile("" :: "r"(pq[u][i]) : "memory");
    }
    if (tid == 0) TSTAMP(8);
    uint32_t stale = 0;
    {
      const uint32_t ca = sb - SB0 - (dlo(0, 16) << 4) + wi * 2048 + (lane >> 2) * 128 + ((((lane & 3) * 2) ^ (lane >> 2)) << 4);
      const uint32_t da_end = dlo(SB0 + SM_RA + NA2 * 16384, 16) + wq * 512, f_end = BAR(B_F2 + wq * 16 + 16);
      uint32_t da = da_end - 1024, db = dlo(SB0 + SM_RB + 4 * 16384, 8192), f = f_end - 128;
      uint32_t xs[32];
#pragma unroll
      for (int i = 0; i < 2; i++) {
        mbar_wait(f + i * 8, 0);
        wgmma_fence();
#pragma unroll
        for (int k = 0; k < 4; k++) wgmma_ss_n128<0, 1, H128, H128>(acc, da - i * 4096 + k * 2, db + i * 1024 + k * 128, (i | k) != 0);
        wgmma_commit();
        if (i == 0) {
#pragma unroll
          for (int jj = 0; jj < 8; jj++)
            ldsm4(((sb + SM_XT + xo) ^ ((jj & 3) << 5)) + (jj >> 2) * 16384, xs[4 * jj], xs[4 * jj + 1], xs[4 * jj + 2], xs[4 * jj + 3]);
          fence_async_smem();
          __syncwarp();
          if (elect_one()) mbar_arrive_cluster(((XT_IN_A ? wq : rank) << 24) + SB0 + SM_BAR + 8 * (XT_IN_A ? B_GO + 3 : B_XTD));
        }
      }
      const float og0 = round_bf16(1.0f - g0), og1 = round_bf16(1.0f - g1);
      da -= 3072; db += 2048; f += 16;
      wgmma_wait<0>();
      fence_regs(acc);
      uint32_t dn = SB0 + SM_BAR + (wi ? (wq << 24) + 8 * (B_GO + NA2) : (rank << 24) + 8 * B_DB);
      if (wi < 2 && elect_one()) mbar_arrive_cluster(dn);
#pragma unroll
      for (int i = 0; i < 32; i++) { acc[2 * i] = fmaf((i & 1) ? og1 : og0, bf_lo(xs[i]), acc[2 * i]); acc[2 * i + 1] = fmaf((i & 1) ? og1 : og0, bf_hi(xs[i]), acc[2 * i + 1]); }
      fence_regs(acc);
      bool got = false;
#pragma unroll 1
      do {
        if (!got) mbar_wait(f, 0);
        wgmma_fence();
        wgmma_ss_n128<0, 1, H128, H128>(acc, da, db, 1);
        const uint32_t ta = ca + (da << 4), t0 = lds_u32(ta), t1 = lds_u32(ta + 1024);
        got = mbar_test(f + 8, 0);
#pragma unroll
        for (int k = 1; k < 4; k++) wgmma_ss_n128<0, 1, H128, H128>(acc, da + k * 2, db + k * 128, 1);
        wgmma_commit();
        da += 1024; if (da == da_end) da -= NA2 * 1024;
        db += 1024; if (db == dlo(SB0 + SM_RB + NB2 * 16384, 8192)) db -= NB2 * 1024;
        f += 8;
        stale |= (t0 ^ par) | (t1 ^ par);
        if (LEAD2 && wq == 0 && wi == 2 && f == f_end - 8 * LEAD_AT && elect_one()) mbar_arrive(BAR(B_F2 + 32 - LEAD2));
        wgmma_wait<1>();
        dn += 8;
        if (wi < 2 && f <= f_end - 32 && elect_one()) mbar_arrive_cluster(dn);
      } while (f != f_end);
      if (__builtin_expect((routed >> 6) == tg * 4 + half * 2 + wq && EXPT != 12, 0)) {
        const unsigned r = (routed & 63) - wi * 16 - (lane >> 2);
        const uint32_t one = (lane & 3) ? 0u : 0x3f80u;
        mbar_wait_bounded(BAR(B_Y), 0);
        wgmma_fence();
        wgmma_rs_n128<1, H128>(acc, r == 0 ? one : 0u, r == 8 ? one : 0u, 0, 0, dlo(SB0 + SM_UPD, 2048), 1);
        wgmma_commit();
      }
      const uint32_t xa = sb + SM_RA + xo, xt = sb + SM_RA + wq * 8192 + wi * 2048;
      const int orow = tg * 256 + half * 128 + wq * 64 + wi * 16;
      const bool redo = __any_sync(0xffffffffu, stale & 1);
      wgmma_wait<0>();
      fence_regs(acc);
      if (wi == 0 && lane == 0) TSTAMP(wq ? 25 : 11);
      stage_out<0, 4>(acc, xa);
      fence_async_smem();
      __syncwarp();
      if (!redo && elect_one()) tma_store_2d(&maps.out, xt, ct * 128, orow);
      stage_out<4, 8>(acc, xa);
      if (__builtin_expect(redo, 0))
        redo_rows(x, wo, sb, b, wq, xa);
      fence_async_smem();
      __syncwarp();
      if (elect_one()) {
        tma_store_2d(&maps.out, xt + 16384, ct * 128 + 64, orow);
        if (redo) tma_store_2d(&maps.out, xt, ct * 128, orow);
      }
      bulk_commit();
      bulk_wait0_read();
    }
  }
}

typedef CUresult (*PFN_encodeTiled)(CUtensorMap*, CUtensorMapDataType, cuuint32_t, void*, const cuuint64_t*, const cuuint64_t*,
                                    const cuuint32_t*, const cuuint32_t*, CUtensorMapInterleave, CUtensorMapSwizzle,
                                    CUtensorMapL2promotion, CUtensorMapFloatOOBfill);
static void make_map(PFN_encodeTiled fn, CUtensorMap* m, const void* ptr, uint64_t rows, uint64_t cols, uint32_t brows, uint32_t bcols,
                     CUtensorMapSwizzle sw, CUtensorMapL2promotion prom) {
  cuuint64_t dims[2] = {cols, rows}; cuuint64_t strides[1] = {cols * 2}; cuuint32_t box[2] = {bcols, brows}; cuuint32_t es[2] = {1, 1};
  fn(m, CU_TENSOR_MAP_DATA_TYPE_BFLOAT16, 2, const_cast<void*>(ptr), dims, strides, box, es, CU_TENSOR_MAP_INTERLEAVE_NONE, sw, prom,
     CU_TENSOR_MAP_FLOAT_OOB_FILL_NONE);
}

extern "C" void kernel_launch(void* const* d_in, const int* in_sizes, int n_in, void* d_out, int out_size) {
  const __nv_bfloat16* x = (const __nv_bfloat16*)d_in[0];
  const __nv_bfloat16* wqkv = (const __nv_bfloat16*)d_in[1];
  const __nv_bfloat16* wphi = (const __nv_bfloat16*)d_in[2];
  const __nv_bfloat16* wo = (const __nv_bfloat16*)d_in[3];
  const __nv_bfloat16* w_r = (const __nv_bfloat16*)d_in[5];
  const __nv_bfloat16* w_gate = (const __nv_bfloat16*)d_in[6];
  const __nv_bfloat16* w_up = (const __nv_bfloat16*)d_in[7];
  const __nv_bfloat16* w_down = (const __nv_bfloat16*)d_in[8];
  const __nv_bfloat16* gate_w = (const __nv_bfloat16*)d_in[9];
  void* fp = nullptr; cudaDriverEntryPointQueryResult qr;
  cudaGetDriverEntryPoint("cuTensorMapEncodeTiled", &fp, cudaEnableDefault, &qr);
  PFN_encodeTiled fn = (PFN_encodeTiled)fp;
  Maps m;
  const CUtensorMapL2promotion P128 = CU_TENSOR_MAP_L2_PROMOTION_L2_128B;
  make_map(fn, &m.x, x, S_, D_, 128, 32, CU_TENSOR_MAP_SWIZZLE_64B, (CUtensorMapL2promotion)PROM_X);
  {
    cuuint64_t dims[3] = {D_, D_, 3}; cuuint64_t strides[2] = {3 * D_ * 2, D_ * 2}; cuuint32_t box[3] = {64, 32, 3}; cuuint32_t es[3] = {1, 1, 1};
    fn(&m.w, CU_TENSOR_MAP_DATA_TYPE_BFLOAT16, 3, (void*)wqkv, dims, strides, box, es, CU_TENSOR_MAP_INTERLEAVE_NONE,
       CU_TENSOR_MAP_SWIZZLE_128B, (CUtensorMapL2promotion)PROM_W, CU_TENSOR_MAP_FLOAT_OOB_FILL_NONE);
  }
  {
    cuuint64_t dims[3] = {64, D_, 16}; cuuint64_t strides[2] = {D_ * 2, 128}; cuuint32_t box[3] = {64, 64, 2}; cuuint32_t es[3] = {1, 1, 1};
    fn(&m.wo, CU_TENSOR_MAP_DATA_TYPE_BFLOAT16, 3, (void*)wo, dims, strides, box, es, CU_TENSOR_MAP_INTERLEAVE_NONE,
       CU_TENSOR_MAP_SWIZZLE_128B, P128, CU_TENSOR_MAP_FLOAT_OOB_FILL_NONE);
  }
  make_map(fn, &m.wphi, wphi, 1024, 32, 64, 32, CU_TENSOR_MAP_SWIZZLE_64B, P128);
  for (int i = 0; i < 3; i++) {
    cuuint64_t dims[3] = {i < 2 ? (cuuint64_t)F_ : 64, i < 2 ? (cuuint64_t)16 : F_, i < 2 ? (cuuint64_t)64 : 16};
    cuuint64_t strides[2] = {i < 2 ? (cuuint64_t)F_ * 2 : D_ * 2, i < 2 ? (cuuint64_t)F_ * 32 : 128};
    cuuint32_t box[3] = {64, i < 2 ? 16u : 4u, i < 2 ? 4u : 16u}; cuuint32_t es[3] = {1, 1, 1};
    fn(&m.wg + i, CU_TENSOR_MAP_DATA_TYPE_BFLOAT16, 3, (void*)(i == 0 ? w_gate : i == 1 ? w_up : w_down), dims, strides, box, es,
       CU_TENSOR_MAP_INTERLEAVE_NONE, CU_TENSOR_MAP_SWIZZLE_NONE, P128, CU_TENSOR_MAP_FLOAT_OOB_FILL_NONE);
  }
  make_map(fn, &m.xt, x, S_, D_, 64, 64, CU_TENSOR_MAP_SWIZZLE_128B, P128);
  make_map(fn, &m.out, d_out, S_, D_, 16, 64, CU_TENSOR_MAP_SWIZZLE_128B, P128);
  make_map(fn, &m.xr, x, S_, D_, 16, 128, CU_TENSOR_MAP_SWIZZLE_NONE, P128);
  make_map(fn, &m.tg, w_gate, D_, F_, 64, 64, CU_TENSOR_MAP_SWIZZLE_NONE, (CUtensorMapL2promotion)PROM_F);
  make_map(fn, &m.tu, w_up, D_, F_, 64, 64, CU_TENSOR_MAP_SWIZZLE_NONE, (CUtensorMapL2promotion)PROM_F);
  make_map(fn, &m.td, w_down, F_ * 16, 64, 64, 64, CU_TENSOR_MAP_SWIZZLE_NONE, P128);
  make_map(fn, &m.to, wo, D_ * 16, 64, 64, 64, CU_TENSOR_MAP_SWIZZLE_NONE, P128);
  cudaFuncSetAttribute(fused_kernel, cudaFuncAttributeMaxDynamicSharedMemorySize, SM_TOTAL);
  int dev = 0, sms = 0;
  cudaGetDevice(&dev);
  cudaDeviceGetAttribute(&sms, cudaDevAttrMultiProcessorCount, dev);
  const int by_smid = BY_SMID && sms == NCTA + 4;
  fused_kernel<<<by_smid ? NCTA + 4 : NCTA + 2, 512, SM_TOTAL>>>(m, x, wo, w_r, gate_w, by_smid);
}
```

```cpp
#include <cuda_runtime.h>
#include <cuda_bf16.h>
#include <cuda.h>
#include <stdint.h>

__device__ __forceinline__ uint32_t smem_u32(const void* p) { return (uint32_t)__cvta_generic_to_shared(p); }
__device__ __forceinline__ void mbar_init(uint32_t bar, uint32_t cnt) { asm volatile("mbarrier.init.shared::cta.b64 [%0], %1;" :: "r"(bar), "r"(cnt) : "memory"); }
__device__ __forceinline__ void mbar_expect_tx(uint32_t bar, uint32_t bytes) { asm volatile("mbarrier.arrive.expect_tx.shared::cta.b64 _, [%0], %1;" :: "r"(bar), "r"(bytes) : "memory"); }
__device__ __forceinline__ void mbar_arrive(uint32_t bar) { asm volatile("mbarrier.arrive.shared::cta.b64 _, [%0];" :: "r"(bar) : "memory"); }
__device__ __forceinline__ bool mbar_try_wait(uint32_t bar, uint32_t parity) {
  uint32_t ok;
  asm volatile("{\n.reg .pred p;\nmbarrier.try_wait.parity.shared::cta.b64 p, [%1], %2;\nselp.u32 %0, 1, 0, p;\n}" : "=r"(ok) : "r"(bar), "r"(parity) : "memory");
  return ok;
}
__device__ __forceinline__ bool mbar_test(uint32_t bar, uint32_t parity) {
  uint32_t ok;
  asm volatile("{\n.reg .pred p;\nmbarrier.test_wait.parity.shared::cta.b64 p, [%1], %2;\nselp.u32 %0, 1, 0, p;\n}" : "=r"(ok) : "r"(bar), "r"(parity) : "memory");
  return ok;
}
__device__ __forceinline__ void mbar_wait(uint32_t bar, uint32_t parity) {
  asm volatile("{\n.reg .pred p;\nWAIT: mbarrier.try_wait.parity.shared::cta.b64 p, [%0], %1;\n@!p bra.uni WAIT;\n}" :: "r"(bar), "r"(parity) : "memory");
}
__device__ __forceinline__ void mbar_wait_bounded(uint32_t bar, uint32_t parity) {
#pragma unroll 1
  for (int it = 0; it < (1 << 22); it++) { if (mbar_try_wait(bar, parity)) return; }
  __trap();
}
__device__ __forceinline__ void tma_load_2d(uint32_t dst, const CUtensorMap* tm, int c0, int c1, uint32_t bar) {
  asm volatile("cp.async.bulk.tensor.2d.shared::cluster.global.mbarrier::complete_tx::bytes [%0], [%1, {%3, %4}], [%2];"
    :: "r"(dst), "l"(tm), "r"(bar), "r"(c0), "r"(c1) : "memory");
}
__device__ __forceinline__ void tma_load_2d_mc(uint32_t dst, const CUtensorMap* tm, int c0, int c1, uint32_t bar) {
  asm volatile("cp.async.bulk.tensor.2d.shared::cluster.global.mbarrier::complete_tx::bytes.multicast::cluster [%0], [%1, {%3, %4}], [%2], %5;"
    :: "r"(dst), "l"(tm), "r"(bar), "r"(c0), "r"(c1), "h"((uint16_t)3) : "memory");
}
__device__ __forceinline__ void mbar_arrive_cluster(uint32_t bar) { asm volatile("mbarrier.arrive.shared::cluster.b64 _, [%0];" :: "r"(bar) : "memory"); }
__device__ __forceinline__ void wgmma_fence() { asm volatile("wgmma.fence.sync.aligned;" ::: "memory"); }
__device__ __forceinline__ void wgmma_commit() { asm volatile("wgmma.commit_group.sync.aligned;" ::: "memory"); }
template <int N> __device__ __forceinline__ void wgmma_wait() { asm volatile("wgmma.wait_group.sync.aligned %0;" :: "n"(N) : "memory"); }
template <int N> __device__ __forceinline__ void fence_regs(float (&d)[N]) {
#pragma unroll
  for (int i = 0; i < N; i++) asm volatile("" : "+f"(d[i]) :: "memory");
}
__host__ __device__ constexpr uint32_t dlo(uint32_t addr, uint32_t lbo) { return (addr >> 4) | ((lbo >> 4) << 16); }
constexpr uint32_t H128 = (1024 >> 4) | (1u << 30);
constexpr uint32_t H64 = (512 >> 4) | (2u << 30);

template <int TA, int TB, uint32_t HA, uint32_t HB>
__device__ __forceinline__ void wgmma_ss_n192(float (&d)[96], uint32_t da, uint32_t db, int scale_d) {
  asm volatile("{\n.reg .pred p;\n.reg .b64 da, db;\nsetp.ne.b32 p, %98, 0;\nmov.b64 da, {%96, %101};\nmov.b64 db, {%97, %102};\n"
    "wgmma.mma_async.sync.aligned.m64n192k16.f32.bf16.bf16 {%0, %1, %2, %3, %4, %5, %6, %7, %8, %9, %10, %11, %12, %13, %14, %15, %16, %17, %18, %19, %20, %21, %22, %23, %24, %25, %26, %27, %28, %29, %30, %31, %32, %33, %34, %35, %36, %37, %38, %39, %40, %41, %42, %43, %44, %45, %46, %47, %48, %49, %50, %51, %52, %53, %54, %55, %56, %57, %58, %59, %60, %61, %62, %63, %64, %65, %66, %67, %68, %69, %70, %71, %72, %73, %74, %75, %76, %77, %78, %79, %80, %81, %82, %83, %84, %85, %86, %87, %88, %89, %90, %91, %92, %93, %94, %95}, da, db, p, 1, 1, %99, %100;\n}\n"
    : "+f"(d[0]), "+f"(d[1]), "+f"(d[2]), "+f"(d[3]), "+f"(d[4]), "+f"(d[5]), "+f"(d[6]), "+f"(d[7]), "+f"(d[8]), "+f"(d[9]), "+f"(d[10]), "+f"(d[11]), "+f"(d[12]), "+f"(d[13]), "+f"(d[14]), "+f"(d[15]), "+f"(d[16]), "+f"(d[17]), "+f"(d[18]), "+f"(d[19]), "+f"(d[20]), "+f"(d[21]), "+f"(d[22]), "+f"(d[23]), "+f"(d[24]), "+f"(d[25]), "+f"(d[26]), "+f"(d[27]), "+f"(d[28]), "+f"(d[29]), "+f"(d[30]), "+f"(d[31]), "+f"(d[32]), "+f"(d[33]), "+f"(d[34]), "+f"(d[35]), "+f"(d[36]), "+f"(d[37]), "+f"(d[38]), "+f"(d[39]), "+f"(d[40]), "+f"(d[41]), "+f"(d[42]), "+f"(d[43]), "+f"(d[44]), "+f"(d[45]), "+f"(d[46]), "+f"(d[47]), "+f"(d[48]), "+f"(d[49]), "+f"(d[50]), "+f"(d[51]), "+f"(d[52]), "+f"(d[53]), "+f"(d[54]), "+f"(d[55]), "+f"(d[56]), "+f"(d[57]), "+f"(d[58]), "+f"(d[59]), "+f"(d[60]), "+f"(d[61]), "+f"(d[62]), "+f"(d[63]), "+f"(d[64]), "+f"(d[65]), "+f"(d[66]), "+f"(d[67]), "+f"(d[68]), "+f"(d[69]), "+f"(d[70]), "+f"(d[71]), "+f"(d[72]), "+f"(d[73]), "+f"(d[74]), "+f"(d[75]), "+f"(d[76]), "+f"(d[77]), "+f"(d[78]), "+f"(d[79]), "+f"(d[80]), "+f"(d[81]), "+f"(d[82]), "+f"(d[83]), "+f"(d[84]), "+f"(d[85]), "+f"(d[86]), "+f"(d[87]), "+f"(d[88]), "+f"(d[89]), "+f"(d[90]), "+f"(d[91]), "+f"(d[92]), "+f"(d[93]), "+f"(d[94]), "+f"(d[95])
    : "r"(da), "r"(db), "r"(scale_d), "n"(TA), "n"(TB), "n"(HA), "n"(HB));
}

template <int TA, int TB, uint32_t HA, uint32_t HB>
__device__ __forceinline__ void wgmma_ss_n128(float (&d)[64], uint32_t da, uint32_t db, int scale_d) {
  asm volatile("{\n.reg .pred p;\n.reg .b64 da, db;\nsetp.ne.b32 p, %66, 0;\nmov.b64 da, {%64, %69};\nmov.b64 db, {%65, %70};\n"
    "wgmma.mma_async.sync.aligned.m64n128k16.f32.bf16.bf16 {%0, %1, %2, %3, %4, %5, %6, %7, %8, %9, %10, %11, %12, %13, %14, %15, %16, %17, %18, %19, %20, %21, %22, %23, %24, %25, %26, %27, %28, %29, %30, %31, %32, %33, %34, %35, %36, %37, %38, %39, %40, %41, %42, %43, %44, %45, %46, %47, %48, %49, %50, %51, %52, %53, %54, %55, %56, %57, %58, %59, %60, %61, %62, %63}, da, db, p, 1, 1, %67, %68;\n}\n"
    : "+f"(d[0]), "+f"(d[1]), "+f"(d[2]), "+f"(d[3]), "+f"(d[4]), "+f"(d[5]), "+f"(d[6]), "+f"(d[7]), "+f"(d[8]), "+f"(d[9]), "+f"(d[10]), "+f"(d[11]), "+f"(d[12]), "+f"(d[13]), "+f"(d[14]), "+f"(d[15]), "+f"(d[16]), "+f"(d[17]), "+f"(d[18]), "+f"(d[19]), "+f"(d[20]), "+f"(d[21]), "+f"(d[22]), "+f"(d[23]), "+f"(d[24]), "+f"(d[25]), "+f"(d[26]), "+f"(d[27]), "+f"(d[28]), "+f"(d[29]), "+f"(d[30]), "+f"(d[31]), "+f"(d[32]), "+f"(d[33]), "+f"(d[34]), "+f"(d[35]), "+f"(d[36]), "+f"(d[37]), "+f"(d[38]), "+f"(d[39]), "+f"(d[40]), "+f"(d[41]), "+f"(d[42]), "+f"(d[43]), "+f"(d[44]), "+f"(d[45]), "+f"(d[46]), "+f"(d[47]), "+f"(d[48]), "+f"(d[49]), "+f"(d[50]), "+f"(d[51]), "+f"(d[52]), "+f"(d[53]), "+f"(d[54]), "+f"(d[55]), "+f"(d[56]), "+f"(d[57]), "+f"(d[58]), "+f"(d[59]), "+f"(d[60]), "+f"(d[61]), "+f"(d[62]), "+f"(d[63])
    : "r"(da), "r"(db), "r"(scale_d), "n"(TA), "n"(TB), "n"(HA), "n"(HB));
}

template <int TA, int TB, uint32_t HA, uint32_t HB>
__device__ __forceinline__ void wgmma_ss_n40(float (&d)[20], uint32_t da, uint32_t db, int scale_d) {
  asm volatile("{\n.reg .pred p;\n.reg .b64 da, db;\nsetp.ne.b32 p, %22, 0;\nmov.b64 da, {%20, %25};\nmov.b64 db, {%21, %26};\n"
    "wgmma.mma_async.sync.aligned.m64n40k16.f32.bf16.bf16 {%0, %1, %2, %3, %4, %5, %6, %7, %8, %9, %10, %11, %12, %13, %14, %15, %16, %17, %18, %19}, da, db, p, 1, 1, %23, %24;\n}\n"
    : "+f"(d[0]), "+f"(d[1]), "+f"(d[2]), "+f"(d[3]), "+f"(d[4]), "+f"(d[5]), "+f"(d[6]), "+f"(d[7]), "+f"(d[8]), "+f"(d[9]), "+f"(d[10]), "+f"(d[11]), "+f"(d[12]), "+f"(d[13]), "+f"(d[14]), "+f"(d[15]), "+f"(d[16]), "+f"(d[17]), "+f"(d[18]), "+f"(d[19])
    : "r"(da), "r"(db), "r"(scale_d), "n"(TA), "n"(TB), "n"(HA), "n"(HB));
}

template <int TB, uint32_t HB>
__device__ __forceinline__ void wgmma_rs_n32(float (&d)[16], uint32_t a0, uint32_t a1, uint32_t a2, uint32_t a3, uint32_t db, int scale_d) {
  asm volatile("{\n.reg .pred p;\n.reg .b64 db;\nsetp.ne.b32 p, %21, 0;\nmov.b64 db, {%20, %23};\n"
    "wgmma.mma_async.sync.aligned.m64n32k16.f32.bf16.bf16 {%0, %1, %2, %3, %4, %5, %6, %7, %8, %9, %10, %11, %12, %13, %14, %15}, {%16, %17, %18, %19}, db, p, 1, 1, %22;\n}\n"
    : "+f"(d[0]), "+f"(d[1]), "+f"(d[2]), "+f"(d[3]), "+f"(d[4]), "+f"(d[5]), "+f"(d[6]), "+f"(d[7]), "+f"(d[8]), "+f"(d[9]), "+f"(d[10]), "+f"(d[11]), "+f"(d[12]), "+f"(d[13]), "+f"(d[14]), "+f"(d[15])
    : "r"(a0), "r"(a1), "r"(a2), "r"(a3), "r"(db), "r"(scale_d), "n"(TB), "n"(HB));
}

template <int TB, uint32_t HB>
__device__ __forceinline__ void wgmma_rs_n40(float (&d)[20], uint32_t a0, uint32_t a1, uint32_t a2, uint32_t a3, uint32_t db, int scale_d) {
  asm volatile("{\n.reg .pred p;\n.reg .b64 db;\nsetp.ne.b32 p, %25, 0;\nmov.b64 db, {%24, %27};\n"
    "wgmma.mma_async.sync.aligned.m64n40k16.f32.bf16.bf16 {%0, %1, %2, %3, %4, %5, %6, %7, %8, %9, %10, %11, %12, %13, %14, %15, %16, %17, %18, %19}, {%20, %21, %22, %23}, db, p, 1, 1, %26;\n}\n"
    : "+f"(d[0]), "+f"(d[1]), "+f"(d[2]), "+f"(d[3]), "+f"(d[4]), "+f"(d[5]), "+f"(d[6]), "+f"(d[7]), "+f"(d[8]), "+f"(d[9]), "+f"(d[10]), "+f"(d[11]), "+f"(d[12]), "+f"(d[13]), "+f"(d[14]), "+f"(d[15]), "+f"(d[16]), "+f"(d[17]), "+f"(d[18]), "+f"(d[19])
    : "r"(a0), "r"(a1), "r"(a2), "r"(a3), "r"(db), "r"(scale_d), "n"(TB), "n"(HB));
}

template <int TB, uint32_t HB>
__device__ __forceinline__ void wgmma_rs_n128(float (&d)[64], uint32_t a0, uint32_t a1, uint32_t a2, uint32_t a3, uint32_t db, int scale_d) {
  asm volatile("{\n.reg .pred p;\n.reg .b64 db;\nsetp.ne.b32 p, %69, 0;\nmov.b64 db, {%68, %71};\n"
    "wgmma.mma_async.sync.aligned.m64n128k16.f32.bf16.bf16 {%0, %1, %2, %3, %4, %5, %6, %7, %8, %9, %10, %11, %12, %13, %14, %15, %16, %17, %18, %19, %20, %21, %22, %23, %24, %25, %26, %27, %28, %29, %30, %31, %32, %33, %34, %35, %36, %37, %38, %39, %40, %41, %42, %43, %44, %45, %46, %47, %48, %49, %50, %51, %52, %53, %54, %55, %56, %57, %58, %59, %60, %61, %62, %63}, {%64, %65, %66, %67}, db, p, 1, 1, %70;\n}\n"
    : "+f"(d[0]), "+f"(d[1]), "+f"(d[2]), "+f"(d[3]), "+f"(d[4]), "+f"(d[5]), "+f"(d[6]), "+f"(d[7]), "+f"(d[8]), "+f"(d[9]), "+f"(d[10]), "+f"(d[11]), "+f"(d[12]), "+f"(d[13]), "+f"(d[14]), "+f"(d[15]), "+f"(d[16]), "+f"(d[17]), "+f"(d[18]), "+f"(d[19]), "+f"(d[20]), "+f"(d[21]), "+f"(d[22]), "+f"(d[23]), "+f"(d[24]), "+f"(d[25]), "+f"(d[26]), "+f"(d[27]), "+f"(d[28]), "+f"(d[29]), "+f"(d[30]), "+f"(d[31]), "+f"(d[32]), "+f"(d[33]), "+f"(d[34]), "+f"(d[35]), "+f"(d[36]), "+f"(d[37]), "+f"(d[38]), "+f"(d[39]), "+f"(d[40]), "+f"(d[41]), "+f"(d[42]), "+f"(d[43]), "+f"(d[44]), "+f"(d[45]), "+f"(d[46]), "+f"(d[47]), "+f"(d[48]), "+f"(d[49]), "+f"(d[50]), "+f"(d[51]), "+f"(d[52]), "+f"(d[53]), "+f"(d[54]), "+f"(d[55]), "+f"(d[56]), "+f"(d[57]), "+f"(d[58]), "+f"(d[59]), "+f"(d[60]), "+f"(d[61]), "+f"(d[62]), "+f"(d[63])
    : "r"(a0), "r"(a1), "r"(a2), "r"(a3), "r"(db), "r"(scale_d), "n"(TB), "n"(HB));
}

constexpr int S_ = 2048, D_ = 1024, F_ = 3584;
constexpr int NCTA = 128;
constexpr int NMOE = 112;
constexpr int KVH = 5 * 128 * 2;

constexpr int NY = 8;
struct Zeroed {
  float kv[32 * KVH];
  float y[NY * 2 * D_];
  uint4 hint[512];
  unsigned done[128];
  unsigned pad[1920];
};
constexpr int ZB = KVH + 128 + NY * 64;
static_assert(sizeof(Zeroed) == NCTA * ZB, "zeroed block");
__device__ __align__(128) Zeroed g_z;
__device__ __align__(128) unsigned g_key[2 * NCTA];
__device__ __align__(128) uint2 g_bcast[2 * 8 * 16];
__device__ __align__(128) unsigned g_gate[S_];
__device__ __align__(1024) __nv_bfloat16 g_o[S_ * D_];
#define TSTAMP(i)
#define GSTAMP(i)

constexpr int STAGES = 6, KT = 32;
constexpr int A_BYTES = 256 * 64, B_BYTES = 192 * 64, STAGE_BYTES = A_BYTES + B_BYTES;
constexpr int SM_RA = 0;
constexpr int SM_RB = STAGES * A_BYTES;
constexpr int SM_PHIK = 0;
constexpr int SM_V = 65536;
constexpr int SM_O = SM_V;
constexpr int NA2 = 5, NB2 = 7;
constexpr int SM_XT = SM_RA + 2 * 16384;
constexpr int SM_XR = STAGES * STAGE_BYTES;
constexpr int SM_MOE = SM_XR;
constexpr int SM_XSEL = SM_XR + 36864;
constexpr int SM_RED = SM_XSEL + 2048;
constexpr int SM_WPHI = 212992;
constexpr int SM_KVB = SM_WPHI + 4096;
constexpr int SM_ONES = SM_KVB + 12288;
constexpr int SM_BAR = SM_ONES + 1024;
constexpr int SM_INFO = SM_BAR + 1008;
constexpr int SM_GATE = SM_BAR + 1024;
constexpr int SM_UPD = SM_WPHI;
constexpr int SM_KEYS = SM_GATE + 512;
constexpr int SM_TS = SM_KEYS + 32;
constexpr int SM_TOTAL = SM_TS + 256;
static_assert(SM_TOTAL <= 232448 && ZB <= 4608, "smem");
static_assert(SM_WPHI % 1024 == 0 && SM_KVB % 1024 == 0 && SM_ONES % 1024 == 0, "align");
static_assert(SM_MOE + 40960 <= SM_WPHI && SM_RB + NB2 * 16384 <= SM_WPHI, "map");
#define COLMAP 0x97fdb5316eca4208ull
#define BY_SMID 1
#define EXPT 0
#define PF_START 0
#define KV_DELAY 400
#define NFIRST 5
#define Q_AFTER B_PHI + 1
#define LEAD2 6
#define B5_AFTER B_F2 + 2
#define REG_C 192
#define REG_K 88
#define STR2(x) #x
#define STR(x) STR2(x)
#define LEAD_AT 1
#define XR_AFTER 3
#define LATE_DELAY 300
#define LATE_STEP 400

constexpr int B_FULL = 0, B_XR = 6, B_WPHI = 10;
constexpr int B_EMPTY = 11, B_XRD = 17;
constexpr int B_INIT = 123;
constexpr int B_ST = 18, B_MOE = 20, B_XSEL = 24, B_H = 25, B_RDY = 26, B_Y = 27, B_XT = 28, B_PEER = 30;
constexpr int B_FB2 = 31, B_F2 = 47;
constexpr int B_DB = 79;
constexpr int B_GO = 95;
constexpr int B_KVB = 111, B_OP = 112, B_MOEE = 116;
constexpr int B_PHI = 120;
constexpr int NBAR = 122;
__host__ __device__ constexpr int bar_count(int i) {
  return i < B_DB ? 1 : i < B_GO ? 2 : i < B_KVB ? (int)(0x3333333333519111ull >> (4 * (i - B_GO))) & 15 : i < B_PHI ? 4 : 8;
}

struct Maps { CUtensorMap x, w, wo, wphi, wg, wu, wd, tg, tu, td, to, xr, xt, out; };

__device__ __forceinline__ uint32_t pack_bf16(float lo, float hi) {
  uint32_t r; asm("cvt.rn.bf16x2.f32 %0, %1, %2;" : "=r"(r) : "f"(hi), "f"(lo)); return r;
}
__device__ __forceinline__ float bf_lo(uint32_t v) { return __uint_as_float(v << 16); }
__device__ __forceinline__ float bf_hi(uint32_t v) { return __uint_as_float(v & 0xffff0000u); }
__device__ __forceinline__ float round_bf16(float v) { return __bfloat162float(__float2bfloat16_rn(v)); }
__device__ __forceinline__ float ex2(float v) { float r; asm("ex2.approx.ftz.f32 %0, %1;" : "=f"(r) : "f"(v)); return r; }
__device__ __forceinline__ float rcp(float v) { float r; asm("rcp.approx.ftz.f32 %0, %1;" : "=f"(r) : "f"(v)); return r; }
__device__ __forceinline__ void stsm4(uint32_t addr, uint32_t r0, uint32_t r1, uint32_t r2, uint32_t r3) {
  asm volatile("stmatrix.sync.aligned.m8n8.x4.shared.b16 [%0], {%1, %2, %3, %4};" :: "r"(addr), "r"(r0), "r"(r1), "r"(r2), "r"(r3) : "memory");
}
__device__ __forceinline__ uint2 lds64(uint32_t addr) {
  uint2 v; asm volatile("ld.shared.v2.u32 {%0, %1}, [%2];" : "=r"(v.x), "=r"(v.y) : "r"(addr) : "memory"); return v;
}
__device__ __forceinline__ void lds128x4(uint32_t addr, uint4& a, uint4& b, uint4& c, uint4& d) {
  asm volatile("ld.shared.v4.u32 {%0, %1, %2, %3}, [%16];\nld.shared.v4.u32 {%4, %5, %6, %7}, [%16 + 128];\n"
               "ld.shared.v4.u32 {%8, %9, %10, %11}, [%16 + 256];\nld.shared.v4.u32 {%12, %13, %14, %15}, [%16 + 384];"
    : "=r"(a.x), "=r"(a.y), "=r"(a.z), "=r"(a.w), "=r"(b.x), "=r"(b.y), "=r"(b.z), "=r"(b.w),
      "=r"(c.x), "=r"(c.y), "=r"(c.z), "=r"(c.w), "=r"(d.x), "=r"(d.y), "=r"(d.z), "=r"(d.w) : "r"(addr) : "memory");
}
__device__ __forceinline__ void ldsm4(uint32_t addr, uint32_t& r0, uint32_t& r1, uint32_t& r2, uint32_t& r3) {
  asm volatile("ldmatrix.sync.aligned.m8n8.x4.shared.b16 {%0, %1, %2, %3}, [%4];" : "=r"(r0), "=r"(r1), "=r"(r2), "=r"(r3) : "r"(addr) : "memory");
}
__device__ __forceinline__ uint4 lds128(uint32_t addr) {
  uint4 v; asm volatile("ld.shared.v4.u32 {%0, %1, %2, %3}, [%4];" : "=r"(v.x), "=r"(v.y), "=r"(v.z), "=r"(v.w) : "r"(addr) : "memory"); return v;
}
__device__ __forceinline__ void sts128(uint32_t addr, uint4 v) {
  asm volatile("st.shared.v4.u32 [%0], {%1, %2, %3, %4};" :: "r"(addr), "r"(v.x), "r"(v.y), "r"(v.z), "r"(v.w) : "memory");
}
__device__ __forceinline__ float lds_f32(uint32_t addr) { float v; asm volatile("ld.shared.f32 %0, [%1];" : "=f"(v) : "r"(addr) : "memory"); return v; }
__device__ __forceinline__ uint32_t lds_u32(uint32_t addr) { uint32_t v; asm volatile("ld.shared.u32 %0, [%1];" : "=r"(v) : "r"(addr) : "memory"); return v; }
__device__ __forceinline__ void sts_u32(uint32_t addr, uint32_t v) { asm volatile("st.shared.u32 [%0], %1;" :: "r"(addr), "r"(v) : "memory"); }
__device__ __forceinline__ unsigned clock32() { unsigned c; asm volatile("mov.u32 %0, %%clock;" : "=r"(c)); return c; }
__device__ __forceinline__ bool elect_one() {
  uint32_t p; asm volatile("{\n.reg .pred q;\nelect.sync _|q, 0xffffffff;\nselp.u32 %0, 1, 0, q;\n}" : "=r"(p)); return p;
}
__device__ __forceinline__ void bar_sync(int id, int n) { asm volatile("bar.sync %0, %1;" :: "r"(id), "r"(n) : "memory"); }
__device__ __forceinline__ void fence_async_smem() { asm volatile("fence.proxy.async.shared::cta;" ::: "memory"); }
__device__ __forceinline__ void fence_gpu() { asm volatile("fence.acq_rel.gpu;" ::: "memory"); }
__device__ __forceinline__ unsigned ld_acquire(const unsigned* p) { unsigned v; asm volatile("ld.acquire.gpu.global.u32 %0, [%1];" : "=r"(v) : "l"(p) : "memory"); return v; }
__device__ __forceinline__ unsigned ld_relaxed(const unsigned* p) { unsigned v; asm volatile("ld.relaxed.gpu.global.u32 %0, [%1];" : "=r"(v) : "l"(p) : "memory"); return v; }
__device__ __forceinline__ void st_relaxed(unsigned* p, unsigned v) { asm volatile("st.relaxed.gpu.global.u32 [%0], %1;" :: "l"(p), "r"(v) : "memory"); }
template <int SLEEP>
__device__ __forceinline__ unsigned wait_tagged(const uint2* p, unsigned tag) {
  uint2 v;
  int it = 0;
  do {
    if (SLEEP && it > 0) __nanosleep(SLEEP);
    asm volatile("ld.relaxed.gpu.global.v2.u32 {%0, %1}, [%2];" : "=r"(v.x), "=r"(v.y) : "l"(p) : "memory");
    if (++it > (1 << 20)) __trap();
  } while (!__all_sync(0xffffffffu, v.y == tag));
  return v.x;
}
__device__ __forceinline__ float4 ldg_l2(const float* p) {
  float4 v; asm volatile("ld.relaxed.gpu.global.v4.f32 {%0, %1, %2, %3}, [%4];" : "=f"(v.x), "=f"(v.y), "=f"(v.z), "=f"(v.w) : "l"(p) : "memory"); return v;
}
__device__ __forceinline__ void sts64(uint32_t addr, float a, float b) { asm volatile("st.shared.v2.f32 [%0], {%1, %2};" :: "r"(addr), "f"(a), "f"(b) : "memory"); }
__device__ __forceinline__ void bulk_load(uint32_t dst, const void* src, uint32_t bytes, uint32_t bar) {
  asm volatile("cp.async.bulk.shared::cluster.global.mbarrier::complete_tx::bytes [%0], [%1], %2, [%3];" :: "r"(dst), "l"(src), "r"(bytes), "r"(bar) : "memory");
}
__device__ __forceinline__ void tma_store_2d(const CUtensorMap* tm, uint32_t src, int c0, int c1) {
  asm volatile("cp.async.bulk.tensor.2d.global.shared::cta.bulk_group [%0, {%2, %3}], [%1];" :: "l"(tm), "r"(src), "r"(c0), "r"(c1) : "memory");
}
__device__ __forceinline__ void bulk_store(void* dst, uint32_t src, uint32_t bytes) {
  asm volatile("cp.async.bulk.global.shared::cta.bulk_group [%0], [%1], %2;" :: "l"(dst), "r"(src), "r"(bytes) : "memory");
}
__device__ __forceinline__ void tma_load_3d(uint32_t dst, const CUtensorMap* tm, int c0, int c1, int c2, uint32_t bar) {
  asm volatile("cp.async.bulk.tensor.3d.shared::cluster.global.mbarrier::complete_tx::bytes [%0], [%1, {%3, %4, %5}], [%2];"
    :: "r"(dst), "l"(tm), "r"(bar), "r"(c0), "r"(c1), "r"(c2) : "memory");
}
__device__ __forceinline__ void prefetch_map(const CUtensorMap* tm) { asm volatile("prefetch.tensormap [%0];" :: "l"(tm) : "memory"); }
__device__ __forceinline__ void bulk_commit() { asm volatile("cp.async.bulk.commit_group;" ::: "memory"); }
__device__ __forceinline__ void bulk_wait0() { asm volatile("cp.async.bulk.wait_group 0;" ::: "memory"); }
__device__ __forceinline__ void bulk_wait0_read() { asm volatile("cp.async.bulk.wait_group.read 0;" ::: "memory"); }
__device__ __forceinline__ void mma16816(float& d0, float& d1, float& d2, float& d3, uint32_t a0, uint32_t a1, uint32_t a2, uint32_t a3, uint32_t b0, uint32_t b1) {
  asm volatile("mma.sync.aligned.m16n8k16.row.col.f32.bf16.bf16.f32 {%0, %1, %2, %3}, {%4, %5, %6, %7}, {%8, %9}, {%0, %1, %2, %3};"
    : "+f"(d0), "+f"(d1), "+f"(d2), "+f"(d3) : "r"(a0), "r"(a1), "r"(a2), "r"(a3), "r"(b0), "r"(b1));
}
__device__ __forceinline__ uint32_t hmul2(uint32_t a, uint32_t b) { uint32_t r; asm("mul.rn.bf16x2 %0, %1, %2;" : "=r"(r) : "r"(a), "r"(b)); return r; }
__device__ __forceinline__ uint32_t hadd2(uint32_t a, uint32_t b) { uint32_t r; asm("add.rn.bf16x2 %0, %1, %2;" : "=r"(r) : "r"(a), "r"(b)); return r; }
__device__ __forceinline__ float sigmoidf_(float v) { return rcp(1.0f + ex2(v * -1.4426950408889634f)); }

__device__ __forceinline__ void hedgehog(const float (&p)[16], uint32_t (&phi)[16]) {
  float mx0 = p[0], mn0 = p[0], mx1 = p[2], mn1 = p[2];
#pragma unroll
  for (int j = 0; j < 4; j++) {
    mx0 = fmaxf(mx0, fmaxf(p[4 * j], p[4 * j + 1])); mn0 = fminf(mn0, fminf(p[4 * j], p[4 * j + 1]));
    mx1 = fmaxf(mx1, fmaxf(p[4 * j + 2], p[4 * j + 3])); mn1 = fminf(mn1, fminf(p[4 * j + 2], p[4 * j + 3]));
  }
#pragma unroll
  for (int o = 1; o <= 2; o <<= 1) {
    mx0 = fmaxf(mx0, __shfl_xor_sync(0xffffffffu, mx0, o)); mn0 = fminf(mn0, __shfl_xor_sync(0xffffffffu, mn0, o));
    mx1 = fmaxf(mx1, __shfl_xor_sync(0xffffffffu, mx1, o)); mn1 = fminf(mn1, __shfl_xor_sync(0xffffffffu, mn1, o));
  }
  float ep[16], en[16];
  float sp0 = 0.f, sn0 = 0.f, sp1 = 0.f, sn1 = 0.f;
#pragma unroll
  for (int j = 0; j < 4; j++) {
#pragma unroll
    for (int c = 0; c < 2; c++) {
      ep[4 * j + c] = ex2(p[4 * j + c] - mx0); en[4 * j + c] = ex2(mn0 - p[4 * j + c]);
      ep[4 * j + 2 + c] = ex2(p[4 * j + 2 + c] - mx1); en[4 * j + 2 + c] = ex2(mn1 - p[4 * j + 2 + c]);
      sp0 += ep[4 * j + c]; sn0 += en[4 * j + c]; sp1 += ep[4 * j + 2 + c]; sn1 += en[4 * j + 2 + c];
    }
  }
#pragma unroll
  for (int o = 1; o <= 2; o <<= 1) {
    sp0 += __shfl_xor_sync(0xffffffffu, sp0, o); sn0 += __shfl_xor_sync(0xffffffffu, sn0, o);
    sp1 += __shfl_xor_sync(0xffffffffu, sp1, o); sn1 += __shfl_xor_sync(0xffffffffu, sn1, o);
  }
  sp0 = rcp(sp0); sn0 = rcp(sn0); sp1 = rcp(sp1); sn1 = rcp(sn1);
#pragma unroll
  for (int j = 0; j < 4; j++) {
    phi[2 * j] = pack_bf16(ep[4 * j] * sp0, ep[4 * j + 1] * sp0);
    phi[2 * j + 1] = pack_bf16(ep[4 * j + 2] * sp1, ep[4 * j + 3] * sp1);
    phi[8 + 2 * j] = pack_bf16(en[4 * j + 1] * sn0, en[4 * j] * sn0);
    phi[8 + 2 * j + 1] = pack_bf16(en[4 * j + 3] * sn1, en[4 * j + 2] * sn1);
  }
}

__device__ __noinline__ void hedgehog_slow(float* buf, int n) {
#pragma unroll 1
  for (int u = 0; u < n; u++) {
    float p[16]; uint32_t phi[16];
#pragma unroll
    for (int i = 0; i < 16; i++) p[i] = buf[u * 16 + i];
    hedgehog(p, phi);
#pragma unroll
    for (int i = 0; i < 16; i++) buf[u * 16 + i] = __uint_as_float(phi[i]);
  }
}

__device__ __forceinline__ void store_phi_k(const uint32_t (&phi)[16], uint32_t a) {
#pragma unroll
  for (int jj = 0; jj < 4; jj++) stsm4(a ^ (jj << 5), phi[4 * jj], phi[4 * jj + 1], phi[4 * jj + 2], phi[4 * jj + 3]);
}
__device__ __forceinline__ void hand_over_smem(uint32_t bar, bool ok) {
  fence_async_smem();
  __syncwarp();
  if (elect_one() & ok) mbar_arrive(bar);
}
__device__ __noinline__ void redo_phi_k(float* buf, unsigned done, uint32_t pa, uint32_t bar) {
  hedgehog_slow(buf, 4);
#pragma unroll 1
  for (int u = 0; u < 4; u++) {
    if ((done >> u) & 1) continue;
    uint32_t phi[16];
#pragma unroll
    for (int i = 0; i < 16; i++) phi[i] = __float_as_uint(buf[u * 16 + i]);
    store_phi_k(phi, pa + (~u & 1) * 32768 + (u >> 1) * 4096);
    if (u >= 2) hand_over_smem(bar + (u - 2) * 8, true);
  }
}

__device__ __forceinline__ uint32_t dup_lo(uint32_t v) { uint32_t r; asm("{\n.reg .b16 l, h;\nmov.b32 {l, h}, %1;\nmov.b32 %0, {l, l};\n}" : "=r"(r) : "r"(v)); return r; }
__device__ __forceinline__ uint32_t dup_hi(uint32_t v) { uint32_t r; asm("{\n.reg .b16 l, h;\nmov.b32 {l, h}, %1;\nmov.b32 %0, {h, h};\n}" : "=r"(r) : "r"(v)); return r; }
struct HState { uint32_t a[16]; float s[5]; };
__device__ __forceinline__ void hedgehog_fast1(const float (&p)[16], HState& a) {
  float sm[8], m[8], r[8];
#pragma unroll
  for (int i = 0; i < 8; i++) {
    const float t0 = ex2(p[2 * i]), t1 = ex2(p[2 * i + 1]);
    a.a[i] = pack_bf16(t0, t1); sm[i] = t0 + t1; m[i] = t0 * t1;
  }
  float mq[4];
#pragma unroll
  for (int i = 0; i < 4; i++) {
    mq[i] = m[2 * i] * m[2 * i + 1];
    const float R = rcp(mq[i]);
    r[2 * i] = R * m[2 * i + 1]; r[2 * i + 1] = R * m[2 * i];
  }
  a.s[4] = (mq[0] + mq[1]) + (mq[2] + mq[3]);
#pragma unroll
  for (int i = 0; i < 4; i++) {
    const uint32_t rr = pack_bf16(r[2 * i], r[2 * i + 1]);
    a.a[8 + 2 * i] = hmul2(a.a[2 * i], dup_lo(rr)); a.a[9 + 2 * i] = hmul2(a.a[2 * i + 1], dup_hi(rr));
  }
#pragma unroll
  for (int c = 0; c < 2; c++) {
    a.s[2 * c] = (sm[c] + sm[2 + c]) + (sm[4 + c] + sm[6 + c]);
    a.s[2 * c + 1] = fmaf(r[6 + c], sm[6 + c], fmaf(r[4 + c], sm[4 + c], fmaf(r[2 + c], sm[2 + c], r[c] * sm[c])));
  }
}
template <bool NORM>
__device__ __forceinline__ bool hedgehog_fast2(const HState& a, uint32_t (&phi)[16], float& s0, float& s1) {
  float s[4] = {a.s[0], a.s[1], a.s[2], a.s[3]};
#pragma unroll
  for (int o = 1; o <= 2; o <<= 1)
#pragma unroll
    for (int i = 0; i < 4; i++) s[i] += __shfl_xor_sync(0xffffffffu, s[i], o);
  const bool ok = ((s[0] + s[1]) + (s[2] + s[3]) <= 7.2e16f) & (a.s[4] <= 1.3e36f);
  if (NORM) {
    const float R0 = rcp(s[0] * s[1]), R1 = rcp(s[2] * s[3]);
    const uint32_t n0 = pack_bf16(R0 * s[1], R0 * s[0]), n1 = pack_bf16(R1 * s[3], R1 * s[2]);
#pragma unroll
    for (int i = 0; i < 8; i++) { phi[i] = hmul2(a.a[i], dup_lo((i & 1) ? n1 : n0)); phi[8 + i] = hmul2(a.a[8 + i], dup_hi((i & 1) ? n1 : n0)); }
  } else {
    const uint32_t n = pack_bf16(s[0] * rcp(s[1]), s[2] * rcp(s[3]));
    s0 = s[0]; s1 = s[2];
#pragma unroll
    for (int i = 0; i < 8; i++) { phi[i] = a.a[i]; phi[8 + i] = hmul2(a.a[8 + i], (i & 1) ? dup_hi(n) : dup_lo(n)); }
  }
  return ok;
}
template <bool NORM>
__device__ __forceinline__ bool hedgehog_fast(const float (&p)[16], uint32_t (&phi)[16], float& s0, float& s1) {
  HState a;
  hedgehog_fast1(p, a);
  return hedgehog_fast2<NORM>(a, phi, s0, s1);
}

template <int OFF>
__device__ __forceinline__ void pack_frags(const float (&acc)[96], uint32_t (&a)[16]) {
#pragma unroll
  for (int i = 0; i < 16; i++) a[i] = pack_bf16(acc[OFF + 2 * i], acc[OFF + 2 * i + 1]);
#pragma unroll
  for (int i = 0; i < 16; i++) asm volatile("" : "+r"(a[i]) :: "memory");
}
__device__ __forceinline__ void issue_feat(const uint32_t (&a)[16], float (&p0)[16], float (&p1)[16], uint32_t wphi) {
  wgmma_fence();
#pragma unroll
  for (int kk = 0; kk < 2; kk++) {
    wgmma_rs_n32<1, H64>(p0, a[4 * kk], a[4 * kk + 1], a[4 * kk + 2], a[4 * kk + 3], dlo(wphi + kk * 1024, 16), kk);
    wgmma_rs_n32<1, H64>(p1, a[8 + 4 * kk], a[8 + 4 * kk + 1], a[8 + 4 * kk + 2], a[8 + 4 * kk + 3], dlo(wphi + 2048 + kk * 1024, 16), kk);
  }
  wgmma_commit();
}
__device__ __forceinline__ void keep_alive(const uint32_t (&a)[16]) {
#pragma unroll
  for (int i = 0; i < 16; i++) asm volatile("" :: "r"(a[i]) : "memory");
}

__device__ __forceinline__ void fma8(float (&a)[8], float xv, const uint4& w) {
  a[0] = fmaf(xv, bf_lo(w.x), a[0]); a[1] = fmaf(xv, bf_hi(w.x), a[1]);
  a[2] = fmaf(xv, bf_lo(w.y), a[2]); a[3] = fmaf(xv, bf_hi(w.y), a[3]);
  a[4] = fmaf(xv, bf_lo(w.z), a[4]); a[5] = fmaf(xv, bf_hi(w.z), a[5]);
  a[6] = fmaf(xv, bf_lo(w.w), a[6]); a[7] = fmaf(xv, bf_hi(w.w), a[7]);
}

template <int J0, int J1>
__device__ __forceinline__ void stage_out(const float (&acc)[64], uint32_t xa) {
#pragma unroll
  for (int jj = J0; jj < J1; jj++)
    stsm4((xa ^ ((jj & 3) << 5)) + (jj >> 2) * 16384, pack_bf16(acc[8 * jj], acc[8 * jj + 1]), pack_bf16(acc[8 * jj + 2], acc[8 * jj + 3]),
          pack_bf16(acc[8 * jj + 4], acc[8 * jj + 5]), pack_bf16(acc[8 * jj + 6], acc[8 * jj + 7]));
}
__device__ __forceinline__ float lds_bf16(uint32_t addr) {
  unsigned short v; asm volatile("ld.shared.u16 %0, [%1];" : "=h"(v) : "r"(addr) : "memory"); return __uint_as_float((uint32_t)v << 16);
}
__device__ __noinline__ void redo_rows(const __nv_bfloat16* x, const __nv_bfloat16* wo, uint32_t sb, int b, int wq, uint32_t xa) {
  const int lane = threadIdx.x & 31, wi = (threadIdx.x >> 5) & 3, blk = (b >> 3) * 2 + wq, row0 = blk * 64 + wi * 16;
  const __nv_bfloat16 *pieces = g_o + (size_t)blk * 16 * 4096, *wo_cols = wo + (b & 7) * 128, *xrows = x + (size_t)row0 * D_ + (b & 7) * 128;
  const unsigned* done = g_z.done + (b & ~15);
  const uint32_t gate = sb + SM_GATE + (row0 & 255) * 2, upd = sb + SM_UPD;
  const int routed = (int)lds_u32(sb + SM_INFO + 4) - row0;
  int it = 0;
  while (!__all_sync(0xffffffffu, ld_acquire(done + (lane & 15)) != 0)) { if (++it > (1 << 20)) __trap(); }
  float acc[64];
  const int g = lane >> 2, q = lane & 3, r0 = wi * 16 + g;
#pragma unroll
  for (int i = 0; i < 32; i++) {
    const int r = g + (i & 1) * 8, c = (i >> 1) * 8 + q * 2;
    const uint32_t v = *reinterpret_cast<const uint32_t*>(xrows + (size_t)r * D_ + c);
    const float og = round_bf16(1.0f - lds_bf16(gate + r * 2));
    acc[2 * i] = og * bf_lo(v); acc[2 * i + 1] = og * bf_hi(v);
    if (r == routed) {
      const uint32_t u = lds_u32(upd + (c >> 6) * 2048 + (c & 63) * 2);
      acc[2 * i] += bf_lo(u); acc[2 * i + 1] += bf_hi(u);
    }
  }
#pragma unroll 1
  for (int ks = 0; ks < 64; ks++) {
    const unsigned* pc = reinterpret_cast<const unsigned*>(pieces + (ks >> 2) * 4096) + r0 * 32 + q;
    const int c0 = ((2 * (ks & 3)) ^ (r0 & 7)) * 4, c1 = ((2 * (ks & 3) + 1) ^ (r0 & 7)) * 4;
    const uint32_t a0 = ld_relaxed(pc + c0), a1 = ld_relaxed(pc + 256 + c0), a2 = ld_relaxed(pc + c1), a3 = ld_relaxed(pc + 256 + c1);
    const unsigned short* wp = reinterpret_cast<const unsigned short*>(wo_cols) + (size_t)(ks * 16 + 2 * q) * D_ + g;
#pragma unroll
    for (int nb = 0; nb < 16; nb++) {
      const uint32_t b0 = wp[nb * 8] | ((uint32_t)wp[nb * 8 + D_] << 16), b1 = wp[nb * 8 + 8 * D_] | ((uint32_t)wp[nb * 8 + 9 * D_] << 16);
      mma16816(acc[4 * nb], acc[4 * nb + 1], acc[4 * nb + 2], acc[4 * nb + 3], a0, a1, a2, a3, b0, b1);
    }
  }
  __syncwarp();
  stage_out<0, 8>(acc, xa);
}

__global__ void __cluster_dims__(2, 1, 1) __launch_bounds__(512, 1)
fused_kernel(const __grid_constant__ Maps maps, const __nv_bfloat16* __restrict__ x,
             const __nv_bfloat16* __restrict__ wo, const __nv_bfloat16* __restrict__ w_r, const __nv_bfloat16* __restrict__ gate_w, int by_smid) {
  extern __shared__ __align__(1024) uint8_t smem_raw[];
  if (threadIdx.x == 0) { prefetch_map(&maps.w); prefetch_map(&maps.x); }
  const int tid = threadIdx.x, warp = __shfl_sync(0xffffffffu, tid >> 5, 0), lane = tid & 31;
  const int rank = blockIdx.x & 1;
  unsigned smid; asm volatile("mov.u32 %0, %%smid;" : "=r"(smid));
  const unsigned cl = !by_smid ? blockIdx.x >> 1 : smid < 124 ? (smid >> 1) + 4 : (smid >> 1) - 62;
  const unsigned hi = (cl - 36) * 37 >> 8, lo7 = cl - 36 - hi * 7;
  const bool r8 = cl < 36;
  const unsigned c4 = cl - 4, col = cl < 4 ? 15 : r8 ? c4 & 7 : 8 + lo7, pos = cl < 4 ? cl : r8 ? c4 >> 3 : hi;
  const unsigned cm = (unsigned)(COLMAP >> (4 * col)) & 15;
  const int b = ((cm >> 3) * 4 + pos) * 16 + (cm & 7) * 2 + rank;
  const unsigned cta = cl * 2 + rank;
  const int e = EXPT == 12 ? 200 : cta;
  const int tg = b >> 4, hp = b & 15;
  const int half = hp >> 3, ct = hp & 7;
  constexpr uint32_t SB0 = 1024;
  const uint32_t sb = SB0 + ((uint32_t)rank << 24);
  auto BAR = [&](int i) { return sb + SM_BAR + 8 * i; };
  auto load_stage = [&](int kt, int s, bool mc) {
    const uint32_t a = sb + SM_RA + s * A_BYTES, full = BAR(B_FULL + s);
    mbar_expect_tx(full, STAGE_BYTES);
    tma_load_3d(sb + SM_RB + s * B_BYTES, &maps.w, hp * 64, kt * 32, 0, full);
    if (mc) tma_load_2d_mc(a + rank * 8192, &maps.x, kt * 32, tg * 256 + rank * 128, full);
    else { tma_load_2d(a, &maps.x, kt * 32, tg * 256, full); tma_load_2d(a + 8192, &maps.x, kt * 32, tg * 256 + 128, full); }
  };
  auto slice_of = [&](int i) { const int t = i - 2 * ((unsigned)(i - 2) < (unsigned)(ct & 6)); return ((i >> 1) ? t : t ^ ct) ^ (half * 8); };
  auto load_b2 = [&](int i) {
    const int j = slice_of(i), sl = i + 4 - (i >= 3) * NB2 - (i >= 10) * NB2;
    mbar_expect_tx(BAR(B_FB2 + i), 16384);
    tma_load_3d(sb + SM_RB + sl * 16384, &maps.wo, 0, j * 64, ct * 2, BAR(B_FB2 + i));
  };
  auto load_xt = [&](int w) {
    mbar_expect_tx(BAR(B_XT + w), 16384);
    tma_load_2d(sb + SM_XT + w * 8192, &maps.xt, ct * 128, tg * 256 + half * 128 + w * 64, BAR(B_XT + w));
    tma_load_2d(sb + SM_XT + w * 8192 + 16384, &maps.xt, ct * 128 + 64, tg * 256 + half * 128 + w * 64, BAR(B_XT + w));
  };
  auto o_piece = [&](int hf, int mb, int j) { return g_o + (size_t)((((tg * 2 + hf) * 2 + mb) * 16 + j) * 4096); };

  if (cta >= NCTA) {
    if (warp == 0 && cta == NCTA) {
      if (smem_u32(smem_raw) != sb) __trap();
      const unsigned tag = (ld_relaxed(&g_bcast[0].y) + 1) & 0xfffu;
#pragma unroll 1
      for (int round = 0; round < 2; round++) {
        bool all;
        int it = 0;
        do {
          uint4 k;
          asm volatile("ld.relaxed.gpu.global.v4.u32 {%0, %1, %2, %3}, [%4];" : "=r"(k.x), "=r"(k.y), "=r"(k.z), "=r"(k.w) : "l"(g_key + round * NCTA + lane * 4) : "memory");
          all = __all_sync(0xffffffffu, (((k.x ^ tag) | (k.y ^ tag) | (k.z ^ tag) | (k.w ^ tag)) & 0xfffu) == 0);
          auto full = [&](unsigned m, int c) { return (m & 0xffff0000u) | ((127u - (lane * 4 + c)) << 4) | ((m >> 12) & 15u); };
          const unsigned val = __reduce_max_sync(0xffffffffu, max(max(full(k.x, 0), full(k.y, 1)), max(full(k.z, 2), full(k.w, 3))));
          asm volatile("{\n.reg .pred p;\nsetp.ne.u32 p, %3, 0;\n@p st.relaxed.gpu.global.v2.u32 [%0], {%1, %2};\n}"
                       :: "l"(g_bcast + round * 128 + (lane & 7) * 16), "r"(val), "r"(tag), "r"((uint32_t)(all && lane < 8)) : "memory");
          if (++it > (1 << 20)) __trap();
        } while (!all);
      }
    } else if (warp == 0) {
      __nanosleep(3000);
    }
    return;
  }
  auto load_xr = [&](int xc) {
    mbar_expect_tx(BAR(B_XR + xc), xc ? 8192 : 12288);
    tma_load_2d(sb + SM_XR + xc * 8192, &maps.xr, xc * 256, b * 16, BAR(B_XR + xc));
    tma_load_2d(sb + SM_XR + xc * 8192 + 4096, &maps.xr, xc * 256 + 128, b * 16, BAR(B_XR + xc));
    if (xc == 0) { bulk_load(sb + SM_XR + 32768, w_r, 2048, BAR(B_XR)); bulk_load(sb + SM_XR + 34816, gate_w, 2048, BAR(B_XR)); }
  };
  if (warp == 8) {
    if (elect_one()) {
      mbar_init(BAR(0), 1);
      TSTAMP(40);
      load_stage(0, 0, false);
      TSTAMP(41);
    }
  } else if (elect_one()) {
    const int i = 3 + warp - (warp > 8);
    mbar_init(BAR(i), i < B_EMPTY ? 1 : 4);
    if (warp >= 14) mbar_init(BAR(warp - 13), 1);
    if (warp == 13) mbar_init(BAR(B_INIT), 3);
  }
  asm volatile("fence.mbarrier_init.release.cluster;" ::: "memory");
  __syncwarp();
  asm volatile("barrier.cluster.arrive.relaxed.aligned;" ::: "memory");
  auto cluster_wait = [&]() { asm volatile("barrier.cluster.wait.aligned;" ::: "memory"); };

  if (warp >= 12) {
    asm volatile("setmaxnreg.dec.sync.aligned.u32 40;");
    const int aw = warp - 12;
    cluster_wait();
    const unsigned old_gate = ld_relaxed(g_gate + b * 16 + aw * 4);
    const uint32_t zero = smem_u32(smem_raw) ^ sb;
    {
      float r[4], l[4];
#pragma unroll
      for (int t = 0; t < 4; t++) { r[t] = 0.f; l[t] = 0.f; }
      uint32_t xa = sb + SM_XR + aw * 1024 + lane * 8, wa = sb + SM_XR + 32768 + lane * 8;
#pragma unroll 1
      for (int i = 0; i < 8; i++) {
        if (!(i & 1)) mbar_wait(BAR(B_XR) + i * 4, 0);
        if (tid == 384 && i == 6) TSTAMP(30);
        uint2 wr = lds64(wa);
        const uint2 gw = lds64(wa + 2048);
        uint2 xv[4];
#pragma unroll
        for (int t = 0; t < 4; t++) xv[t] = lds64(xa + t * 256);
        xa += 4096; wa += 256;
        wr.x |= (xv[1].x | xv[2].x | xv[3].x) & zero;
        const float w0 = bf_lo(wr.x), w1 = bf_hi(wr.x), w2 = bf_lo(wr.y), w3 = bf_hi(wr.y);
#pragma unroll
        for (int t = 0; t < 4; t++) {
          const uint32_t p0 = hmul2(xv[t].x, gw.x), p1 = hmul2(xv[t].y, gw.y);
          r[t] = fmaf(bf_hi(xv[t].y), w3, fmaf(bf_lo(xv[t].y), w2, fmaf(bf_hi(xv[t].x), w1, fmaf(bf_lo(xv[t].x), w0, r[t]))));
          l[t] += (bf_lo(p0) + bf_hi(p0)) + (bf_lo(p1) + bf_hi(p1));
        }
      }
      float u[4];
#pragma unroll
      for (int t = 0; t < 4; t++) u[t] = ((lane & 4) ? l[t] : r[t]) + __shfl_xor_sync(0xffffffffu, (lane & 4) ? r[t] : l[t], 4);
      const float v0 = ((lane & 1) ? u[1] : u[0]) + __shfl_xor_sync(0xffffffffu, (lane & 1) ? u[0] : u[1], 1);
      const float v1 = ((lane & 1) ? u[3] : u[2]) + __shfl_xor_sync(0xffffffffu, (lane & 1) ? u[2] : u[3], 1);
      float v = ((lane & 2) ? v1 : v0) + __shfl_xor_sync(0xffffffffu, (lane & 2) ? v0 : v1, 2);
      v += __shfl_xor_sync(0xffffffffu, v, 8);
      v += __shfl_xor_sync(0xffffffffu, v, 16);
      v = round_bf16(v);
      unsigned k = __float_as_uint(v) >> 16;
      k = (k & 0x8000u) ? (~k & 0xffffu) : (k | 0x8000u);
      k = __reduce_max_sync(0xffffffffu, lane < 4 ? (k << 4) | (15u - (aw * 4 + lane)) : 0u);
      if (lane == 0) sts_u32(sb + SM_KEYS + aw * 4, k);
      if ((lane >> 2) == 1) st_relaxed(g_gate + b * 16 + aw * 4 + (lane & 3), __float_as_uint(round_bf16(sigmoidf_(v))) | ((old_gate + 1) & 0xfffu));
      mbar_wait(BAR(B_INIT), 0);
    }
    if (tid == 384) { TSTAMP(31); GSTAMP(60); }
    fence_async_smem();
    __syncwarp();
    if (elect_one()) mbar_arrive(BAR(B_XRD));
    mbar_wait_bounded(BAR(B_XSEL), 0);
    if (tid == 384) TSTAMP(36);
    float ag[8];
#pragma unroll
    for (int i = 0; i < 8; i++) ag[i] = 0.f;
    if (e < NMOE) {
      const uint32_t lw = sb + SM_MOE + aw * 2048 + (lane >> 3) * 512 + (lane & 7) * 16;
      uint32_t lx = sb + SM_XSEL + aw * 32 + (lane >> 3) * 8, fb = BAR(B_MOE), wa = lw;
      bool got = false;
#pragma unroll 1
      for (int m = 0; m < 12; m++) {
#pragma unroll
        for (int c = 0; c < 2; c++) {
          if (!got) mbar_wait(fb + c * 8, (m >> 1) & 1);
          uint4 w0, w1, w2, w3;
          lds128x4(wa + c * 8192, w0, w1, w2, w3);
          uint2 xv = lds64(lx + c * 128);
          got = mbar_test(c ? fb ^ 16 : fb + 8, ((m + c) >> 1) & 1);
          const uint32_t dep = ((w0.x | w1.x | w2.x) | w3.x) & zero;
          xv.x |= dep;
          if (elect_one()) mbar_arrive(fb + dep + (B_MOEE - B_MOE + c) * 8);
          fma8(ag, bf_lo(xv.x), w0); fma8(ag, bf_hi(xv.x), w1); fma8(ag, bf_lo(xv.y), w2); fma8(ag, bf_hi(xv.y), w3);
        }
        fb ^= 16; wa = 2 * lw + 16384 - wa; lx += 256;
        if (m == 7) {
          int ln;
          asm volatile("mov.u32 %0, %%laneid;" : "=r"(ln));
#pragma unroll
          for (int i = 0; i < 4; i++) ag[i] = ((ln & 16) ? ag[4 + i] : ag[i]) + __shfl_xor_sync(0xffffffffu, (ln & 16) ? ag[i] : ag[4 + i], 16);
          const float v0 = ((ln & 8) ? ag[2] : ag[0]) + __shfl_xor_sync(0xffffffffu, (ln & 8) ? ag[0] : ag[2], 8);
          const float v1 = ((ln & 8) ? ag[3] : ag[1]) + __shfl_xor_sync(0xffffffffu, (ln & 8) ? ag[1] : ag[3], 8);
          const uint32_t own = (uint32_t)(ln & 4) << 22;
          asm volatile("st.async.shared::cluster.mbarrier::complete_tx::bytes.v2.f32 [%0], {%1, %2}, [%3];"
                       :: "r"(own + SB0 + SM_RED + rank * 512 + aw * 128 + (ln & 3) * 32 + (ln >> 3) * 8), "f"(v0), "f"(v1), "r"(own + SB0 + SM_BAR + 8 * B_H) : "memory");
          mbar_wait_bounded(BAR(B_H), 0);
          const uint32_t ra = sb + SM_RED + ln * 4;
          float gv = round_bf16((lds_f32(ra) + lds_f32(ra + 128)) + (lds_f32(ra + 256) + lds_f32(ra + 384)));
          const float uv = round_bf16((lds_f32(ra + 512) + lds_f32(ra + 640)) + (lds_f32(ra + 768) + lds_f32(ra + 896)));
          gv = round_bf16(gv * sigmoidf_(gv));
          lx = sb + SM_XSEL + aw * 32;
          asm volatile("st.shared.b16 [%0], %1;" :: "r"(lx + (ln >> 2) * 128 + (ln & 3) * 2), "h"(__bfloat16_as_ushort(__float2bfloat16_rn(gv * uv))) : "memory");
          __syncwarp();
#pragma unroll
          for (int i = 0; i < 8; i++) ag[i] = 0.f;
          if (tid == 384) TSTAMP(33);
        }
      }
      mbar_wait(BAR(B_RDY), 0);
#pragma unroll
      for (int j = 0; j < 3; j++)
        asm volatile("red.global.add.v4.f32 [%0], {%1, %2, %3, %4};" :: "l"(g_z.y + (e & (NY - 1)) * 2 * D_ + (j * 128 + aw * 32 + lane) * 4),
                     "f"(ag[3 * j]), "f"(ag[3 * j + 1]), "f"(j < 2 ? ag[3 * j + 2] : 0.f), "f"(1.0f) : "memory");
    }
    fence_async_smem();
    if (tid == 384) TSTAMP(34);
    bar_sync(4, 128);
    if (aw == 3) {
      const uint4 info = lds128(sb + SM_INFO);
      int it = 0;
      if ((info.y >> 7) == tg * 2 + half && EXPT != 12) {
        mbar_wait(BAR(B_RDY), 0);
        const float rs = round_bf16(sigmoidf_(__uint_as_float(info.z)));
        float y[9];
        do {
          __nanosleep(100);
#pragma unroll
          for (int i = 0; i < 9; i++) y[i] = 0.f;
#pragma unroll 1
          for (int c = lane >> 4; c < NY; c += 2) {
            const float* yp = g_z.y + c * 2 * D_ + (ct * 16 + (lane & 15)) * 4;
            const float4 a0 = ldg_l2(yp), a1 = ldg_l2(yp + 512), a2 = ldg_l2(yp + 1024);
            y[0] += a0.x; y[1] += a0.y; y[2] += a0.z; y[3] += a1.x; y[4] += a1.y; y[5] += a1.z; y[6] += a2.x; y[7] += a2.y;
            y[8] += a0.w + a1.w + a2.w;
          }
#pragma unroll
          for (int i = 0; i < 9; i++) y[i] += __shfl_xor_sync(0xffffffffu, y[i], 16);
          if (++it > (1 << 20)) __trap();
        } while (!__all_sync(0xffffffffu, y[8] == 3.f * NMOE));
        const int hw = lane >> 4;
        const uint2 xv = __ldg(reinterpret_cast<const uint2*>(x + (size_t)info.y * D_ + ct * 128) + (lane & 15) * 2 + hw);
        const float og = round_bf16(1.0f - lds_bf16(sb + SM_GATE + (info.y & 255) * 2));
        const uint32_t rs2 = pack_bf16(rs, rs);
        const uint32_t t0 = hadd2(xv.x, hmul2(pack_bf16(hw ? y[4] : y[0], hw ? y[5] : y[1]), rs2));
        const uint32_t t1 = hadd2(xv.y, hmul2(pack_bf16(hw ? y[6] : y[2], hw ? y[7] : y[3]), rs2));
        mbar_wait(BAR(B_OP), 0); mbar_wait(BAR(B_OP + 2), 0);
        sts64(sb + SM_UPD + (lane & 8) * 256 + (lane & 7) * 16 + hw * 8,
              __uint_as_float(pack_bf16(og * (bf_lo(t0) - bf_lo(xv.x)), og * (bf_hi(t0) - bf_hi(xv.x)))),
              __uint_as_float(pack_bf16(og * (bf_lo(t1) - bf_lo(xv.y)), og * (bf_hi(t1) - bf_hi(xv.y)))));
        fence_async_smem();
        __syncwarp();
        if (elect_one()) { mbar_arrive(BAR(B_Y)); TSTAMP(39); }
      }
    } else {
      if (aw == 0) mbar_wait(BAR(B_PHI), 0);
      if (elect_one()) load_b2(aw);
      if (aw) {
#pragma unroll 1
        for (int i = 0; i < 16; i++) {
          mbar_wait_bounded(BAR(B_FB2 + i), 0);
          if (i == 0) mbar_wait(BAR(B_OP + half * 2 + aw - 1), 0);
          if (elect_one()) mbar_expect_tx(BAR(B_F2 + (aw - 1) * 16 + i), i ? 8192 : 0);
        }
      }
    }
  } else if (warp >= 8) {
    asm volatile("setmaxnreg.dec.sync.aligned.u32 24;");
    cluster_wait();
    if (tid == 256) TSTAMP(58);
    if (warp != 8) {
      if (elect_one()) {
#pragma unroll 1
        for (int i = B_ST + warp - 9; i < NBAR; i += 3) mbar_init(BAR(i), bar_count(i) + (LEAD2 && i == B_F2 + 32 - LEAD2));
        asm volatile("fence.mbarrier_init.release.cluster;" ::: "memory");
      }
#pragma unroll
      for (int i = 0; i < (ZB + 1535) / 1536; i++) sts128(sb + SM_KVB + (i * 96 + tid - 288) * 16, make_uint4(0, 0, 0, 0));
      if (warp < 11) sts128(sb + SM_ONES + (tid - 288) * 16, make_uint4(0x3f803f80u, 0x3f803f80u, 0x3f803f80u, 0x3f803f80u));
      if (tid == 352) asm volatile("st.shared::cluster.u32 [%0], %1;" :: "r"((sb ^ (1u << 24)) + SM_KEYS + 16), "r"(cl) : "memory");
      hand_over_smem(BAR(B_INIT), true);
      if (tid == 288) TSTAMP(57);
    }
    if (warp == 8) {
      int s = 1, ph = 1;
#pragma unroll 1
      for (int kt = 1; kt < KT; kt++) {
        mbar_wait_bounded(BAR(B_EMPTY + s), ph);
        if (elect_one()) {
          load_stage(kt, s, true);
          const unsigned xc = kt - XR_AFTER;
          if (xc < 4) load_xr(xc);
          const int pg = kt - STAGES - PF_START;
          if (pg >= (e < NMOE ? 0 : 24) && pg < 26) {
            const CUtensorMap* tm = &maps.tg + (pg < 16 ? (b & 1) : pg < 24 ? 2 : 3);
            const int c0 = pg < 16 ? (e >> 1) * 64 : 0, c1 = (pg < 16 ? pg : pg < 24 ? e * 8 + pg - 16 : b * 2 + pg - 24) * 64;
            asm volatile("cp.async.bulk.prefetch.tensor.2d.L2.global [%0, {%1, %2}];" :: "l"(tm), "r"(c0), "r"(c1) : "memory");
          }
        }
        if (++s == STAGES) { s = 0; ph ^= 1; }
      }
      mbar_wait(BAR(B_EMPTY + 1), 1);
#pragma unroll 1
      for (int i = 3; i < NB2; i++)
        if (elect_one()) load_b2(i);
    } else if (warp == 9) {
      const unsigned tag = (ld_relaxed(g_key + b) + 1) & 0xfffu;
      if (elect_one()) {
        mbar_expect_tx(BAR(B_WPHI), 4096);
        tma_load_2d(sb + SM_WPHI, &maps.wphi, 0, hp * 64, BAR(B_WPHI));
      }
      mbar_wait(BAR(B_WPHI), 0);
#pragma unroll 1
      for (uint32_t ad = sb + SM_WPHI + lane * 16; ad < sb + SM_WPHI + 4096; ad += 512) {
        constexpr float L = 1.4426950408889634f;
        const uint4 w = lds128(ad);
        sts128(ad, make_uint4(pack_bf16(bf_lo(w.x) * L, bf_hi(w.x) * L), pack_bf16(bf_lo(w.y) * L, bf_hi(w.y) * L),
                              pack_bf16(bf_lo(w.z) * L, bf_hi(w.z) * L), pack_bf16(bf_lo(w.w) * L, bf_hi(w.w) * L)));
      }
      fence_async_smem();
      mbar_wait(BAR(B_XRD), 0);
      {
        const uint4 k = lds128(sb + SM_KEYS);
        if (lane == 0) st_relaxed(g_key + b, (max(max(k.x, k.y), max(k.z, k.w)) << 12) | tag);
      }
      const unsigned best = __shfl_sync(0xffffffffu, wait_tagged<0>(g_bcast + tg * 16, tag), 0);
      const unsigned idx = 2047u - (best & 0x7ffu);
      unsigned u = best >> 16;
      u = (u & 0x8000u) ? (u & 0x7fffu) : (~u & 0xffffu);
      if (elect_one()) {
        sts128(sb + SM_INFO, make_uint4(tag, idx, u << 16, 0));
        mbar_expect_tx(BAR(B_H), 1024);
        mbar_expect_tx(BAR(B_XSEL), 2048);
        bulk_load(sb + SM_XSEL, x + (size_t)idx * D_, 2048, BAR(B_XSEL));
        TSTAMP(32); GSTAMP(61);
        bulk_store(reinterpret_cast<char*>(&g_z) + b * ZB, sb + SM_KVB, ZB);
      }
      bulk_commit(); bulk_wait0();
      fence_gpu();
      __syncwarp();
      if (lane == 0) { st_relaxed(g_key + NCTA + b, tag); TSTAMP(42); }
      int it = 0;
#pragma unroll 1
      for (int c = 0; c < 2; c++) {
        uint4 gv;
        do {
          asm volatile("ld.relaxed.gpu.global.v4.u32 {%0, %1, %2, %3}, [%4];" : "=r"(gv.x), "=r"(gv.y), "=r"(gv.z), "=r"(gv.w)
                       : "l"(g_gate + tg * 256 + c * 128 + lane * 4) : "memory");
          if (++it > (1 << 20)) __trap();
        } while (!__all_sync(0xffffffffu, (((gv.x ^ tag) | (gv.y ^ tag) | (gv.z ^ tag) | (gv.w ^ tag)) & 0xfffu) == 0));
        sts64(sb + SM_GATE + c * 256 + lane * 8, __uint_as_float(__byte_perm(gv.x, gv.y, 0x7632)), __uint_as_float(__byte_perm(gv.z, gv.w, 0x7632)));
      }
      wait_tagged<200>(g_bcast + 128 + tg * 16, tag);
      if (lds_u32(sb + SM_KEYS + 16) != cl) __trap();
      __syncwarp();
      if (elect_one()) { mbar_arrive(BAR(B_RDY)); TSTAMP(43); }
    } else if (e < NMOE) {
      const int w = warp & 1;
      const CUtensorMap* tm = &maps.wg + rank;
      int c0 = (e >> 1) * 64, c1 = 0, c2 = 4 * w;
      uint32_t bar = BAR(B_MOE + w);
      mbar_wait(BAR(B_XRD), 0);
#pragma unroll 1
      for (int m = 0; m < 12; m++) {
        mbar_wait(bar + (B_MOEE - B_MOE) * 8, ((m >> 1) & 1) ^ 1);
        if (elect_one()) {
          mbar_expect_tx(bar, 8192);
          tma_load_3d(sb + SM_MOE + w * 8192 + (m & 1) * 16384, tm, c0, c1, c2, bar);
        }
        bar ^= 16;
        if (m < 7) c2 += 8; else c1 += 8;
        if (m == 7) { tm = &maps.wd; c0 = 0; c1 = e * 32 + w * 4; c2 = 0; }
      }
    }
    const int wi = warp - 8, st = tid - 256;
    bar_sync(5, 128);
    asm volatile("setmaxnreg.inc.sync.aligned.u32 " STR(REG_K) ";");
    {
      auto kv_half = [&](float (&d)[20], int h, int mb) {
#pragma unroll
        for (int i = 0; i < 8; i++)
          wgmma_ss_n40<1, 1, H128, H64>(d, dlo(SB0 + SM_PHIK + 32768, 16) - h * 2048 + (((i & 2) << 2) + (i & 4) + mb * 2 + (i & 1)) * 128,
                                        dlo(SB0 + SM_V, SM_ONES - SM_V) + (h * 16 + (i & 4) * 2 + mb * 4 + (i & 3)) * (64 - (64 << 16)), (mb | i) != 0);
      };
      auto kv_out = [&](float (&d)[20], int h) {
        fence_regs(d);
        float* dst = g_z.kv + (hp * 2 + h) * KVH + st * 2;
        const int q = lane & 3;
        uint32_t w[8];
#pragma unroll
        for (int i = 0; i < 8; i++) w[i] = pack_bf16(d[2 * i], d[2 * i + 1]);
#pragma unroll
        for (int c = 0; c < 4; c++)
          asm volatile("red.global.add.noftz.v2.bf16x2 [%0], {%1, %2};" :: "l"(dst + c * 256), "r"(w[2 * c]), "r"(q == c ? 0x3f80u : w[2 * c + 1]) : "memory");
        asm volatile("red.global.add.noftz.v2.bf16x2 [%0], {%1, %2};" :: "l"(dst + 1024), "r"((q & 2) ? ((q & 1) ? w[7] : w[5]) : ((q & 1) ? w[3] : w[1])),
                     "r"(q == 0 ? 0x3f80u : q == 1 ? pack_bf16(d[16], d[18]) : 0u) : "memory");
      };
#pragma unroll 1
      for (int h = 0; h < 2; h++) {
        float kv[20];
        mbar_wait_bounded(BAR(B_PHI + h), 0);
        if (st == 0) TSTAMP(23 + h);
        wgmma_fence();
        kv_half(kv, h, 0); kv_half(kv, h, 1);
        wgmma_commit();
        wgmma_wait<0>();
        if (st == 0) TSTAMP(21 + h);
        kv_out(kv, h);
        bar_sync(5, 128);
        if (h == 0 && wi < 2 && elect_one()) load_xt(wi);
      }
      if (wi == 3 && elect_one()) mbar_arrive_cluster(BAR(B_PEER) ^ (1u << 24));
      if (st == 0) TSTAMP(13);
      const int f = wi * 16 + (lane & 15), sw = (f >> 1) & 3, chi = lane >> 4;
      uint2 v[10];
      const float* src = g_z.kv + hp * 2 * KVH + st * 2;
      const int q = lane & 3;
      { const unsigned c0 = clock32(); while (clock32() - c0 < KV_DELAY) {} }
      int it = 0;
      unsigned need = 0x3ff;
#pragma unroll
      for (int i = 0; i < 10; i++) v[i] = make_uint2(0, 0);
      do {
        if (++it > (1 << 20)) __trap();
        unsigned bad = 0;
        if (st == 0 && it == 1) TSTAMP(35);
#pragma unroll
        for (int i = 0; i < 10; i++)
          asm volatile("{\n.reg .pred p;\nsetp.ne.u32 p, %3, 0;\n@p ld.relaxed.gpu.global.v2.u32 {%0, %1}, [%2];\n}"
                       : "+r"(v[i].x), "+r"(v[i].y) : "l"(src + i * 256), "r"(need & (1u << i)) : "memory");
#pragma unroll
        for (int i = 0; i < 10; i++) bad |= (v[i].y != 0x4100u) << i;
        need = __reduce_or_sync(0xffffffffu, bad & ((0x21u << q) | (q ? 0u : 0x210u)));
        if (st == 0 && it == 1) TSTAMP(20);
      } while (need);
      uint32_t zz[2];
#pragma unroll
      for (int h = 0; h < 2; h++) {
        const uint2* w = v + h * 5;
        const uint32_t kb = sb + SM_KVB + h * 4096 + f * 64;
        zz[h] = __shfl_sync(0xffffffffu, w[4].y, (lane & 28) + 1);
        stsm4(kb + ((chi ^ sw) << 4), w[0].x, q == 0 ? w[4].x : w[0].y, w[1].x, q == 1 ? w[4].x : w[1].y);
        stsm4(kb + (((2 + chi) ^ sw) << 4), w[2].x, q == 2 ? w[4].x : w[2].y, w[3].x, q == 3 ? w[4].x : w[3].y);
      }
      stsm4(sb + SM_KVB + 8192 + f * 64 + ((chi ^ sw) << 4), zz[0], zz[0] >> 16, zz[1], zz[1] >> 16);
      fence_async_smem();
      __syncwarp();
      if (elect_one()) mbar_arrive(BAR(B_KVB));
    }
    {
      const int pm = wi >> 1;
      if (wi & 1) {
        const int hf = half ^ pm;
        mbar_wait(BAR(B_PEER), 0);
        mbar_wait_bounded(BAR(B_OP + hf * 2), 0);
        const unsigned c0 = clock32();
        while (clock32() - c0 < (unsigned)(pm ? LATE_DELAY + ct * LATE_STEP : 0)) {}
        __syncwarp();
        auto to_partner = [&](int mb) {
          asm volatile("cp.async.bulk.shared::cluster.shared::cta.mbarrier::complete_tx::bytes [%0], [%1], 8192, [%2];"
                       :: "r"((sb ^ (1u << 24)) + SM_RA + mb * 8192), "r"(sb + SM_O + mb * 8192), "r"(BAR(B_F2 + mb * 16 + 1) ^ (1u << 24)) : "memory");
        };
        uint4* hint = g_z.hint + (tg * 2 + hf) * 32 + hp;
#pragma unroll 1
        for (int mb = 0; mb < 2; mb++) {
          if (mb) mbar_wait(BAR(B_OP + hf * 2 + 1), 0);
          if (elect_one()) {
            bulk_store(o_piece(hf, mb, hp), sb + SM_O + pm * 16384 + mb * 8192, 8192);
            if (!pm) bulk_store(hint + mb * 16, sb + SM_ONES, 16);
            if (!pm) to_partner(mb);
          }
          bulk_commit();
          if (pm) {
            bulk_wait0();
            __syncwarp();
            if (lane == 0) st_relaxed(&hint[mb * 16].x, 1);
          }
          if (lane == 0) TSTAMP((pm ? 37 : 15) + mb);
        }
        bulk_wait0();
        __syncwarp();
        if (lane == 0) mbar_arrive(BAR(B_ST + pm));
        if (pm == 0) {
          if (lane < 2) mbar_arrive_cluster((lane << 24) + SB0 + SM_BAR + 8 * (B_GO + NA2));
          mbar_wait(BAR(B5_AFTER), 0);
#pragma unroll 1
          for (int i = NB2; i < 16; i++) {
            mbar_wait(BAR(B_DB + i - NB2), 0);
            if (elect_one()) load_b2(i);
          }
        } else {
          mbar_wait(BAR(B_ST), 0);
          fence_gpu();
          if (lane == 0) st_relaxed(g_z.done + b, 1);
        }
      } else if (pm) {
        const __nv_bfloat16* src = o_piece(half, rank, half * 8);
        uint32_t dst = sb + SM_RA + 16384 + rank * 8192;
        mbar_wait(BAR(B_PEER), 0);
#pragma unroll 1
        for (int i = 2; i < 16; i++) {
          if (i == (ct & 6) + 2) src += 2 * 4096;
          if (i == 8) src -= half * 16 * 4096;
          mbar_wait_bounded(BAR(B_GO + i), 0);
          if (elect_one()) {
            asm volatile("cp.async.bulk.shared::cluster.global.mbarrier::complete_tx::bytes.multicast::cluster [%0], [%1], 8192, [%2], %3;"
                         :: "r"(dst), "l"(src), "r"(BAR(B_F2 + rank * 16 + i)), "h"((uint16_t)3) : "memory");
            if (i == 2) TSTAMP(19);
          }
          src += 4096;
          dst += (i == 5 || i == 10) ? -4 * 16384 : 16384;
        }
      } else {
        const unsigned* flag = &g_z.hint[(tg * 2 + half) * 32 + rank * 16 + slice_of(lane & 15)].x;
        bool seen = lane < 2 || lane > 15;
        mbar_wait(BAR(B_OP + half * 2 + rank), 0);
        int it = 0;
        do {
          if (ld_relaxed(flag) != 0 && !seen) {
            mbar_arrive(BAR(B_GO) + lane * 8);
            seen = true;
          }
          if (++it > (1 << 20)) __trap();
        } while (!__all_sync(0xffffffffu, seen));
      }
    }
  } else {
    asm volatile("setmaxnreg.inc.sync.aligned.u32 224;");
    const int wg = warp >> 2, wi = warp & 3;
    cluster_wait();
    if (tid == 0) TSTAMP(59);
    float acc0[96], acc1[96];
    {
      int s = 0, ph = 0, sprev = 0;
#pragma unroll 1
      for (int kt = 0; kt < KT - STAGES; kt++) {
        mbar_wait(BAR(B_FULL + s), ph);
        if (kt == 0 && tid == 0) TSTAMP(1);
        if (tid == 0 && !(kt & 1)) TSTAMP(44 + kt / 2);
        const uint32_t da = dlo(SB0 + SM_RA, 16) + s * (A_BYTES >> 4) + wg * 512;
        const uint32_t db = dlo(SB0 + SM_RB, 4096) + s * (B_BYTES >> 4);
        wgmma_fence();
#pragma unroll
        for (int k = 0; k < 2; k++) {
          wgmma_ss_n192<0, 1, H64, H128>(acc0, da + k * 2, db + k * 128, (kt | k) != 0);
          wgmma_ss_n192<0, 1, H64, H128>(acc1, da + 256 + k * 2, db + k * 128, (kt | k) != 0);
        }
        wgmma_commit();
        wgmma_wait<1>();
        if (kt > 0 && wi < 2 && elect_one()) mbar_arrive_cluster((wi << 24) + SB0 + SM_BAR + 8 * (B_EMPTY + sprev));
        sprev = s;
        if (++s == STAGES) { s = 0; ph ^= 1; }
      }
#pragma unroll 1
      for (int kt = 0; kt < STAGES; kt++) {
        mbar_wait(BAR(B_FULL + s), ph);
        const uint32_t da = dlo(SB0 + SM_RA, 16) + s * (A_BYTES >> 4) + wg * 512;
        const uint32_t db = dlo(SB0 + SM_RB, 4096) + s * (B_BYTES >> 4);
        wgmma_fence();
        wgmma_ss_n192<0, 1, H64, H128>(acc0, da, db, 1);
        wgmma_ss_n192<0, 1, H64, H128>(acc0, da + 2, db + 128, 1);
        wgmma_commit();
        wgmma_wait<1>();
        if (kt == 0 && wi < 2 && elect_one()) mbar_arrive_cluster((wi << 24) + SB0 + SM_BAR + 8 * (B_EMPTY + 1));
        if (++s == STAGES) { s = 0; ph ^= 1; }
      }
      mbar_wait(BAR(B_RDY), 0);
    }
    const int trow = wg * 128 + wi * 16 + (lane & 15);
    const int chi = lane >> 4;
    uint32_t ak[16], aq[2][16];
    float p[4][16];
    auto catch_one = [&](int i) {
      const int s = (2 + (i >> 1)) % STAGES;
      wgmma_ss_n192<0, 1, H64, H128>(acc1, dlo(SB0 + SM_RA + s * A_BYTES + 4096 + (i & 1) * 32, 16) + wg * 512, dlo(SB0 + SM_RB + s * B_BYTES + (i & 1) * 2048, 4096), 1);
    };
    auto catch_up = [&](int s) { wgmma_fence(); catch_one(2 * s - 4); catch_one(2 * s - 3); wgmma_commit(); };
    auto store_v = [&](const float (&acc)[96], int mb) {
#pragma unroll
      for (int h = 0; h < 2; h++)
#pragma unroll
        for (int jj = 0; jj < 2; jj++) {
          const int o = 64 + h * 16 + jj * 8;
          stsm4(sb + SM_V + h * 16384 + (trow + mb * 64) * 64 + (((2 * jj + chi) ^ ((trow >> 1) & 3)) << 4),
                pack_bf16(acc[o], acc[o + 1]), pack_bf16(acc[o + 2], acc[o + 3]), pack_bf16(acc[o + 4], acc[o + 5]), pack_bf16(acc[o + 6], acc[o + 7]));
        }
    };
    const uint32_t pa = sb + SM_PHIK + (wi >> 1) * 16384 + wg * 8192 + (trow & 31) * 128 + ((chi ^ (trow & 7)) << 4);
    auto store_phi = [&](const uint32_t (&phi)[16], int h, int mb) { store_phi_k(phi, pa + (1 - h) * 32768 + mb * 4096); };
    auto hand_over = [&](int i, bool ok) { hand_over_smem(BAR(B_PHI + i), ok); };
    bool okk[3];
    {
      HState hs;
      uint32_t phi[16];
      float d0, d1;
      catch_up(2);
      wgmma_wait<1>();
      fence_regs(acc0);
      if (tid == 0) TSTAMP(2);
      store_v(acc0, 0);
      pack_frags<32>(acc0, ak);
      issue_feat(ak, p[0], p[1], SB0 + SM_WPHI);
      catch_up(3);
      pack_frags<0>(acc0, aq[0]);
      wgmma_wait<1>();
      fence_regs(p[0]); fence_regs(p[1]); keep_alive(ak);
      wgmma_fence();
#pragma unroll
      for (int i = 4; i < 4 + NFIRST; i++) catch_one(i);
      okk[0] = hedgehog_fast<true>(p[0], phi, d0, d1);
      store_phi(phi, 0, 0);
#pragma unroll
      for (int i = 4 + NFIRST; i < 12; i++) catch_one(i);
      wgmma_commit();
      okk[0] &= hedgehog_fast<true>(p[1], phi, d0, d1);
      store_phi(phi, 1, 0);
      if (tid == 0) TSTAMP(17);
      wgmma_wait<0>();
      fence_regs(acc1);
      if (tid == 0) TSTAMP(27);
      if (wi < 2 && elect_one()) mbar_arrive_cluster((wi << 24) + SB0 + SM_BAR + 8 * (B_EMPTY + 1));
      pack_frags<32>(acc1, ak);
      issue_feat(ak, p[2], p[3], SB0 + SM_WPHI);
      store_v(acc1, 1);
      pack_frags<0>(acc1, aq[1]);
      wgmma_wait<0>();
      fence_regs(p[2]); fence_regs(p[3]); keep_alive(ak);
      asm volatile("setmaxnreg.dec.sync.aligned.u32 " STR(REG_C) ";");
      if (tid == 0) TSTAMP(28);
      HState h2;
      hedgehog_fast1(p[2], hs);
      hedgehog_fast1(p[3], h2);
      okk[1] = __all_sync(0xffffffffu, okk[0] & hedgehog_fast2<true>(hs, phi, d0, d1));
      store_phi(phi, 0, 1);
      hand_over(0, okk[1]);
      h2.s[0] += lds_f32(sb + SM_INFO + 12);
      okk[2] = __all_sync(0xffffffffu, okk[0] & hedgehog_fast2<true>(h2, phi, d0, d1));
      store_phi(phi, 1, 1);
      hand_over(1, okk[2]);
    }
    if (__builtin_expect(!(okk[1] & okk[2]), 0)) {
      __align__(16) float buf[64];
#pragma unroll
      for (int i = 0; i < 64; i++) buf[i] = p[i >> 4][i & 15];
      redo_phi_k(buf, okk[1] * 5 + okk[2] * 10, pa, BAR(B_PHI));
    }
    if (wi == 0 && lane == 0) TSTAMP(wg ? 29 : 3);
    uint32_t pq[4][16];
    float sc[8];
    issue_feat(aq[0], p[0], p[1], SB0 + SM_WPHI);
    issue_feat(aq[1], p[2], p[3], SB0 + SM_WPHI);
    mbar_wait(BAR(Q_AFTER), 0);
    wgmma_wait<0>();
#pragma unroll
    for (int u = 0; u < 4; u++) fence_regs(p[u]);
    keep_alive(aq[0]); keep_alive(aq[1]);
    if (tid == 0) TSTAMP(4);
    {
      bool ok = true;
#pragma unroll
      for (int u = 0; u < 4; u++) ok &= hedgehog_fast<false>(p[u], pq[u], sc[2 * u], sc[2 * u + 1]);
      if (__builtin_expect(!__all_sync(0xffffffffu, ok), 0)) {
        __align__(16) float buf[64];
#pragma unroll
        for (int i = 0; i < 64; i++) buf[i] = p[i >> 4][i & 15];
        hedgehog_slow(buf, 4);
#pragma unroll
        for (int i = 0; i < 64; i++) pq[i >> 4][i & 15] = __float_as_uint(buf[i]);
#pragma unroll
        for (int i = 0; i < 8; i++) sc[i] = 1.0f;
      }
    }
    if (tid == 0) TSTAMP(5);
    float acc[64];
    const int wq = wg ^ half;
    const uint32_t xo = wq * 8192 + wi * 2048 + (lane & 15) * 128 + ((chi ^ (lane & 7)) << 4);
    const uint32_t ga = sb + SM_GATE + (half * 128 + wq * 64 + wi * 16) * 2 + (lane >> 2) * 2;
    mbar_wait(BAR(B_XT + wq), 0);
    float gt[4];
#pragma unroll
    for (int i = 0; i < 4; i++) gt[i] = lds_bf16(sb + SM_GATE + (wg * 128 + (i >> 1) * 64 + wi * 16 + (i & 1) * 8 + (lane >> 2)) * 2);
    const float g0 = lds_bf16(ga), g1 = lds_bf16(ga + 16);
    const unsigned routed = lds_u32(sb + SM_INFO + 4);
    const uint32_t par = lds_u32(sb + SM_INFO) & 1, tmask = (lane & 3) ? ~0u : ~1u, tbit = (lane & 3) ? 0u : par;
    mbar_wait(BAR(B_KVB), 0);
    if (tid == 0) TSTAMP(7);
    if (wg != half) mbar_wait(BAR(B_OP + half * 2), 0);
    {
      float nd[4][20];
#pragma unroll
      for (int u = 0; u < 4; u++)
#pragma unroll
        for (int i = 0; i < 16; i++) asm volatile("" : "+r"(pq[u][i]) :: "memory");
      auto num = [&](int mb, int k0, int k1) {
#pragma unroll
        for (int kk = k0; kk < k1; kk++)
#pragma unroll
          for (int h = 0; h < 2; h++) {
            const int u = mb * 2 + h;
            wgmma_rs_n40<1, H64>(nd[u], pq[u][4 * kk], pq[u][4 * kk + 1], pq[u][4 * kk + 2], pq[u][4 * kk + 3],
                                 dlo(SB0 + SM_KVB + h * 4096 + kk * 1024, 8192 - h * 4096 + h * 16), kk != 0);
          }
        wgmma_commit();
      };
      wgmma_fence();
      num(0, 0, 4);
#pragma unroll
      for (int mb = 0; mb < 2; mb++) {
        wgmma_wait<0>();
        fence_regs(nd[2 * mb]); fence_regs(nd[2 * mb + 1]);
        if (mb == 0) { wgmma_fence(); num(1, 0, 4); }
        if (tid == 0 && mb == 0) TSTAMP(18);
#pragma unroll
        for (int h = 0; h < 2; h++) {
          const int u = mb * 2 + h;
          const float i0 = gt[2 * mb] * rcp(fmaf(sc[2 * u], 1e-6f, nd[u][16])), i1 = gt[2 * mb + 1] * rcp(fmaf(sc[2 * u + 1], 1e-6f, nd[u][18]));
#pragma unroll
          for (int jj = 0; jj < 2; jj++) {
            const int o = jj * 8;
            stsm4(sb + SM_O + (wg ^ half) * 16384 + ((trow & 63) + mb * 64) * 128 + (((h * 4 + 2 * jj + chi) ^ (trow & 7)) << 4),
                  (pack_bf16(nd[u][o] * i0, nd[u][o + 1] * i0) & tmask) | tbit, (pack_bf16(nd[u][o + 2] * i1, nd[u][o + 3] * i1) & tmask) | tbit,
                  pack_bf16(nd[u][o + 4] * i0, nd[u][o + 5] * i0), pack_bf16(nd[u][o + 6] * i1, nd[u][o + 7] * i1));
          }
        }
        fence_async_smem();
        __syncwarp();
        if (elect_one()) mbar_arrive(BAR(B_OP + wg * 2 + mb));
      }
#pragma unroll
      for (int u = 0; u < 4; u++)
#pragma unroll
        for (int i = 0; i < 16; i++) asm volatile("" :: "r"(pq[u][i]) : "memory");
    }
    if (tid == 0) TSTAMP(8);
    uint32_t stale = 0;
    {
      const uint32_t ca = sb - SB0 - (dlo(0, 16) << 4) + wi * 2048 + (lane >> 2) * 128 + ((((lane & 3) * 2) ^ (lane >> 2)) << 4);
      const uint32_t da_end = dlo(SB0 + SM_RA + NA2 * 16384, 16) + wq * 512, f_end = BAR(B_F2 + wq * 16 + 16);
      uint32_t da = da_end - 1024, db = dlo(SB0 + SM_RB + 4 * 16384, 8192), f = f_end - 128;
      uint32_t xs[32];
#pragma unroll
      for (int i = 0; i < 2; i++) {
        mbar_wait(f + i * 8, 0);
        wgmma_fence();
#pragma unroll
        for (int k = 0; k < 4; k++) wgmma_ss_n128<0, 1, H128, H128>(acc, da - i * 4096 + k * 2, db + i * 1024 + k * 128, (i | k) != 0);
        wgmma_commit();
        if (i == 0) {
#pragma unroll
          for (int jj = 0; jj < 8; jj++)
            ldsm4(((sb + SM_XT + xo) ^ ((jj & 3) << 5)) + (jj >> 2) * 16384, xs[4 * jj], xs[4 * jj + 1], xs[4 * jj + 2], xs[4 * jj + 3]);
          fence_async_smem();
          __syncwarp();
          if (elect_one()) mbar_arrive_cluster((wq << 24) + SB0 + SM_BAR + 8 * (B_GO + 3));
        }
      }
      const float og0 = round_bf16(1.0f - g0), og1 = round_bf16(1.0f - g1);
      da -= 3072; db += 2048; f += 16;
      wgmma_wait<0>();
      fence_regs(acc);
      uint32_t dn = SB0 + SM_BAR + (wi ? (wq << 24) + 8 * (B_GO + NA2) : (rank << 24) + 8 * B_DB);
      if (wi < 2 && elect_one()) mbar_arrive_cluster(dn);
#pragma unroll
      for (int i = 0; i < 32; i++) { acc[2 * i] = fmaf((i & 1) ? og1 : og0, bf_lo(xs[i]), acc[2 * i]); acc[2 * i + 1] = fmaf((i & 1) ? og1 : og0, bf_hi(xs[i]), acc[2 * i + 1]); }
      fence_regs(acc);
      bool got = false;
#pragma unroll 1
      do {
        if (!got) mbar_wait(f, 0);
        wgmma_fence();
        wgmma_ss_n128<0, 1, H128, H128>(acc, da, db, 1);
        const uint32_t ta = ca + (da << 4), t0 = lds_u32(ta), t1 = lds_u32(ta + 1024);
        got = mbar_test(f + 8, 0);
#pragma unroll
        for (int k = 1; k < 4; k++) wgmma_ss_n128<0, 1, H128, H128>(acc, da + k * 2, db + k * 128, 1);
        wgmma_commit();
        da += 1024; if (da == da_end) da -= NA2 * 1024;
        db += 1024; if (db == dlo(SB0 + SM_RB + NB2 * 16384, 8192)) db -= NB2 * 1024;
        f += 8;
        stale |= (t0 ^ par) | (t1 ^ par);
        if (LEAD2 && wq == 0 && wi == 2 && f == f_end - 8 * LEAD_AT && elect_one()) mbar_arrive(BAR(B_F2 + 32 - LEAD2));
        wgmma_wait<1>();
        dn += 8;
        if (wi < 2 && f <= f_end - 32 && elect_one()) mbar_arrive_cluster(dn);
      } while (f != f_end);
      if (__builtin_expect((routed >> 6) == tg * 4 + half * 2 + wq && EXPT != 12, 0)) {
        const unsigned r = (routed & 63) - wi * 16 - (lane >> 2);
        const uint32_t one = (lane & 3) ? 0u : 0x3f80u;
        mbar_wait_bounded(BAR(B_Y), 0);
        wgmma_fence();
        wgmma_rs_n128<1, H128>(acc, r == 0 ? one : 0u, r == 8 ? one : 0u, 0, 0, dlo(SB0 + SM_UPD, 2048), 1);
        wgmma_commit();
      }
      const uint32_t xa = sb + SM_RA + xo, xt = sb + SM_RA + wq * 8192 + wi * 2048;
      const int orow = tg * 256 + half * 128 + wq * 64 + wi * 16;
      const bool redo = __any_sync(0xffffffffu, stale & 1);
      wgmma_wait<0>();
      fence_regs(acc);
      if (wi == 0 && lane == 0) TSTAMP(wq ? 25 : 11);
      stage_out<0, 4>(acc, xa);
      fence_async_smem();
      __syncwarp();
      if (!redo && elect_one()) tma_store_2d(&maps.out, xt, ct * 128, orow);
      stage_out<4, 8>(acc, xa);
      if (__builtin_expect(redo, 0))
        redo_rows(x, wo, sb, b, wq, xa);
      fence_async_smem();
      __syncwarp();
      if (elect_one()) {
        tma_store_2d(&maps.out, xt + 16384, ct * 128 + 64, orow);
        if (redo) tma_store_2d(&maps.out, xt, ct * 128, orow);
      }
      bulk_commit();
      bulk_wait0_read();
    }
  }
}

typedef CUresult (*PFN_encodeTiled)(CUtensorMap*, CUtensorMapDataType, cuuint32_t, void*, const cuuint64_t*, const cuuint64_t*,
                                    const cuuint32_t*, const cuuint32_t*, CUtensorMapInterleave, CUtensorMapSwizzle,
                                    CUtensorMapL2promotion, CUtensorMapFloatOOBfill);
static void make_map(PFN_encodeTiled fn, CUtensorMap* m, const void* ptr, uint64_t rows, uint64_t cols, uint32_t brows, uint32_t bcols,
                     CUtensorMapSwizzle sw, CUtensorMapL2promotion prom) {
  cuuint64_t dims[2] = {cols, rows}; cuuint64_t strides[1] = {cols * 2}; cuuint32_t box[2] = {bcols, brows}; cuuint32_t es[2] = {1, 1};
  fn(m, CU_TENSOR_MAP_DATA_TYPE_BFLOAT16, 2, const_cast<void*>(ptr), dims, strides, box, es, CU_TENSOR_MAP_INTERLEAVE_NONE, sw, prom,
     CU_TENSOR_MAP_FLOAT_OOB_FILL_NONE);
}

extern "C" void kernel_launch(void* const* d_in, const int* in_sizes, int n_in, void* d_out, int out_size) {
  const __nv_bfloat16* x = (const __nv_bfloat16*)d_in[0];
  const __nv_bfloat16* wqkv = (const __nv_bfloat16*)d_in[1];
  const __nv_bfloat16* wphi = (const __nv_bfloat16*)d_in[2];
  const __nv_bfloat16* wo = (const __nv_bfloat16*)d_in[3];
  const __nv_bfloat16* w_r = (const __nv_bfloat16*)d_in[5];
  const __nv_bfloat16* w_gate = (const __nv_bfloat16*)d_in[6];
  const __nv_bfloat16* w_up = (const __nv_bfloat16*)d_in[7];
  const __nv_bfloat16* w_down = (const __nv_bfloat16*)d_in[8];
  const __nv_bfloat16* gate_w = (const __nv_bfloat16*)d_in[9];
  void* fp = nullptr; cudaDriverEntryPointQueryResult qr;
  cudaGetDriverEntryPoint("cuTensorMapEncodeTiled", &fp, cudaEnableDefault, &qr);
  PFN_encodeTiled fn = (PFN_encodeTiled)fp;
  Maps m;
  const CUtensorMapL2promotion P128 = CU_TENSOR_MAP_L2_PROMOTION_L2_128B;
  make_map(fn, &m.x, x, S_, D_, 128, 32, CU_TENSOR_MAP_SWIZZLE_64B, P128);
  {
    cuuint64_t dims[3] = {D_, D_, 3}; cuuint64_t strides[2] = {3 * D_ * 2, D_ * 2}; cuuint32_t box[3] = {64, 32, 3}; cuuint32_t es[3] = {1, 1, 1};
    fn(&m.w, CU_TENSOR_MAP_DATA_TYPE_BFLOAT16, 3, (void*)wqkv, dims, strides, box, es, CU_TENSOR_MAP_INTERLEAVE_NONE,
       CU_TENSOR_MAP_SWIZZLE_128B, P128, CU_TENSOR_MAP_FLOAT_OOB_FILL_NONE);
  }
  {
    cuuint64_t dims[3] = {64, D_, 16}; cuuint64_t strides[2] = {D_ * 2, 128}; cuuint32_t box[3] = {64, 64, 2}; cuuint32_t es[3] = {1, 1, 1};
    fn(&m.wo, CU_TENSOR_MAP_DATA_TYPE_BFLOAT16, 3, (void*)wo, dims, strides, box, es, CU_TENSOR_MAP_INTERLEAVE_NONE,
       CU_TENSOR_MAP_SWIZZLE_128B, P128, CU_TENSOR_MAP_FLOAT_OOB_FILL_NONE);
  }
  make_map(fn, &m.wphi, wphi, 1024, 32, 64, 32, CU_TENSOR_MAP_SWIZZLE_64B, P128);
  for (int i = 0; i < 3; i++) {
    cuuint64_t dims[3] = {i < 2 ? (cuuint64_t)F_ : 64, i < 2 ? (cuuint64_t)16 : F_, i < 2 ? (cuuint64_t)64 : 16};
    cuuint64_t strides[2] = {i < 2 ? (cuuint64_t)F_ * 2 : D_ * 2, i < 2 ? (cuuint64_t)F_ * 32 : 128};
    cuuint32_t box[3] = {64, i < 2 ? 16u : 4u, i < 2 ? 4u : 16u}; cuuint32_t es[3] = {1, 1, 1};
    fn(&m.wg + i, CU_TENSOR_MAP_DATA_TYPE_BFLOAT16, 3, (void*)(i == 0 ? w_gate : i == 1 ? w_up : w_down), dims, strides, box, es,
       CU_TENSOR_MAP_INTERLEAVE_NONE, CU_TENSOR_MAP_SWIZZLE_NONE, P128, CU_TENSOR_MAP_FLOAT_OOB_FILL_NONE);
  }
  make_map(fn, &m.xt, x, S_, D_, 64, 64, CU_TENSOR_MAP_SWIZZLE_128B, P128);
  make_map(fn, &m.out, d_out, S_, D_, 16, 64, CU_TENSOR_MAP_SWIZZLE_128B, P128);
  make_map(fn, &m.xr, x, S_, D_, 16, 128, CU_TENSOR_MAP_SWIZZLE_NONE, P128);
  make_map(fn, &m.tg, w_gate, D_, F_, 64, 64, CU_TENSOR_MAP_SWIZZLE_NONE, P128);
  make_map(fn, &m.tu, w_up, D_, F_, 64, 64, CU_TENSOR_MAP_SWIZZLE_NONE, P128);
  make_map(fn, &m.td, w_down, F_ * 16, 64, 64, 64, CU_TENSOR_MAP_SWIZZLE_NONE, P128);
  make_map(fn, &m.to, wo, D_ * 16, 64, 64, 64, CU_TENSOR_MAP_SWIZZLE_NONE, P128);
  cudaFuncSetAttribute(fused_kernel, cudaFuncAttributeMaxDynamicSharedMemorySize, SM_TOTAL);
  int dev = 0, sms = 0;
  cudaGetDevice(&dev);
  cudaDeviceGetAttribute(&sms, cudaDevAttrMultiProcessorCount, dev);
  const int by_smid = BY_SMID && sms == NCTA + 4;
  fused_kernel<<<by_smid ? NCTA + 4 : NCTA + 2, 512, SM_TOTAL>>>(m, x, wo, w_r, gate_w, by_smid);
}
```
